```python
import torch

def _softmax(x, axis=-1):
    return torch.softmax(x, dim=axis)

def _gelu(x):
    return torch.nn.functional.gelu(x, approximate='tanh')

def _silu(x):
    return torch.nn.functional.silu(x)

def _sigmoid(x):
    return torch.sigmoid(x)

def _layernorm(x, axis=-1, eps=1e-05):
    m = x.mean(dim=axis, keepdim=True)
    v = x.var(dim=axis, keepdim=True, unbiased=False)
    return (x - m) / torch.sqrt(v + eps)

def _scatter_add(tgt, idx, src, axis=0):
    return tgt.clone().index_add_(axis, idx, src)

def _segment_sum(src, seg, n):
    out = torch.zeros((n,) + src.shape[1:], dtype=src.dtype)
    return out.index_add_(0, seg, src)

def _pad(x, pw):
    flat = tuple((v for pair in reversed(pw) for v in pair))
    return torch.nn.functional.pad(x, flat)
kernel_name = 'interleave_layers__memory_aug_recurrent_mem_tr__glu_gated_glu__prompt'

def setup_inputs():

    _w = lambda a: (lambda t: t.to(torch.bfloat16) if t.is_floating_point() else t)(torch.as_tensor(a))

    def _A_setup():
        B, S, Dm = (1, 2048, 640)
        H, Dh = (32, 192)
        M, seg = (8, 32)
        seg = min(seg, S)
        S = S // seg * seg
        return {'x': _w((lambda *s: torch.randn(*s, dtype=torch.bfloat16) * 0.05)(B, S, Dm)), 'mem0': _w((lambda *s: torch.randn(*s, dtype=torch.bfloat16) * 0.8)(B, M, Dm)), 'Wq': _w((lambda *s: torch.randn(*s, dtype=torch.bfloat16) * 0.8)(Dm, H, Dh) * Dm ** (-0.5)), 'Wk': _w((lambda *s: torch.randn(*s, dtype=torch.bfloat16) * 0.8)(Dm, H, Dh) * Dm ** (-0.5)), 'Wv': _w((lambda *s: torch.randn(*s, dtype=torch.bfloat16) * 0.8)(Dm, H, Dh) * Dm ** (-0.5)), 'Wo': _w((lambda *s: torch.randn(*s, dtype=torch.bfloat16) * 0.8)(H, Dh, Dm) * (H * Dh) ** (-0.5)), 'seg_len': seg}
    _A_in = _A_setup()

    def _B_setup():
        B, S, D, F = (1, 2048, 640, 1536)
        return {'x': _w((lambda *s: torch.randn(*s, dtype=torch.bfloat16) * 0.05)(B, S, D)), 'w_gate': _w((lambda *s: torch.randn(*s, dtype=torch.bfloat16) * 0.05)(D, F)), 'w_up': _w((lambda *s: torch.randn(*s, dtype=torch.bfloat16) * 0.05)(D, F)), 'w_down': _w((lambda *s: torch.randn(*s, dtype=torch.bfloat16) * 0.05)(F, D))}
    _B_in = _B_setup()
    return {'A_x': _A_in['x'], 'A_mem0': _A_in['mem0'], 'A_Wq': _A_in['Wq'], 'A_Wk': _A_in['Wk'], 'A_Wv': _A_in['Wv'], 'A_Wo': _A_in['Wo'], 'A_seg_len': _A_in['seg_len'], 'B_x': _B_in['x'], 'B_w_gate': _B_in['w_gate'], 'B_w_up': _B_in['w_up'], 'B_w_down': _B_in['w_down']}

def reference(A_x, A_mem0, A_Wq, A_Wk, A_Wv, A_Wo, A_seg_len, B_x, B_w_gate, B_w_up, B_w_down):

    def _A_ref(x, mem0, Wq, Wk, Wv, Wo, seg_len):
        B, S, Dm = x.shape
        H, Dh = (Wq.shape[1], Wq.shape[2])
        M = mem0.shape[1]
        scale = Dh ** (-0.5)
        n_seg = S // seg_len
        L = M + seg_len
        idx = torch.arange(L)
        mask = (idx[:, None] < M) | (idx[:, None] >= idx[None, :])
        mem = mem0
        outs = []
        for s in range(n_seg):
            xs = x[:, s * seg_len:(s + 1) * seg_len, :].clone()
            h = torch.concatenate([mem, xs], axis=1)
            q = torch.einsum('btd,dhe->bhte', h, Wq)
            k = torch.einsum('btd,dhe->bhte', h, Wk)
            v = torch.einsum('btd,dhe->bhte', h, Wv)
            scores = torch.einsum('bhqe,bhke->bhqk', q, k) * scale
            scores = torch.where(mask[None, None], scores, -1000000000.0)
            p = _softmax(scores, axis=-1)
            o = torch.einsum('bhqk,bhke->bhqe', p, v)
            o = torch.einsum('bhte,hed->btd', o, Wo)
            mem = o[:, :M, :].clone()
            outs.append(o[:, M:, :])
        return torch.concatenate(outs, axis=1)

    def _B_ref(x, w_gate, w_up, w_down):
        g = torch.einsum('bsd,df->bsf', x, w_gate)
        u = torch.einsum('bsd,df->bsf', x, w_up)
        h = _sigmoid(g) * u
        return torch.einsum('bsf,fd->bsd', h, w_down)
    x = A_x
    x = x + _A_ref(_layernorm(x, axis=-1), A_mem0, A_Wq, A_Wk, A_Wv, A_Wo, A_seg_len)
    x = x + _B_ref(_layernorm(x, axis=-1), B_w_gate, B_w_up, B_w_down)
    x = x + _A_ref(_layernorm(x, axis=-1), A_mem0, A_Wq, A_Wk, A_Wv, A_Wo, A_seg_len)
    x = x + _B_ref(_layernorm(x, axis=-1), B_w_gate, B_w_up, B_w_down)
    return x
```

```cpp
#include <cuda_runtime.h>
#include <cuda_bf16.h>
#include <cuda.h>
#include <stdint.h>
#include <stdlib.h>

constexpr int SEQ = 2048, DM = 640, NH = 32, DH = 192, HD = NH * DH, FF = 1536;
constexpr int NSEG = 64, SEGL = 32, NMEM = 8;
constexpr int NBLK = 16;

#define DI __device__ __forceinline__

DI uint32_t smem_base() {
  extern __shared__ __align__(1024) unsigned char smem_raw[];
  uint32_t a;
  asm volatile("{.reg .u64 t; cvta.to.shared.u64 t, %1; cvt.u32.u64 %0, t;}" : "=r"(a) : "l"(smem_raw));
  return a;
}
DI uint32_t mapa(uint32_t a, uint32_t r) {
  uint32_t o;
  asm("mapa.shared::cluster.u32 %0, %1, %2;" : "=r"(o) : "r"(a), "r"(r));
  return o;
}
DI void mbar_init(uint32_t bar, uint32_t cnt) { asm volatile("mbarrier.init.shared::cta.b64 [%0], %1;" ::"r"(bar), "r"(cnt) : "memory"); }
DI void mbar_arrive(uint32_t bar) { asm volatile("mbarrier.arrive.shared::cta.b64 _, [%0];" ::"r"(bar) : "memory"); }
DI void mbar_arrive_remote(uint32_t bar) { asm volatile("mbarrier.arrive.release.cluster.shared::cluster.b64 _, [%0];" ::"r"(bar) : "memory"); }
DI void mbar_expect(uint32_t bar, uint32_t tx) { asm volatile("mbarrier.arrive.expect_tx.shared::cta.b64 _, [%0], %1;" ::"r"(bar), "r"(tx) : "memory"); }
DI void mbar_arrive_if(bool p, uint32_t bar) { asm volatile("{.reg .pred p; setp.ne.b32 p, %1, 0; @p mbarrier.arrive.shared::cta.b64 _, [%0];}" ::"r"(bar), "r"((int)p) : "memory"); }
DI void mbar_arrive_if(bool p, uint32_t bar, uint32_t cnt) {
  asm volatile("{.reg .pred p; setp.ne.b32 p, %1, 0; @p mbarrier.arrive.shared::cta.b64 _, [%0], %2;}" ::"r"(bar), "r"((int)p), "r"(cnt) : "memory");
}
DI void mbar_expect_if(bool p, uint32_t bar, uint32_t tx) {
  asm volatile("{.reg .pred p; setp.ne.b32 p, %2, 0; @p mbarrier.arrive.expect_tx.shared::cta.b64 _, [%0], %1;}" ::"r"(bar), "r"(tx), "r"((int)p) : "memory");
}
DI bool mbar_test(uint32_t bar, uint32_t par) {
  uint32_t ok;
  asm volatile("{.reg .pred p; mbarrier.test_wait.parity.shared::cta.b64 p, [%1], %2; selp.u32 %0, 1, 0, p;}" : "=r"(ok) : "r"(bar), "r"(par) : "memory");
  return ok;
}
DI void mbar_wait(uint32_t bar, uint32_t par) {
  asm volatile(
      "{.reg .pred p;\n"
      "LOOP:\n"
      "mbarrier.try_wait.parity.shared::cta.b64 p, [%0], %1;\n"
      "@!p bra LOOP;\n}" ::"r"(bar), "r"(par) : "memory");
}
DI void mbar_wait_wd(uint32_t bar, uint32_t par) {
  asm volatile(
      "{.reg .pred p; .reg .u32 c;\n"
      "mov.u32 c, 0;\n"
      "LOOP:\n"
      "mbarrier.try_wait.parity.shared::cta.b64 p, [%0], %1;\n"
      "@p bra DONE;\n"
      "add.u32 c, c, 1;\n"
      "setp.lt.u32 p, c, 4000000;\n"
      "@p bra LOOP;\n"
      "trap;\n"
      "DONE:\n}" ::"r"(bar), "r"(par) : "memory");
}
DI void fence_async_smem() { asm volatile("fence.proxy.async.shared::cta;" ::: "memory"); }
DI void fence_async_global() { asm volatile("fence.proxy.async.global;" ::: "memory"); }
DI void bar_sync(int id, int n) { asm volatile("bar.sync %0, %1;" ::"r"(id), "r"(n) : "memory"); }
DI void bar_arrive(int id, int n) { asm volatile("bar.arrive %0, %1;" ::"r"(id), "r"(n) : "memory"); }
DI void cluster_sync() { asm volatile("barrier.cluster.arrive.release.aligned; barrier.cluster.wait.acquire.aligned;" ::: "memory"); }
DI bool elect_one() {
  uint32_t p;
  asm volatile("{.reg .pred p; elect.sync _|p, 0xffffffff; selp.u32 %0, 1, 0, p;}" : "=r"(p));
  return p;
}
DI void bulk_g2s(uint32_t dst, const void* src, uint32_t bytes, uint32_t bar) {
  asm volatile("cp.async.bulk.shared::cluster.global.mbarrier::complete_tx::bytes [%0], [%1], %2, [%3];" ::"r"(dst), "l"(src), "r"(bytes), "r"(bar) : "memory");
}
DI void bulk_g2s_mc(uint32_t dst, const void* src, uint32_t bytes, uint32_t bar, uint16_t mask) {
  asm volatile("cp.async.bulk.shared::cluster.global.mbarrier::complete_tx::bytes.multicast::cluster [%0], [%1], %2, [%3], %4;" ::"r"(dst), "l"(src), "r"(bytes), "r"(bar), "h"(mask) : "memory");
}
DI void bulk_s2s(uint32_t dst, uint32_t src, uint32_t bytes, uint32_t bar) {
  asm volatile("cp.async.bulk.shared::cluster.shared::cta.mbarrier::complete_tx::bytes [%0], [%1], %2, [%3];" ::"r"(dst), "r"(src), "r"(bytes), "r"(bar) : "memory");
}
DI void tma_2d(uint32_t dst, const CUtensorMap* map, int c0, int c1, uint32_t bar) {
  asm volatile("cp.async.bulk.tensor.2d.shared::cluster.global.mbarrier::complete_tx::bytes [%0], [%1, {%3, %4}], [%2];" ::"r"(dst), "l"(map), "r"(bar), "r"(c0), "r"(c1) : "memory");
}
DI void st_async4(uint32_t a, uint32_t x, uint32_t y, uint32_t z, uint32_t w, uint32_t bar) {
  asm volatile("st.async.shared::cluster.mbarrier::complete_tx::bytes.v4.b32 [%0], {%1,%2,%3,%4}, [%5];" ::"r"(a), "r"(x), "r"(y), "r"(z), "r"(w), "r"(bar) : "memory");
}
DI void st_async2(uint32_t a, uint32_t x, uint32_t y, uint32_t bar) {
  asm volatile("st.async.shared::cluster.mbarrier::complete_tx::bytes.v2.b32 [%0], {%1,%2}, [%3];" ::"r"(a), "r"(x), "r"(y), "r"(bar) : "memory");
}
DI void st_async1(uint32_t a, uint32_t x, uint32_t bar) {
  asm volatile("st.async.shared::cluster.mbarrier::complete_tx::bytes.b32 [%0], %1, [%2];" ::"r"(a), "r"(x), "r"(bar) : "memory");
}
DI void sts32(uint32_t a, uint32_t x) { asm volatile("st.shared.b32 [%0], %1;" ::"r"(a), "r"(x) : "memory"); }
DI void sts128(uint32_t a, uint4 v) { asm volatile("st.shared.v4.b32 [%0], {%1,%2,%3,%4};" ::"r"(a), "r"(v.x), "r"(v.y), "r"(v.z), "r"(v.w) : "memory"); }
DI uint32_t lds32(uint32_t a) { uint32_t v; asm volatile("ld.shared.b32 %0, [%1];" : "=r"(v) : "r"(a) : "memory"); return v; }
DI uint2 lds64(uint32_t a) { uint2 v; asm volatile("ld.shared.v2.b32 {%0,%1}, [%2];" : "=r"(v.x), "=r"(v.y) : "r"(a) : "memory"); return v; }
DI uint4 lds128(uint32_t a) { uint4 v; asm volatile("ld.shared.v4.b32 {%0,%1,%2,%3}, [%4];" : "=r"(v.x), "=r"(v.y), "=r"(v.z), "=r"(v.w) : "r"(a) : "memory"); return v; }
DI void stsm4(uint32_t a, uint32_t r0, uint32_t r1, uint32_t r2, uint32_t r3) {
  asm volatile("stmatrix.sync.aligned.m8n8.x4.shared.b16 [%0], {%1,%2,%3,%4};" ::"r"(a), "r"(r0), "r"(r1), "r"(r2), "r"(r3) : "memory");
}
DI void stsm2(uint32_t a, uint32_t r0, uint32_t r1) {
  asm volatile("stmatrix.sync.aligned.m8n8.x2.shared.b16 [%0], {%1,%2};" ::"r"(a), "r"(r0), "r"(r1) : "memory");
}
DI uint32_t movm(uint32_t a) { uint32_t d; asm volatile("movmatrix.sync.aligned.m8n8.trans.b16 %0, %1;" : "=r"(d) : "r"(a)); return d; }
DI uint32_t pack2(float lo, float hi) { uint32_t d; asm("cvt.rn.bf16x2.f32 %0, %1, %2;" : "=r"(d) : "f"(hi), "f"(lo)); return d; }
DI uint4 ld_rlx4(const void* p) {
  uint4 v;
  asm volatile("ld.relaxed.gpu.global.v4.u32 {%0,%1,%2,%3}, [%4];" : "=r"(v.x), "=r"(v.y), "=r"(v.z), "=r"(v.w) : "l"(p) : "memory");
  return v;
}
DI void st_rlx4(void* p, uint32_t x, uint32_t y, uint32_t z, uint32_t w) {
  asm volatile("st.relaxed.gpu.global.v4.u32 [%0], {%1,%2,%3,%4};" ::"l"(p), "r"(x), "r"(y), "r"(z), "r"(w) : "memory");
}
DI void st_rlx1(void* p, uint32_t x) { asm volatile("st.relaxed.gpu.global.u32 [%0], %1;" ::"l"(p), "r"(x) : "memory"); }
DI uint32_t ld_acq(const uint32_t* p) { uint32_t v; asm volatile("ld.acquire.gpu.global.u32 %0, [%1];" : "=r"(v) : "l"(p) : "memory"); return v; }
DI uint32_t ld_rlx(const uint32_t* p) { uint32_t v; asm volatile("ld.relaxed.gpu.global.u32 %0, [%1];" : "=r"(v) : "l"(p) : "memory"); return v; }
DI void red_rel(uint32_t* p, uint32_t v) { asm volatile("red.release.gpu.global.add.u32 [%0], %1;" ::"l"(p), "r"(v) : "memory"); }
DI void guard(uint32_t& g) { asm volatile("{.reg .pred p; add.u32 %0, %0, 1; setp.gt.u32 p, %0, 8000000; @p trap;}" : "+r"(g)); }
DI void poll_ge(const uint32_t* p, uint32_t target) {
  asm volatile(
      "{.reg .pred p; .reg .u32 v;\n"
      "LOOP:\n"
      "ld.acquire.gpu.global.u32 v, [%0];\n"
      "setp.lt.u32 p, v, %1;\n"
      "vote.sync.any.pred p, p, 0xffffffff;\n"
      "@p bra.uni LOOP;\n}" ::"l"(p), "r"(target) : "memory");
}
DI float ex2(float x) { float y; asm("ex2.approx.ftz.f32 %0, %1;" : "=f"(y) : "f"(x)); return y; }

DI void wg_fence() { asm volatile("wgmma.fence.sync.aligned;" ::: "memory"); }
DI void wg_commit() { asm volatile("wgmma.commit_group.sync.aligned;" ::: "memory"); }
template <int N> DI void wg_wait() { asm volatile("wgmma.wait_group.sync.aligned %0;" ::"n"(N) : "memory"); }
template <int N> DI void reg_fence(float* d) {
#pragma unroll
  for (int i = 0; i < N; i++) asm volatile("" : "+f"(d[i])::"memory");
}
__host__ __device__ constexpr uint64_t mkdesc(uint32_t addr, uint32_t lbo, uint32_t sbo, uint32_t sw) {
  return (uint64_t)((addr & 0x3FFFF) >> 4) | ((uint64_t)(lbo >> 4) << 16) | ((uint64_t)(sbo >> 4) << 32) | ((uint64_t)sw << 62);
}

#define ACC4(d, o) "+f"(d[o]), "+f"(d[o + 1]), "+f"(d[o + 2]), "+f"(d[o + 3])
#define ACC16(d, o) ACC4(d, o), ACC4(d, o + 4), ACC4(d, o + 8), ACC4(d, o + 12)
#define ACC20(d) ACC16(d, 0), ACC4(d, 16)

template <int TA, int TB> DI void wg_ss40(float* d, uint64_t da, uint64_t db, int sc) {
  asm volatile("{.reg .pred p; setp.ne.b32 p, %22, 0;\n"
               "wgmma.mma_async.sync.aligned.m64n40k16.f32.bf16.bf16 {%0,%1,%2,%3,%4,%5,%6,%7,%8,%9,%10,%11,%12,%13,%14,%15,%16,%17,%18,%19}, %20, %21, p, 1, 1, %23, %24;}"
               : ACC20(d) : "l"(da), "l"(db), "r"(sc), "n"(TA), "n"(TB));
}
DI void wg_rs40(float* d, uint32_t a0, uint32_t a1, uint32_t a2, uint32_t a3, uint64_t db, int sc) {
  asm volatile("{.reg .pred p; setp.ne.b32 p, %25, 0;\n"
               "wgmma.mma_async.sync.aligned.m64n40k16.f32.bf16.bf16 {%0,%1,%2,%3,%4,%5,%6,%7,%8,%9,%10,%11,%12,%13,%14,%15,%16,%17,%18,%19}, {%20,%21,%22,%23}, %24, p, 1, 1, 0;}"
               : ACC20(d) : "r"(a0), "r"(a1), "r"(a2), "r"(a3), "l"(db), "r"(sc));
}
DI void wg_rs32(float* d, uint32_t a0, uint32_t a1, uint32_t a2, uint32_t a3, uint64_t db, int sc) {
  asm volatile("{.reg .pred p; setp.ne.b32 p, %21, 0;\n"
               "wgmma.mma_async.sync.aligned.m64n32k16.f32.bf16.bf16 {%0,%1,%2,%3,%4,%5,%6,%7,%8,%9,%10,%11,%12,%13,%14,%15}, {%16,%17,%18,%19}, %20, p, 1, 1, 0;}"
               : ACC16(d, 0) : "r"(a0), "r"(a1), "r"(a2), "r"(a3), "l"(db), "r"(sc));
}
DI void wg_rs8(float* d, uint32_t a0, uint32_t a1, uint32_t a2, uint32_t a3, uint64_t db, int sc) {
  asm volatile("{.reg .pred p; setp.ne.b32 p, %9, 0;\n"
               "wgmma.mma_async.sync.aligned.m64n8k16.f32.bf16.bf16 {%0,%1,%2,%3}, {%4,%5,%6,%7}, %8, p, 1, 1, 0;}"
               : ACC4(d, 0) : "r"(a0), "r"(a1), "r"(a2), "r"(a3), "l"(db), "r"(sc));
}
DI void mma16816(float* c, const uint32_t* a, uint32_t b0, uint32_t b1) {
  asm volatile("mma.sync.aligned.m16n8k16.row.col.f32.bf16.bf16.f32 {%0,%1,%2,%3}, {%4,%5,%6,%7}, {%8,%9}, {%0,%1,%2,%3};"
               : ACC4(c, 0) : "r"(a[0]), "r"(a[1]), "r"(a[2]), "r"(a[3]), "r"(b0), "r"(b1));
}
DI void wg_ss8(float* d, uint64_t da, uint64_t db, int sc) {
  asm volatile("{.reg .pred p; setp.ne.b32 p, %6, 0;\n"
               "wgmma.mma_async.sync.aligned.m64n8k16.f32.bf16.bf16 {%0,%1,%2,%3}, %4, %5, p, 1, 1, 1, 1;}"
               : ACC4(d, 0) : "l"(da), "l"(db), "r"(sc));
}
DI void wg_rs16(float* d, uint32_t a0, uint32_t a1, uint32_t a2, uint32_t a3, uint64_t db, int sc) {
  asm volatile("{.reg .pred p; setp.ne.b32 p, %13, 0;\n"
               "wgmma.mma_async.sync.aligned.m64n16k16.f32.bf16.bf16 {%0,%1,%2,%3,%4,%5,%6,%7}, {%8,%9,%10,%11}, %12, p, 1, 1, 0;}"
               : ACC4(d, 0), ACC4(d, 4) : "r"(a0), "r"(a1), "r"(a2), "r"(a3), "l"(db), "r"(sc));
}
__device__ uint4 g_xn[2 * NSEG * 10 * 256];
__device__ uint4 g_oT[2 * NBLK * 96 * 1024];
constexpr int PART_RING = 96 * 256;
__device__ uint4 g_part[4 * PART_RING];
constexpr int MEM_OFF = 192;
__device__ __align__(8192) uint4 g_mem[5 * 2 * 2 * 512];
constexpr int C_XN = 0;
constexpr int C_O = C_XN + 2 * NBLK;
constexpr int C_HALF = C_O + 6 * 2 * NBLK;
constexpr int C_TOTAL = 512;
constexpr int CSTRIDE = 32;
__device__ uint32_t g_cnt[C_TOTAL * CSTRIDE];
constexpr uint32_t XN_TARGET = 128;

#define TRACE(c, n, i, v)
#define SLOG(i)
#define PROF(i)
#define PROFA(c)
#define PROFV(i, v)

constexpr uint32_t SMEM0 = 1024;
constexpr uint32_t SM_WK = 0, SM_WO = 81920, SM_H = 163840, SM_QT = 215040, QSTR = 1056  , SM_KT = SM_QT + 5 * QSTR + 1024,
                   SM_SR = SM_KT + 5120  , SM_PROF = SM_SR + 5760, R_SMEM = 232448,
                   SM_RED = SM_QT + 1024, SM_BAR = SM_RED + 768;
constexpr uint32_t SM_P = SM_KT, SM_OB = SM_QT + 3200;
constexpr uint32_t B_HFULL = SM_BAR, B_HEMPTY = SM_BAR + 40, B_MTRY = SM_BAR + 80, B_W = SM_BAR + 112, B_SR = B_W + 32,
                   B_PMEM = B_SR + 24, B_PTOK = B_SR + 32, B_OB = B_SR + 40, B_OPD = B_SR + 48, B_RFREE = B_SR + 56,
                   B_GATE = B_SR + 64, B_PSUM = B_SR + 72, B_END = B_SR + 80, B_PVI = B_SR + 88,
                   B_OPI = B_SR + 96, B_OTOK = B_SR + 112, SM_TOPI = B_SR + 128,
                   SM_RS = SM_QT + 2 * QSTR + 1024;
static_assert(SM_TOPI + 8 <= SM_QT + 2 * QSTR, "barriers must fit the unused q row group");

struct RParams {
  uint64_t dH, dWK, dWO, dQT, dKT, dP, dOB[6];
  const char* w[4];
  int nslots, d3, pn, moff, ds, dh;
  int d2[10], d1[8];
  uint32_t slot[2 * NSEG];
};
static void r_fill_desc(RParams& p) {
  p.dH = mkdesc(SMEM0 + SM_H, 128, 2048, 0);
  p.dWK = mkdesc(SMEM0 + SM_WK, 1024, 1024, 1);
  p.dWO = mkdesc(SMEM0 + SM_WO, 1024, 1024, 1);
  for (int i = 0; i < 6; i++) p.dOB[i] = mkdesc(SMEM0 + SM_OB + (i < 3 ? 0 : (i - 3) * 1024), 128, 128, 0);
  p.dQT = mkdesc(SMEM0 + SM_QT, 128, QSTR, 0);
  p.dKT = mkdesc(SMEM0 + SM_KT, 128, 1024, 0);
  p.dP = mkdesc(SMEM0 + SM_P, 128, 640, 0);
}
DI uint64_t dadd(uint64_t d, int bytes) {
  uint64_t r;
  asm volatile("add.u64 %0, %1, %2;" : "=l"(r) : "l"(d), "l"((long long)(bytes / 16)));
  return r;
}
template <int BYTES> DI void dstep(uint64_t& d) { asm volatile("add.u64 %0, %0, %1;" : "+l"(d) : "n"((long long)(BYTES / 16))); }
__host__ __device__ constexpr int hoff(int ks) { return (ks >> 3) * 10240 + (ks & 7) * 256; }

DI int opaque(int v) { asm volatile("" : "+r"(v)); return v; }
DI uint32_t pin(uint32_t v, int lane) { return __shfl_sync(~0u, v + (lane >> 5), lane); }
DI char* pin(char* p, int lane) { return (char*)__shfl_sync(~0u, (unsigned long long)p, lane); }
DI float blo(uint32_t w) { return __uint_as_float(w << 16); }
DI float bhi(uint32_t w) { return __uint_as_float(w & 0xffff0000u); }
#define R_FB 1
#define PIN_DST 1
#define RG0 232
#define RG1 216
#define RG2 40
#define RG3 24
DI void ldsm4t(uint32_t* r, uint32_t a) {
  asm volatile("ldmatrix.sync.aligned.m8n8.x4.trans.shared.b16 {%0,%1,%2,%3}, [%4];" : "=r"(r[0]), "=r"(r[1]), "=r"(r[2]), "=r"(r[3]) : "r"(a) : "memory");
}
DI void st_tagged(void* p, float a, float b, uint32_t keep, uint32_t tagbit) {
  asm volatile("{.reg .b32 t; cvt.rn.bf16x2.f32 t, %2, %1; lop3.b32 t, t, %3, %4, 0xea; st.relaxed.gpu.global.b32 [%0], t;}" ::"l"(p), "f"(a), "f"(b),
               "r"(keep), "r"(tagbit) : "memory");
}
DI uint32_t lop_bad(uint32_t a, uint32_t b, uint32_t m) { uint32_t d; asm("lop3.b32 %0, %1, %2, %3, 0x7e;" : "=r"(d) : "r"(a), "r"(b), "r"(m)); return d; }
DI uint32_t lop_or3(uint32_t a, uint32_t b, uint32_t c) { uint32_t d; asm("lop3.b32 %0, %1, %2, %3, 0xfe;" : "=r"(d) : "r"(a), "r"(b), "r"(c)); return d; }
DI uint32_t clk() { uint32_t t; asm volatile("mov.u32 %0, %%clock;" : "=r"(t)); return t; }
DI void spin(uint32_t cyc) { const uint32_t t0 = clk(); while (__any_sync(~0u, clk() - t0 < cyc)) {} }
template <int NL> DI float2 poll_sum(const uint32_t* src, uint32_t tag, uint32_t even, uint32_t& g) {
  uint32_t r[NL];
  while (true) {
#pragma unroll
    for (int i = 0; i < NL; i++) r[i] = ld_rlx(src + i * 32);
    uint32_t bad = lop_or3(lop_bad(r[0], r[1], tag), lop_bad(r[2], r[3], tag), lop_bad(r[4], r[5], tag));
    if (NL == 12) bad = lop_or3(bad, lop_bad(r[6], r[7], tag), lop_bad(r[8], r[9], tag));
    asm volatile("lop3.b32 %0, %0, %1, %2, 0xa8;" : "+r"(bad) : "r"(lop_bad(r[NL - 2], r[NL - 1], tag)), "r"(even));
    if (!__any_sync(~0u, bad)) break;
    g++;
  }
  float x[NL / 2], y[NL / 2];
#pragma unroll
  for (int i = 0; i < NL / 2; i++) { x[i] = blo(r[2 * i]) + blo(r[2 * i + 1]); y[i] = bhi(r[2 * i]) + bhi(r[2 * i + 1]); }
  float2 u = make_float2((x[0] + x[1]) + (x[2] + x[3]), (y[0] + y[1]) + (y[2] + y[3]));
  if (NL == 12) { u.x += x[4] + x[5]; u.y += y[4] + y[5]; }
  return u;
}

__global__ void __launch_bounds__(512, 1)
r_kernel(const __grid_constant__ CUtensorMap mapWq, const __grid_constant__ CUtensorMap mapWk, const __grid_constant__ CUtensorMap mapWv,
         const __grid_constant__ CUtensorMap mapWo, const __grid_constant__ RParams prm) {
  const uint32_t sb = smem_base();
  const int wid = __shfl_sync(~0u, threadIdx.x >> 5, 0);
  const int lane0 = __shfl_sync(~0u, threadIdx.x & 31, threadIdx.x & 31);
  const int lane = lane0;
  const int warp = wid & 3, wg = wid >> 2;
  const uint32_t rank = blockIdx.x, head = blockIdx.y, cta = head * 3 + rank;
  const uint32_t peer1 = mapa(sb, rank == 2 ? 0 : rank + 1), peer2 = mapa(sb, rank == 0 ? 2 : rank - 1);
  const int nslots = prm.nslots;

  SLOG(0);
  if (threadIdx.x == 0) {
    if ((sb & 0x3FFFF) != SMEM0) __trap();
    for (int c = 0; c < 5; c++) { mbar_init(sb + B_HFULL + 8 * c, 2); mbar_init(sb + B_HEMPTY + 8 * c, c == 4 ? 8 : 4); }
    for (int c = 0; c < 11; c++) mbar_init(sb + B_MTRY + 8 * c, 1);
    mbar_init(sb + B_PTOK, rank == 0 ? 3 : 2); mbar_init(sb + B_OB, 5); mbar_init(sb + B_OPD, 4);
    mbar_init(sb + B_OPI, 1); mbar_init(sb + B_OPI + 8, 1); mbar_init(sb + B_RFREE, 1); mbar_init(sb + B_GATE, 1); mbar_init(sb + B_PMEM, 2); mbar_init(sb + B_PSUM, 2); mbar_init(sb + B_PVI, 1); mbar_init(sb + B_OTOK, 4); mbar_init(sb + B_OTOK + 8, 4); mbar_init(sb + B_END, 15);
    asm volatile("fence.mbarrier_init.release.cluster;" ::: "memory");
    fence_async_smem();
  }
  cluster_sync();
  asm volatile("griddepcontrol.launch_dependents;");

  if (wg == 0) {
    asm volatile("setmaxnreg.inc.sync.aligned.u32 %0;" ::"n"(RG0));
    uint32_t wq[160];
    SLOG(1);
    mbar_wait(sb + B_W, 0);
    SLOG(2);
    {
      const uint32_t ld_off = ((lane >> 4) * 8 + (lane & 7)) * 128 + (((2 * warp + ((lane >> 3) & 1)) ^ (lane & 7)) << 4);
#pragma unroll
      for (int ks = 0; ks < 40; ks++) ldsm4t(wq + 4 * ks, sb + SM_WO + ks * 2048 + ld_off);
    }
    fence_async_smem();
    bar_arrive(5, 160);
    mbar_wait(sb + B_W + 16, 0);
    SLOG(3);
    const uint32_t st_addr = pin(sb + SM_QT + (lane >> 4) * 1024 + (2 * warp + ((lane >> 3) & 1)) * 128 + (lane & 7) * 16, lane);
    const uint32_t sq_addr = pin(sb + SM_QT + (2 + (lane & 3)) * QSTR + warp * 256 + (lane >> 2) * 16, lane);
    const uint32_t to_lo = warp == 0 ? peer1 : mapa(sb, warp == 2 ? 2 : 0), to_hi = warp == 0 ? peer2 : mapa(sb, warp == 1 ? 1 : 0);
    const uint32_t sr_off = SM_SR + warp * 1920 + rank * 640, sr_bar = B_SR + warp * 8;
    const uint32_t sa0 = pin(to_lo + sr_off + lane * 16, lane), sb0 = pin(to_lo + sr_bar, lane), sa1 = pin(to_lo + sr_off + 512 + lane * 4, lane), sb1 = pin(sb0, lane);
    const uint32_t sa2 = pin(to_hi + sr_off + lane * 16, lane), sb2 = pin(to_hi + sr_bar, lane), sa3 = pin(to_hi + sr_off + 512 + lane * 4, lane), sb3 = pin(sb2, lane);
#pragma unroll 1
    for (int n = 0; n < nslots; n++) {
      const uint32_t par = n & 1;
      PROFA(warp == PW);
      float qa[20], ka[20];
      uint64_t rk = prm.dWK, rh = prm.dH, rq;
      auto K = [&](int ks) { wg_ss40<1, 0>(ka, rk, rh, ks != 0); };
      auto Q = [&](int ks, uint64_t db) { wg_rs40(qa, wq[4 * ks], wq[4 * ks + 1], wq[4 * ks + 2], wq[4 * ks + 3], db, ks != 0); };
      auto next = [&](uint64_t& d, int ks) { if ((ks & 7) == 7) dstep<10240 - 7 * 256>(d); else dstep<256>(d); };
      bool ok = true;
      mbar_wait(sb + B_HFULL, par);
#pragma unroll
      for (int g = 0; g < 20; g++) {
        if (!ok) {
          if (g <= 16 && (g & 3) == 0) mbar_wait(sb + B_HFULL + 8 * (g >> 2), par);
          mbar_wait(sb + B_GATE, 1);
        }
        if (g == 0) PROF(0);
        if (g < 19) ok = mbar_test(sb + B_GATE, 1);
        if (g < 16 && (g & 3) == 3) ok &= mbar_test(sb + B_HFULL + 8 * ((g + 1) >> 2), par);
        wg_fence();
        if (g < 16) {
#pragma unroll
          for (int ks = 2 * g; ks < 2 * g + 2; ks++) { K(ks); Q(ks, rh); dstep<2048>(rk); next(rh, ks); }
          if (g == 15) { wg_commit(); rq = rh; }
        } else {
          K(2 * g); dstep<2048>(rk); dstep<256>(rh);
          Q(16 + g, rq); dstep<256>(rq);
          K(2 * g + 1);
          if (g < 19) { dstep<2048>(rk); dstep<256>(rh); }
        }
      }
      wg_commit();
#pragma unroll
      for (int ks = 36; ks < 40; ks++) { Q(ks, rq); if (ks < 39) dstep<256>(rq); }
      wg_commit();
      wg_wait<2>();
      bar_arrive(2, 256);
      mbar_wait(sb + B_OPD, par ^ 1);
      wg_wait<1>();
      reg_fence<20>(ka);
      stsm2(st_addr + (SM_KT - SM_QT), pack2(ka[0], ka[1]), pack2(ka[2], ka[3]));
      stsm4(st_addr + (SM_KT - SM_QT) + 1024, pack2(ka[4], ka[5]), pack2(ka[6], ka[7]), pack2(ka[8], ka[9]), pack2(ka[10], ka[11]));
      stsm4(st_addr + (SM_KT - SM_QT) + 3072, pack2(ka[12], ka[13]), pack2(ka[14], ka[15]), pack2(ka[16], ka[17]), pack2(ka[18], ka[19]));
      wg_wait<0>();
      reg_fence<20>(qa);
      PROF(9);
      stsm2(st_addr, pack2(qa[0], qa[1]), pack2(qa[2], qa[3]));
      sts128(sq_addr, make_uint4(pack2(qa[4], qa[5]), pack2(qa[8], qa[9]), pack2(qa[12], qa[13]), pack2(qa[16], qa[17])));
      sts128(sq_addr + 128, make_uint4(pack2(qa[6], qa[7]), pack2(qa[10], qa[11]), pack2(qa[14], qa[15]), pack2(qa[18], qa[19])));
      mbar_arrive_if(lane == 0, sb + B_HEMPTY + 32);
      fence_async_smem();
      bar_sync(1, 128);
      PROF(1);
      wg_fence();
#pragma unroll
      for (int k = 0; k < 4; k++) wg_ss40<1, 1>(qa, dadd(prm.dQT, k * 256), dadd(prm.dKT, k * 256), k != 0);
      wg_commit();
      bar_arrive(7, 256);
      wg_wait<0>();
      reg_fence<20>(qa);
      PROF(3);
      if (warp < 3) {
        uint32_t p[5];
#pragma unroll
        for (int j = 0; j < 5; j++) p[j] = pack2(qa[4 * j], qa[4 * j + 1]);
        if (warp == 0) {
          st_async4(sa0, p[0], p[1], p[2], p[3], sb0);
          st_async4(sa2, p[0], p[1], p[2], p[3], sb2);
          st_async1(sa1, p[4], sb1);
          st_async1(sa3, p[4], sb3);
          sts128(sb + sr_off + lane * 16, make_uint4(p[0], p[1], p[2], p[3]));
          sts32(sb + sr_off + 512 + lane * 4, p[4]);
          __syncwarp();
          mbar_expect_if(lane == 0, sb + B_SR, 1280);
        } else {
          uint32_t h[5];
#pragma unroll
          for (int j = 0; j < 5; j++) h[j] = pack2(qa[4 * j + 2], qa[4 * j + 3]);
          spin(prm.d3);
          st_async4(sa0, p[0], p[1], p[2], p[3], sb0);
          st_async4(sa2, h[0], h[1], h[2], h[3], sb2);
          st_async1(sa1, p[4], sb1);
          st_async1(sa3, h[4], sb3);
        }
      }
    }
  } else if (wg == 1) {
    asm volatile("setmaxnreg.inc.sync.aligned.u32 %0;" ::"n"(RG1));
    uint32_t wv[160];
    mbar_wait(sb + B_W + 8, 0);
    SLOG(4);
    {
      const uint32_t ld_off = ((lane >> 4) * 8 + (lane & 7)) * 128 + (((2 * warp + ((lane >> 3) & 1)) ^ (lane & 7)) << 4);
#pragma unroll
      for (int ks = 0; ks < 40; ks++) ldsm4t(wv + 4 * ks, sb + SM_WO + ks * 2048 + ld_off);
    }
    fence_async_smem();
    bar_arrive(6, 160);
    const uint64_t dH = prm.dH;
    uint32_t op[8];
    const uint32_t ob_off = SM_OB + (4 * rank + warp) * 256 + lane * 4;
    const uint32_t oa0 = pin(peer1 + ob_off, lane), ob0 = pin(peer1 + B_OB, lane), oa1 = pin(peer2 + ob_off, lane), ob1 = pin(peer2 + B_OB, lane);
    const uint32_t oa2 = pin(oa0 + 128, lane), ob2 = pin(ob0, lane), oa3 = pin(oa1 + 128, lane), ob3 = pin(ob1, lane);
    const uint32_t o_loc = pin(sb + ob_off, lane), rs_addr = pin(sb + SM_RS + (lane & 3) * 8, lane);
    const uint32_t tok_off = pin((cta * 1024 + 64 * warp + (lane ^ (lane >> 3))) * 16, lane), keep = pin((lane & 1) ? ~0u : ~1u, lane);
    const uint32_t pb_off = pin((8 * rank + 2 * warp) * 4096 + head * 128 + lane * 4, lane);
    const uint32_t ph_off = pin(72 * 4096 + 2 * warp * 12288 + cta * 64 + (lane & 2) * 3072 + (lane >> 2) * 8 + (lane & 1) * 4, lane);
    auto store_tok = [&](int m, int lane) {
      const uint32_t ls = prm.slot[m] & 127, sig = prm.slot[m] >> 16;
      uint4* dst = (uint4*)((char*)(g_oT + (size_t)((ls >> 2) * (96 * 1024) + (ls & 3) * 256)) + tok_off);
      dst[0] = make_uint4(op[0], op[1], op[2], op[3]);
      dst[32] = make_uint4(op[4], op[5], op[6], op[7]);
      __syncwarp();
      mbar_arrive_if(sig && lane == 0, sb + B_OTOK + (ls >> 6) * 8);
    };
#pragma unroll 1
    for (int n = 0; n < nslots; n++) {
      const uint32_t par = n & 1;
      const int lane = opaque(lane0);
      PROFA(warp == PW);
      float va[20];
      mbar_expect_if(warp == 0 && lane == 0, sb + B_PTOK, rank == 0 ? 1280 : 1920);
      bar_sync(2, 256);
#pragma unroll
      for (int g = 0; g < 10; g++) {
        wg_fence();
#pragma unroll
        for (int ks = 4 * g; ks < 4 * g + 4; ks++) { wg_rs40(va, wv[4 * ks], wv[4 * ks + 1], wv[4 * ks + 2], wv[4 * ks + 3], dadd(dH, hoff(ks)), ks != 0); }
        wg_commit();
        if (g >= 2 && !(g & 1)) {
          wg_wait<1>();
          if (lane == 0) mbar_arrive(sb + B_HEMPTY + 8 * (g / 2 - 1));
        }
        if (g == 2) bar_sync(7, 256);
      }
      wg_wait<0>();
      reg_fence<20>(va);
      if (lane == 0) mbar_arrive(sb + B_HEMPTY + 32);
      PROF(10);
      uint32_t vf[10];
#pragma unroll
      for (int j = 0; j < 10; j++) {
        const int i = (j + 4) % 10;
        asm volatile("cvt.rn.bf16x2.f32 %0, %1, %2;" : "=r"(vf[i]) : "f"(va[2 * i + 1]), "f"(va[2 * i]));
        if (j == 5) mbar_wait(sb + B_W + 8, 0);
      }
      uint32_t z0, z1;
      asm volatile("shr.u32 %0, %2, 5; shr.u32 %1, %2, 6;" : "=r"(z0), "=r"(z1) : "r"(lane));
      const uint32_t info = prm.slot[n];
      const uint32_t tagbit = ~(info >> 1) & ~keep;
      char* const ring = (char*)(g_part + (size_t)((((info >> 5) & 2) + (info & 1)) * PART_RING));
      char* const pb = pin(ring + pb_off, lane);
      char* const ph = ring + ph_off;
      mbar_wait(sb + B_PMEM, par);
      float om[4];
      wg_fence();
      wg_rs8(om, vf[0], vf[1], vf[2], vf[3], prm.dP, 0);
      wg_rs8(om, vf[4], vf[5], vf[6], vf[7], dadd(prm.dP, 256), 1);
      wg_rs8(om, vf[8], vf[9], z0, z1, dadd(prm.dP, 512 - (128 << 16)), 1);
      wg_commit();
      {
        mbar_wait(sb + B_PSUM, par);
        const uint2 rs = lds64(rs_addr);
        wg_wait<0>();
        reg_fence<4>(om);
        const float r0 = __uint_as_float(rs.x), r1 = __uint_as_float(rs.y);
        const uint32_t b0 = pack2(om[0] * r0, om[1] * r1), b1 = pack2(om[2] * r0, om[3] * r1);
        st_async1(oa0, b0, ob0);
        st_async1(oa1, b0, ob1);
        st_async1(oa2, b1, ob2);
        st_async1(oa3, b1, ob3);
        sts32(o_loc, b0);
        sts32(o_loc + 128, b1);
        fence_async_smem();
        __syncwarp();
        mbar_arrive_if(lane == 0, sb + B_OB);
      }
      PROF(11);
      {
        float c[8];
        if (n == 0) { SLOG(5); mbar_wait(sb + B_W + 24, 0); SLOG(6); }
        mbar_wait(sb + B_OB, par);
        asm volatile("fence.proxy.async::generic.acquire.sync_restrict::shared::cluster.cluster;" ::: "memory");
        PROF(16);
        if ((info & 63) == NSEG - 1) {
          mbar_wait(sb + B_OPI + par * 8, (n >> 1) & 1);
          mbar_arrive_if(warp == 3 && lane == 0, sb + B_GATE);
        } else {
#pragma unroll
        for (int p = 0; p < 4; p++) {
          float* const cur = c + 4 * (p & 1);
          float* const prv = c + 4 * (~p & 1);
          if (p == 2) mbar_wait(sb + B_OPI + par * 8, (n >> 1) & 1);
          wg_fence();
#pragma unroll
          for (int ks = 0; ks < (p < 3 ? 12 : 4); ks++) {
            wg_ss8(cur, dadd(prm.dWO, p * 24576 + ks * 2048), dadd(prm.dOB[p < 3 ? p : 3 + rank], ks * 256), ks != 0);
            if (p == 3 && ks == 3) mbar_arrive_if(warp == 3 && lane == 0, sb + B_GATE);
            if (p > 0 && ks == 3) {
              wg_commit();
              wg_wait<1>();
              reg_fence<4>(prv);
              st_tagged(pb + (p - 1) * 98304, prv[0], prv[1], keep, tagbit);
              st_tagged(pb + (p - 1) * 98304 + 4096, prv[2], prv[3], keep, tagbit);
            }
          }
          if (p < 3) wg_commit();
        }
        wg_wait<0>();
        reg_fence<4>(c + 4);
        st_tagged(ph, c[4], c[5], keep, tagbit);
        st_tagged(ph + 12288, c[6], c[7], keep, tagbit);
        }
        PROF(17);
      }
      mbar_wait(sb + B_PTOK, par);
      PROF(12);
      {
        float ot[16];
        wg_fence();
        wg_rs32(ot, vf[0], vf[1], vf[2], vf[3], dadd(prm.dP, 640), 0);
        wg_rs32(ot, vf[4], vf[5], vf[6], vf[7], dadd(prm.dP, 640 + 256), 1);
        wg_rs32(ot, vf[8], vf[9], z0, z1, dadd(prm.dP, 640 + 512 - (128 << 16)), 1);
        wg_commit();
        wg_wait<0>();
        reg_fence<16>(ot);
#pragma unroll
        for (int i = 0; i < 8; i++) op[(i & 1) * 4 + (i >> 1)] = pack2(ot[2 * i], ot[2 * i + 1]);
      }
      if (lane == 0) mbar_arrive(sb + B_OPD);
      PROF(13);
      if (info & 128) spin(prm.ds);
      store_tok(n, lane);
    }
  } else if (wg == 2) {
    asm volatile("setmaxnreg.dec.sync.aligned.u32 %0;" ::"n"(RG2));
    if (warp == 1) {
      if (elect_one()) {
        for (int i = 0; i < 4; i++) mbar_expect(sb + B_W + 8 * i, 81920);
        for (int i = 0; i < 5; i++) tma_2d(sb + SM_WO + i * 16384, &mapWq, cta * 64, i * 128, sb + B_W);
        for (int i = 0; i < 5; i++) tma_2d(sb + SM_WK + i * 16384, &mapWk, cta * 64, i * 128, sb + B_W + 16);
      }
      bar_sync(5, 160);
      if (elect_one()) {
        for (int i = 0; i < 5; i++) tma_2d(sb + SM_WO + i * 16384, &mapWv, cta * 64, i * 128, sb + B_W + 8);
      }
      bar_sync(6, 160);
      if (elect_one()) {
        for (int i = 0; i < 10; i++)
          tma_2d(sb + SM_WO + i * 8192, &mapWo, i < 9 ? (i / 3 * 3 + rank) * 64 : 576, head * DH + (i < 9 ? i % 3 : rank) * 64, sb + B_W + 24);
      }
    }
    const uint32_t grp = warp == 1 ? 1 + rank : 4 - (rank >> 1);
    constexpr float SC = 0.07216878364870322f * 1.4426950408889634f;
    const bool split = cta >= 72;
    const uint32_t wd = split ? 72 * 16 + cta * 16 : cta * 32;
    const uint32_t src_off = pin(split ? 72 * 4096 + (cta - 72) * 6144 + warp * 1536 + (lane & 2) * 32 + (lane >> 2) * 8 + (lane & 1) * 4 : cta * 4096 + warp * 1024 + lane * 4, lane);
    const uint32_t dst_off = pin(((wd >> 9) * 8192 + prm.moff * 4 + (wd & 511) + lane) * 4, lane);
    const uint32_t red = pin(sb + SM_RED + (warp < 2 ? 0 : (warp - 1) * 256) + lane * 8, lane);
    const uint32_t fl = (warp & 2) * 8 + (lane >> 3) * 4 + (lane & 3), hf = lane & 4;
    const uint32_t s0 = pin(sb + SM_SR + fl * 16 + hf * 2, lane), s1 = pin(sb + fl * 4, lane), pd = pin(s1 + hf * 64, lane);
    const uint32_t even = pin(~lane & 1, lane);
    uint32_t nred = 0;
    const uint32_t arm = pin(warp == 0 && (lane == 5 || ((lane == 1 || lane == 2) && lane + rank != 3)) ? sb + B_SR + lane * 8 : 0, lane);
#pragma unroll 1
    for (int n = 0; n < nslots; n++) {
      const uint32_t par = n & 1;
      const int lane = opaque(lane0);
      PROFA(warp == PW2);
      const uint32_t info = prm.slot[n], s = info & 63, l = (info >> 6) & 1;
      {
        mbar_expect_if(arm, arm, lane == 5 ? 2048 : 1920);
        if (warp == 0 || warp == 3) {
          mbar_wait(sb + B_SR, par);
          PROF(4);
          const uint2 a0 = lds64(s0), a1 = lds64(s0 + 640), a2 = lds64(s0 + 1280);
          const uint32_t b0 = lds32(s1 + SM_SR + 512), b1 = lds32(s1 + SM_SR + 1152), b2 = lds32(s1 + SM_SR + 1792);
          float v[6];
          v[0] = blo(a0.x) + blo(a1.x) + blo(a2.x); v[1] = bhi(a0.x) + bhi(a1.x) + bhi(a2.x);
          v[2] = blo(a0.y) + blo(a1.y) + blo(a2.y); v[3] = bhi(a0.y) + bhi(a1.y) + bhi(a2.y);
          v[4] = blo(b0) + blo(b1) + blo(b2); v[5] = bhi(b0) + bhi(b1) + bhi(b2);
          float m = fmaxf(fmaxf(v[0], v[1]), fmaxf(v[2], v[3]));
          m = fmaxf(fmaxf(m, __shfl_xor_sync(~0u, m, 4)), fmaxf(v[4], v[5]));
          {
            const float m1 = __shfl_xor_sync(~0u, m, 1), m2 = __shfl_xor_sync(~0u, m, 2), m3 = __shfl_xor_sync(~0u, m, 3);
            m = fmaxf(fmaxf(m, m1), fmaxf(m2, m3));
          }
          const float ms = -m * SC;
#pragma unroll
          for (int i = 0; i < 6; i++) v[i] = ex2(fmaf(v[i], SC, ms));
          float sum = (v[0] + v[1]) + (v[2] + v[3]);
          const float so = __shfl_xor_sync(~0u, sum, 4);
          sts32(pd + SM_P, pack2(v[0], v[1]));
          sts32(pd + SM_P + 128, pack2(v[2], v[3]));
          sts32(s1 + SM_P + 512, pack2(v[4], v[5]));
          fence_async_smem();
          __syncwarp();
          mbar_arrive_if(lane == 0, sb + B_PMEM);
          PROF(5);
          sum += so + (v[4] + v[5]);
          {
            const float t1 = __shfl_xor_sync(~0u, sum, 1), t2 = __shfl_xor_sync(~0u, sum, 2), t3 = __shfl_xor_sync(~0u, sum, 3);
            sum = (sum + t1) + (t2 + t3);
          }
          float r;
          asm("rcp.approx.ftz.f32 %0, %1;" : "=f"(r) : "f"(sum));
          sts32(sb + SM_RS + (warp & 2) * 8 + (lane >> 3) * 4, __float_as_uint(r));
          __syncwarp();
          mbar_arrive_if(lane == 0, sb + B_PSUM);
        } else {
          if (warp + rank != 3) {
            const uint32_t src = sb + SM_SR + warp * 1920;
            mbar_wait(sb + B_SR + warp * 8, par);
            const uint4 a0 = lds128(src + lane * 16), a1 = lds128(src + 640 + lane * 16), a2 = lds128(src + 1280 + lane * 16);
            const uint32_t b0 = lds32(src + 512 + lane * 4), b1 = lds32(src + 1152 + lane * 4), b2 = lds32(src + 1792 + lane * 4);
            float v[10];
            v[0] = blo(a0.x) + blo(a1.x) + blo(a2.x); v[1] = bhi(a0.x) + bhi(a1.x) + bhi(a2.x);
            v[2] = blo(a0.y) + blo(a1.y) + blo(a2.y); v[3] = bhi(a0.y) + bhi(a1.y) + bhi(a2.y);
            v[4] = blo(a0.z) + blo(a1.z) + blo(a2.z); v[5] = bhi(a0.z) + bhi(a1.z) + bhi(a2.z);
            v[6] = blo(a0.w) + blo(a1.w) + blo(a2.w); v[7] = bhi(a0.w) + bhi(a1.w) + bhi(a2.w);
            v[8] = blo(b0) + blo(b1) + blo(b2); v[9] = bhi(b0) + bhi(b1) + bhi(b2);
            {
              const int lim = 6 + 2 * grp + (lane & 24) + ((lane >> 2) & 1) - 2 * (lane & 3);
#pragma unroll
              for (int i = 2; i < 10; i++) if ((i >> 1) * 8 + (i & 1) > lim) v[i] = -INFINITY;
            }
            float m = fmaxf(fmaxf(fmaxf(v[0], v[1]), fmaxf(v[2], v[3])), fmaxf(fmaxf(v[4], v[5]), fmaxf(v[6], v[7])));
            m = fmaxf(m, fmaxf(v[8], v[9]));
            {
              const float m1 = __shfl_xor_sync(~0u, m, 1), m2 = __shfl_xor_sync(~0u, m, 2), m3 = __shfl_xor_sync(~0u, m, 3);
              m = fmaxf(fmaxf(m, m1), fmaxf(m2, m3));
            }
            const float ms = -m * SC;
#pragma unroll
            for (int i = 0; i < 10; i++) v[i] = ex2(fmaf(v[i], SC, ms));
            float sum = ((v[0] + v[1]) + (v[2] + v[3])) + ((v[4] + v[5]) + (v[6] + v[7])) + (v[8] + v[9]);
            {
              const float s1 = __shfl_xor_sync(~0u, sum, 1), s2 = __shfl_xor_sync(~0u, sum, 2), s3 = __shfl_xor_sync(~0u, sum, 3);
              sum = (sum + s1) + (s2 + s3);
            }
            float r;
            asm("rcp.approx.ftz.f32 %0, %1;" : "=f"(r) : "f"(sum));
            {
              const uint32_t row = SM_P + grp * 640;
#pragma unroll
              for (int j = 0; j < 5; j++) sts32(sb + row + j * 128 + lane * 4, pack2(v[2 * j] * r, v[2 * j + 1] * r));
              fence_async_smem();
              __syncwarp();
              mbar_arrive_if(lane == 0, sb + B_PTOK);
              if (elect_one()) {
                bulk_s2s(peer1 + row, sb + row, 640, peer1 + B_PTOK);
                bulk_s2s(peer2 + row, sb + row, 640, peer2 + B_PTOK);
              }
            }
          }
        }
      }
      const uint32_t* const src = (const uint32_t*)((char*)(g_part + (size_t)((l * 2 + (s & 1)) * PART_RING)) + src_off);
      uint32_t* const dst = (uint32_t*)pin((char*)(g_mem + l * 1024 + (~s & 1) * 512) + dst_off, lane);
      {
        const uint32_t d1 = prm.d1[cta / 24 + ((info >> 5) & 4)];
        if (warp == 3) {
          mbar_wait(sb + B_OB, par);
          mbar_arrive_if(lane == 0, sb + B_GATE);
          sts32(sb + SM_TOPI + par * 4, clk());
          __syncwarp();
          mbar_arrive_if(lane == 0, sb + B_OPI + par * 8);
          TRACE(true, n, 0, gtl());
        }
        const bool reduce = cta < 88 && s != NSEG - 1;
        if (reduce || warp == 0) mbar_wait(sb + B_OPI + par * 8, (n >> 1) & 1);
        if (!reduce) continue;
        mbar_wait(sb + B_RFREE, (nred++ & 1) ^ 1);
        mbar_wait(sb + B_GATE, 1);
        if (d1) spin(d1);
      }
      {
        uint32_t g = 0;
        float2 u;
        PROF(14);
        if (!split) {
          u = poll_sum<8>(src, ~(s >> 1), even, g);
        } else {
          u = poll_sum<12>(src, ~(s >> 1), even, g);
          u.x += __shfl_xor_sync(~0u, u.x, 2);
          u.y += __shfl_xor_sync(~0u, u.y, 2);
        }
        PROF(18);
        if (warp != 1) {
          asm volatile("st.shared.v2.f32 [%0], {%1,%2};" ::"r"(red), "f"(u.x), "f"(u.y) : "memory");
          bar_arrive(3, 128);
        } else {
          bar_sync(3, 128);
          const uint2 o0 = lds64(red), o1 = lds64(red + 256), o2 = lds64(red + 512);
          const uint32_t w = movm(pack2((u.x + __uint_as_float(o0.x)) + (__uint_as_float(o1.x) + __uint_as_float(o2.x)),
                                        (u.y + __uint_as_float(o0.y)) + (__uint_as_float(o1.y) + __uint_as_float(o2.y))));
          if (!split || lane < 16) {
            st_rlx1(dst, w);
            st_rlx1(dst + ((s & 1) ? 2048 : -2048), ~0u);
          }
          mbar_arrive_if(lane == 0, sb + B_RFREE);
        }
        PROF(19);
        PROFV(2, g);
        TRACE(warp == 1, n, 1, gtl());
        TRACE(g, n, 2, g);
      }
    }
  } else {
    asm volatile("setmaxnreg.dec.sync.aligned.u32 %0;" ::"n"(RG3));
    const uint32_t chk = lane * 32 + ((lane >> 2) << 2);
    const uint32_t bar = sb + B_MTRY + 8 * warp;
    uint32_t mph = 0, waited = 0, pub = 0, pph = 0;
    auto publish = [&](uint32_t upto) {
#pragma unroll 1
      for (; pub < upto; pub++) {
        const uint32_t e = prm.slot[pub], l = (e >> 6) & 1;
        if (warp == 3 && (e >> 16)) {
          mbar_wait_wd(sb + B_OTOK + l * 8, (pph >> l) & 1);
          pph ^= 1 << l;
          if (elect_one()) red_rel(&g_cnt[(e >> 16) * CSTRIDE], 1);
        }
      }
    };
#pragma unroll 1
    for (int m = 0; m < nslots; m++) {
      const uint32_t info = prm.slot[m], prod = (info >> 8) & 255, ls = info & 127;
      uint32_t g = 0;
#pragma unroll 1
      for (; waited < prod && waited + 1 < m; waited++) mbar_wait_wd(sb + B_OPI + (waited & 1) * 8, (waited >> 1) & 1);
      uint32_t t0 = lds32(sb + SM_TOPI + (~waited & 1) * 4);
      publish(waited);
      if ((ls & 3) == 0) {
        while (__any_sync(~0u, ld_acq(&g_cnt[(C_XN + (ls >> 2)) * CSTRIDE]) < XN_TARGET)) guard(g);
        fence_async_global();
      }
#pragma unroll 1
      for (uint32_t c = warp; c < 5; c += 4) {
        const uint32_t dst = sb + SM_H + c * 10240, full = sb + B_HFULL + 8 * c;
        const uint4* src = g_mem + (c * 2048 + (ls >> 6) * 1024 + (ls & 1) * 512 + prm.moff);
        const uint32_t d = prod ? prm.d2[(m - prod) * 5 + c] : 0;
        const uint4* tok = g_xn + (size_t)(ls * 2560 + c * 512);
        const uint32_t pp = (m & 1) ^ 1;
        const bool single = waited < prod;
        mbar_wait_wd(full, pp);
        mbar_expect_if(lane < 2, lane ? bar : full, lane ? 2048 : 8192);
        if (!single) while (__any_sync(~0u, clk() - t0 < d)) {}
        if (c >= 2) mbar_wait_wd(sb + B_HEMPTY + 8 * c, pp);
        mbar_wait_wd(sb + (c < 2 ? B_HEMPTY + 8 * c : c == 2 && !single ? B_PMEM : B_OB), pp);
        if (c != 2 || single) { if (elect_one()) bulk_g2s(dst + 2048, tok, 8192, full); }
        if (single) {
          mbar_wait_wd(sb + B_OPI + (waited & 1) * 8, (waited >> 1) & 1);
          waited++;
          t0 = lds32(sb + SM_TOPI + (~waited & 1) * 4);
          publish(waited);
          while (__any_sync(~0u, clk() - t0 < d)) {}
        }
        else if (c < 2) spin(prm.dh);
        if (elect_one()) bulk_g2s(dst, src, 2048, bar);
        if (c == 2 && !single) {
          mbar_wait_wd(sb + B_OB, pp);
          if (elect_one()) bulk_g2s(dst + 2048, tok, 8192, full);
        }
        g = 0;
        while (true) {
          mbar_wait_wd(bar, mph);
          mph ^= 1;
          const uint32_t v0 = lds32(dst + chk), v1 = lds32(dst + chk + 1024);
          if (__all_sync(~0u, v0 != ~0u && v1 != ~0u)) break;
          if (elect_one()) {
            mbar_expect(bar, 2048);
            bulk_g2s(dst, src, 2048, bar);
          }
          guard(g);
        }
        mbar_arrive_if(lane == 0, full);
        TRACE(c < 2, m, 3 + 2 * c, gtl());
        TRACE(c < 2, m, 4 + 2 * c, g);
      }
    }
    publish(nslots);
    if (warp == 0) mbar_wait_wd(sb + B_END, 0);
  }
  __syncwarp();
  if (wid != 12 && lane0 == 0) mbar_arrive(sb + B_END);
  cluster_sync();
}
constexpr int PLANE = 16 * 40 * 32, MAXPL = 13;
__device__ uint2 g_acc[(size_t)2 * NBLK * 2 * MAXPL * PLANE];
DI uint2* acc_planes(int lb, int d) { return g_acc + (size_t)((lb * 2 + d) * MAXPL) * PLANE; }
__device__ uint32_t g_xa[NBLK * 10 * 4096];
__device__ uint32_t g_h[NBLK * 24 * 4096];

enum { T_A = 0, T_F1 = 1, T_U = 2, T_D = 3, T_F2 = 4, T_NONE = 7 };
__host__ __device__ constexpr int c_phase(int type, int lb) { return C_O + type * 32 + lb; }
constexpr int C_TICKET = c_phase(5, 0);
constexpr int G_NST = 7;
constexpr uint32_t GS_RED = G_NST * 32768, GS_BAR = GS_RED + 1088, G_SMEM = GS_BAR + 224;
constexpr uint32_t GB_FULL = GS_BAR, GB_EMPTY = GS_BAR + 64, GB_ORD = GS_BAR + 128, GB_READY = GS_BAR + 144, GB_ACK = GS_BAR + 152, GB_GATE = GS_BAR + 160, GB_SIG = GS_BAR + 176, GB_SACK = GS_BAR + 192,
                   GS_SIG = GS_BAR + 208, GS_COL = GS_BAR + 216;
constexpr int NF = 16;
constexpr int G_EARLY = 36;
constexpr int G_LATE = 96, PL = 6, ML = 8, DL = 24, TL = 10;
constexpr int GRC = 112, GRP = 32;
constexpr uint32_t E_UP = 1u << 8, E_HALF = 1u << 28, E_GRP = 1u << 29, E_HAND = 1u << 30, E_EXCL = 1u << 31;

struct GParams {
  __nv_bfloat16* out;
  int rot;
  uint8_t need[5][2 * NBLK];
  uint32_t tab[G_EARLY * (PL + ML + DL) + G_LATE * TL];
};
constexpr int EL = PL + ML + DL, TAB_TAIL = G_EARLY * EL;
struct GIter {
  int p, left, period;
  uint32_t e, type, lb, n0, kb0, nkb;
  bool gemm, valid;
  DI GIter(const GParams& prm, int col) {
    if (col < G_EARLY) { p = col * EL; left = PL; period = 0; }
    else { p = TAB_TAIL + (col - G_EARLY) * TL; left = TL; period = NBLK - 1; }
  }
  DI bool next(const GParams& prm, int col) {
    do {
      if (left == 0) {
        if (++period == NBLK) return false;
        left = period < NBLK - 1 ? ML : DL;
        if (period > 1 && period < NBLK - 1) p -= ML;
      }
      e = prm.tab[p++]; left--;
    } while ((e & 7) == T_NONE);
    const int b = (e >> 4) & 15, blk = period < NBLK - 1 ? period - b : b;
    type = e & 7; valid = blk >= 0; lb = (e & 8) * 2 + (blk & 15); n0 = (e >> 9) & 127; kb0 = (e >> 16) & 127;
    gemm = type != T_F1 && type != T_F2;
    nkb = valid ? (e >> 23) & 31 : 0;
    return true;
  }
  DI int id() const { return period < NBLK - 1 ? period * 10 + ML - left : 150 + DL - left; }
};

#define GLOG(nt, i, v)
template <int TA> DI void wg_ss128(float* d, uint64_t da, uint64_t db, int sc) {
  asm volatile("{.reg .pred p; setp.ne.b32 p, %66, 0;\n"
               "wgmma.mma_async.sync.aligned.m64n128k16.f32.bf16.bf16 "
               "{%0,%1,%2,%3,%4,%5,%6,%7,%8,%9,%10,%11,%12,%13,%14,%15,%16,%17,%18,%19,%20,%21,%22,%23,%24,%25,%26,%27,%28,%29,%30,%31,"
               "%32,%33,%34,%35,%36,%37,%38,%39,%40,%41,%42,%43,%44,%45,%46,%47,%48,%49,%50,%51,%52,%53,%54,%55,%56,%57,%58,%59,%60,%61,%62,%63}, "
               "%64, %65, p, 1, 1, %67, 1;}"
               : ACC16(d, 0), ACC16(d, 16), ACC16(d, 32), ACC16(d, 48) : "l"(da), "l"(db), "r"(sc), "n"(TA));
}

DI void ln_stats(const float4* v, uint32_t red, int warp, int lane, int bar, float& mean, float& rstd) {
  float s = 0.f;
#pragma unroll
  for (int i = 0; i < 5; i++) s += (v[i].x + v[i].y) + (v[i].z + v[i].w);
  s += __shfl_xor_sync(~0u, s, 1);
  s += __shfl_xor_sync(~0u, s, 2);
  s *= 1.f / 80;
  float q = 0.f;
#pragma unroll
  for (int i = 0; i < 5; i++) q += ((v[i].x - s) * (v[i].x - s) + (v[i].y - s) * (v[i].y - s)) + ((v[i].z - s) * (v[i].z - s) + (v[i].w - s) * (v[i].w - s));
  q += __shfl_xor_sync(~0u, q, 1);
  q += __shfl_xor_sync(~0u, q, 2);
  if ((lane & 3) == 0) asm volatile("st.shared.v2.f32 [%0], {%1,%2};" ::"r"(red + lane * 16 + warp * 8), "f"(s), "f"(q) : "memory");
  bar_sync(bar, 256);
  const uint4 t = lds128(red + lane * 16);
  const float m0 = __uint_as_float(t.x), m1 = __uint_as_float(t.z);
  mean = m0 + m1;
  mean += __shfl_xor_sync(~0u, mean, 1);
  mean += __shfl_xor_sync(~0u, mean, 2);
  mean *= 0.125f;
  q = __uint_as_float(t.y) + __uint_as_float(t.w) + 80.f * ((m0 - mean) * (m0 - mean) + (m1 - mean) * (m1 - mean));
  q += __shfl_xor_sync(~0u, q, 1);
  q += __shfl_xor_sync(~0u, q, 2);
  rstd = rsqrtf(q * (1.f / DM) + 1e-5f);
}
template <int SH, int STR> DI void store_img(uint32_t* dst, const float4* v, int warp, float mean, float rstd) {
#pragma unroll
  for (int i = 0; i < 5; i++) {
    const int U = 10 * warp + 2 * i;
    uint32_t* p = dst + (U >> SH) * STR + (U & ((1 << SH) - 1)) * 32;
    p[0] = pack2((v[i].x - mean) * rstd, (v[i].y - mean) * rstd);
    p[32] = pack2((v[i].z - mean) * rstd, (v[i].w - mean) * rstd);
  }
}
DI uint32_t* xn_row_group(int layer, int rg) { return (uint32_t*)(g_xn + (size_t)((layer * NSEG + (rg >> 2)) * 2560 + (rg & 3) * 128)); }

template <int TA> DI void g_mainloop(float* acc, uint32_t sb, uint32_t hand, uint32_t gate, int nkb, int cw, int lane, uint32_t st, uint32_t ph) {
  const uint64_t da0 = (TA ? mkdesc(SMEM0, 4096, 512, 2) : mkdesc(SMEM0, 128, 1024, 0)) + (cw >> 2) * 512;
  const uint64_t db0 = mkdesc(SMEM0 + 16384, 8192, 1024, 1);
  uint32_t prev = 0;
#pragma unroll 1
  for (int kb = 0; kb < nkb; kb++) {
    mbar_wait(sb + GB_FULL + 8 * st, ph);
    mbar_wait(gate, 1);
    const uint64_t da = da0 + st * 2048, db = db0 + st * 2048;
    wg_fence();
#pragma unroll
    for (int k = 0; k < 4; k++) wg_ss128<TA>(acc, da + k * (TA ? 64 : 16), db + k * 128, 1);
    wg_commit();
    mbar_arrive_if(hand && kb == nkb - 1 && lane == 0, hand);
    wg_wait<1>();
    mbar_arrive_if(kb > 0 && lane == 0, sb + GB_EMPTY + 8 * prev);
    prev = st;
    if (++st == G_NST) { st = 0; ph ^= 1; }
  }
  wg_wait<0>();
  reg_fence<64>(acc);
  mbar_arrive_if(lane == 0, sb + GB_EMPTY + 8 * prev);
}

__global__ void __launch_bounds__(640, 1)
g_kernel(const __grid_constant__ CUtensorMap mapWo, const __grid_constant__ CUtensorMap mapWg, const __grid_constant__ CUtensorMap mapWu,
         const __grid_constant__ CUtensorMap mapWd, const __grid_constant__ GParams prm) {
  const uint32_t sb = smem_base();
  const int wid = __shfl_sync(~0u, threadIdx.x >> 5, 0), lane = threadIdx.x & 31;
  if (threadIdx.x == 0) {
    if ((sb & 0x3FFFF) != SMEM0) __trap();
    {
      uint32_t sm; asm volatile("mov.u32 %0, %%smid;" : "=r"(sm));
      const bool a = prm.rot >= 0 && (sm >= 124 || sm == 48 || sm == 49);
      const uint32_t t = atomicAdd(&g_cnt[C_TICKET * CSTRIDE], a ? 0x10001 : 1), n = t & 0xffff, na = t >> 16;
      uint32_t c = n;
      if (n < G_EARLY && prm.rot >= 0) c = ((a ? na : G_EARLY - 1 - (n - na)) + prm.rot) % G_EARLY;
      sts32(sb + GS_COL, c);
    }
    for (int i = 0; i < G_NST; i++) { mbar_init(sb + GB_FULL + 8 * i, 1); mbar_init(sb + GB_EMPTY + 8 * i, 8); }
    mbar_init(sb + GB_ORD, 8); mbar_init(sb + GB_ORD + 8, 8); mbar_init(sb + GB_READY, 1); mbar_init(sb + GB_ACK, 1);
    mbar_init(sb + GB_GATE, 1); mbar_init(sb + GB_GATE + 8, 1);
    mbar_init(sb + GB_SIG, 8); mbar_init(sb + GB_SIG + 8, 8); mbar_init(sb + GB_SACK, 1); mbar_init(sb + GB_SACK + 8, 1);
    fence_async_smem();
  }
  __syncthreads();
  const int col = __shfl_sync(~0u, lds32(sb + GS_COL), 0);

  if (wid >= 16) {
    GIter t(prm, col);
    asm volatile("setmaxnreg.dec.sync.aligned.u32 %0;" ::"n"(GRP));
    uint32_t st = 0, ph = 1, k = 0;
    if (wid == 16) {
      while (t.next(prm, col)) {
        const CUtensorMap* m0 = t.type == T_A ? &mapWo : t.type == T_U ? &mapWg : &mapWd;
        const CUtensorMap* m1 = t.type == T_U ? &mapWu : m0;
        const int c0 = t.type == T_U ? t.n0 * 64 : (t.n0 & 7) * 128, c1 = t.type == T_U ? c0 : c0 + 64;
#pragma unroll 1
        for (uint32_t kb = t.kb0; kb < t.kb0 + t.nkb; kb++) {
          mbar_wait(sb + GB_EMPTY + 8 * st, ph);
          if (elect_one()) {
            const uint32_t full = sb + GB_FULL + 8 * st, dst = sb + st * 32768;
            mbar_expect(full, (t.e & E_HALF) ? 24576 : 32768);
            tma_2d(dst + 16384, m0, c0, kb * 64, full);
            tma_2d(dst + 24576, m1, c1, kb * 64, full);
          }
          if (++st == G_NST) { st = 0; ph ^= 1; }
        }
      }
    } else if (wid == 17) {
      while (t.next(prm, col)) {
        if (!t.nkb) continue;
        const char* asrc = t.type == T_A ? (const char*)g_oT + (size_t)t.lb * (96 * 16384)
                         : t.type == T_U ? (const char*)g_xa + (size_t)(t.lb & 15) * (10 * 16384) : (const char*)g_h + (size_t)(t.lb & 15) * (24 * 16384);
        const uint32_t up = (t.e & E_UP) * 32;
        GLOG(t.id(), 1, gtime());
        mbar_wait(sb + GB_READY, k & 1);
        mbar_arrive_if(lane == 0, sb + GB_ACK);
        k++;
#pragma unroll 1
        for (uint32_t kb = t.kb0; kb < t.kb0 + t.nkb; kb++) {
          mbar_wait(sb + GB_EMPTY + 8 * st, ph);
          if (elect_one()) bulk_g2s(sb + st * 32768 + up, asrc + (size_t)kb * 16384 + up, (t.e & E_HALF) ? 8192 : 16384, sb + GB_FULL + 8 * st);
          if (++st == G_NST) { st = 0; ph ^= 1; }
        }
      }
    } else if (wid == 18) {
      while (t.next(prm, col)) {
        if (!t.nkb) continue;
        const bool lower = t.type == T_A && (t.e & (E_HALF | E_UP)) == E_HALF;
        poll_ge(&g_cnt[(lower ? C_HALF + t.lb : c_phase(t.type, t.lb)) * CSTRIDE], prm.need[t.type][t.lb]);
        fence_async_global();
        GLOG(t.id(), 2, gtime());
        mbar_wait(sb + GB_ACK, (k & 1) ^ 1);
        mbar_arrive_if(lane == 0, sb + GB_READY);
        k++;
      }
    } else {
      uint32_t live = 3, par = 0, g = 0;
      while (live) {
        const bool ev = lane < 2 && ((live >> lane) & 1) && mbar_test(sb + GB_SIG + 8 * lane, (par >> lane) & 1);
        const uint32_t evs = __ballot_sync(~0u, ev);
        if (!evs) { guard(g); continue; }
        const uint32_t msg = ev ? lds32(sb + GS_SIG + 4 * lane) : 0;
        mbar_arrive_if(ev, sb + GB_SACK + 8 * lane);
        mbar_arrive_if(msg >> 31, sb + GB_GATE + 8 * lane);
        if (msg) red_rel(&g_cnt[(msg & 0xffff) * CSTRIDE], (msg >> 16) & 255);
        par ^= evs;
        live &= ~__ballot_sync(~0u, ev && !msg);
        g = 0;
      }
      asm volatile("griddepcontrol.wait;" ::: "memory");
    }
  } else {
    asm volatile("setmaxnreg.inc.sync.aligned.u32 %0;" ::"n"(GRC));
    const int cw = wid & 7, wk = wid >> 3;
    GIter t(prm, col);
    uint32_t pos = 0, seen = 0, waited = 0;
    uint32_t nsig = 0;
    auto signal = [&](uint32_t msg) {
      mbar_wait(sb + GB_SACK + 8 * wk, (nsig++ & 1) ^ 1);
      if (cw == 0) sts32(sb + GS_SIG + 4 * wk, msg);
      __syncwarp();
      mbar_arrive_if(lane == 0, sb + GB_SIG + 8 * wk);
    };
    while (t.next(prm, col)) {
      const uint32_t pos0 = pos;
      pos = (pos + t.nkb) % (2 * G_NST);
      if (((t.e >> 29) & 1) != wk) { seen += (t.e >> 30) & 1; continue; }
      const uint32_t type = t.type, blk = t.lb & 15, layer = t.lb >> 4, n0 = t.n0;
      if (cw == 0 && t.valid) GLOG(t.id(), 0, 0x80000000u | type | (t.lb << 3) | (n0 << 8) | (t.nkb << 16));
      if (!t.gemm) {
        if (!t.valid) continue;
        const int rg = blk * 16 + n0;
        float4 v[5];
        const int off = (n0 * 40 + cw * 5) * 32 + lane, npl = t.kb0;
        const uint2* src = acc_planes(t.lb, type == T_F2) + off;
        if (cw == 0) {
          poll_ge(&g_cnt[c_phase(type, t.lb) * CSTRIDE], prm.need[type][t.lb]);
          mbar_arrive_if((t.e & E_EXCL) && lane == 0, sb + GB_GATE + 8 * wk);
          GLOG(t.id(), 2, gtime()); GLOG(t.id(), 3, gtime());
        }
        bar_sync(1 + wk, 256);
        {
          const uint32_t eye = (lane >> 3) == (lane & 3) ? ((lane & 4) ? 0x3f800000u : 0x00003f80u) : 0u;
#pragma unroll
          for (int i = 0; i < 5; i++) v[i] = make_float4(0.f, 0.f, 0.f, 0.f);
#pragma unroll 1
          for (int p0 = 0; p0 < npl; p0 += 6) {
            uint32_t r[3][5][4];
#pragma unroll
            for (int p = 0; p < 6; p++)
#pragma unroll
              for (int i = 0; i < 5; i++) {
                const uint2 w = p0 + p < npl ? __ldcg(src + (size_t)(p0 + p) * PLANE + i * 32) : make_uint2(0, 0);
                r[p >> 1][i][(p & 1) * 2] = w.x; r[p >> 1][i][(p & 1) * 2 + 1] = w.y;
              }
#pragma unroll
            for (int p = 0; p < 3; p++) {
              if (p0 + 2 * p >= npl) break;
              if (t.e & E_EXCL) {
#pragma unroll
                for (int i = 0; i < 5; i++) mma16816(&v[i].x, r[p][i], eye, eye);
              } else {
#pragma unroll
                for (int i = 0; i < 5; i++) {
                  const uint32_t* w = r[p][i];
                  v[i].x += blo(w[0]) + blo(w[2]); v[i].y += bhi(w[0]) + bhi(w[2]); v[i].z += blo(w[1]) + blo(w[3]); v[i].w += bhi(w[1]) + bhi(w[3]);
                }
              }
            }
          }
        }
        if (type == T_F2 && layer == 1) {
          uint2* dst = (uint2*)prm.out + (size_t)(rg * 8 + (lane >> 2)) * (DM / 4) + cw * 20 + (lane & 1) * 2 + ((lane >> 1) & 1);
#pragma unroll
          for (int i = 0; i < 5; i++) {
            const uint32_t a = pack2(v[i].x, v[i].y), b = pack2(v[i].z, v[i].w);
            const uint32_t o = __shfl_xor_sync(~0u, (lane & 1) ? a : b, 1);
            dst[i * 4] = (lane & 1) ? make_uint2(o, b) : make_uint2(a, o);
          }
        } else {
          uint2* nx = (type == T_F1 ? acc_planes(t.lb, 1) : acc_planes(NBLK + blk, 0)) + off;
#pragma unroll
          for (int i = 0; i < 5; i++) {
            const uint2 w = make_uint2(pack2(v[i].x, v[i].y), pack2(v[i].z, v[i].w));
            nx[i * 32] = w;
            v[i] = make_float4(blo(w.x), bhi(w.x), blo(w.y), bhi(w.y));
          }
          float mean, rstd;
          ln_stats(v, sb + GS_RED + wk * 512, cw, lane, 1 + wk, mean, rstd);
          if (type == T_F2) store_img<4, 2048>(xn_row_group(1, rg) + lane, v, cw, mean, rstd);
          else store_img<3, 4096>(g_xa + (size_t)(blk * 10 * 4096 + n0 * 256) + lane, v, cw, mean, rstd);
        }
      } else {
        float acc[64];
#pragma unroll
        for (int j = 0; j < 64; j++) acc[j] = 0.f;
        if (waited != seen) { mbar_wait(sb + GB_ORD + 8 * (wk ^ 1), waited & 1); waited++; }
        const uint32_t hand = (t.e & E_HAND) ? sb + GB_ORD + 8 * wk : 0;
        if (!t.valid) { mbar_arrive_if(hand && lane == 0, hand); continue; }
        if (cw == 0) GLOG(t.id(), 3, gtime());
        const uint32_t ph = pos0 >= G_NST, st = pos0 - ph * G_NST, early = (t.e & E_EXCL) ? 0 : hand;
        const bool idle = (t.e & E_HALF) && ((t.e >> 8) & 1) != (cw >> 2);
        if (idle) {
          uint32_t s2 = st, p2 = ph;
#pragma unroll 1
          for (uint32_t kb = 0; kb < t.nkb; kb++) {
            mbar_wait(sb + GB_FULL + 8 * s2, p2);
            mbar_arrive_if(lane == 0, sb + GB_EMPTY + 8 * s2);
            if (++s2 == G_NST) { s2 = 0; p2 ^= 1; }
          }
          mbar_arrive_if(early && lane == 0, early);
        } else if (type == T_A) g_mainloop<1>(acc, sb, early, sb + GB_GATE + 8 * (wk ^ 1), t.nkb, cw, lane, st, ph);
        else g_mainloop<0>(acc, sb, early, sb + GB_GATE + 8 * (wk ^ 1), t.nkb, cw, lane, st, ph);
        if (cw == 0) GLOG(t.id(), 4, gtime());
        if (idle) {
        } else if (type == T_U) {
          uint32_t* dst = g_h + (size_t)((blk * 24 + n0) * 4096 + cw * 512) + lane;
#pragma unroll
          for (int j = 0; j < 8; j++) {
            float h[4];
#pragma unroll
            for (int e = 0; e < 4; e++) {
              float th;
              asm("tanh.approx.f32 %0, %1;" : "=f"(th) : "f"(0.5f * acc[4 * j + e]));
              h[e] = acc[32 + 4 * j + e] * fmaf(th, 0.5f, 0.5f);
            }
            dst[j * 32] = pack2(h[0], h[1]);
            dst[j * 32 + 256] = pack2(h[2], h[3]);
          }
        } else {
          uint2* dst = acc_planes(t.lb, type == T_D) + (size_t)((1 + (n0 >> 3)) * PLANE + (2 * cw * 40 + (n0 & 7) * 8) * 32) + lane;
#pragma unroll
          for (int j = 0; j < 16; j++) {
            const float* a = acc + (j >> 1) * 8 + (j & 1) * 2;
            dst[(j >> 1) * 32 + (j & 1) * 1280] = make_uint2(pack2(a[0], a[1]), pack2(a[4], a[5]));
          }
        }
        mbar_arrive_if(hand != early && lane == 0, hand);
      }
      if (cw == 0) GLOG(t.id(), 5, gtime());
      if (cw == 0) GLOG(t.id(), 6, gtime());
      if (type == T_F2 && layer == 1) mbar_arrive_if((t.e & E_EXCL) && cw == 0 && lane == 0, sb + GB_GATE + 8 * wk);
      else
        signal((type != T_F2 ? c_phase(type + 1, t.lb) | (1 << 16) : (C_XN + NBLK + blk) | ((XN_TARGET / NF) << 16)) | (t.gemm ? 0 : t.e & E_EXCL));
    }
    signal(0);
  }
}

__global__ void __launch_bounds__(256) prep_kernel(const uint32_t* __restrict__ x, const uint4* __restrict__ mem0, int moff, const char* w0, const char* w1, const char* w2, const char* w3, int npf) {
  __shared__ __align__(16) uint32_t red[128];
  const int tid = threadIdx.x, lane = tid & 31, warp = tid >> 5, rg = blockIdx.x;
  const int gt = blockIdx.x * 256 + tid;
  const uint32_t* src = x + (size_t)(rg * 8 + (lane >> 2)) * (DM / 2) + warp * 40 + (lane & 3);
  uint32_t a[10];
#pragma unroll
  for (int i = 0; i < 10; i++) a[i] = src[i * 4];
  if (tid == 0) {
    const char* w[4] = {w0, w1, w2, w3};
#pragma unroll
    for (int i = 0; i < 4; i++) if (i < npf) asm volatile("cp.async.bulk.prefetch.L2.global [%0], 30720;" ::"l"(w[i] + blockIdx.x * 30720) : "memory");
  }
  if (gt < 2560) g_mem[(gt >> 7) * 512 + moff + (gt & 127)] = (gt & 128) ? make_uint4(~0u, ~0u, ~0u, ~0u) : mem0[(gt & 7) * 80 + (gt >> 9) * 16 + ((gt >> 3) & 15)];
  for (int i = gt; i < 4 * PART_RING; i += 65536) g_part[i] = make_uint4(0, 0, 0, 0);
  if (gt < C_TOTAL) g_cnt[gt * CSTRIDE] = (gt >= C_XN && gt < C_XN + NBLK) ? XN_TARGET : 0;
  float4 v[5];
#pragma unroll
  for (int i = 0; i < 5; i++) {
    v[i] = make_float4(blo(a[2 * i]), bhi(a[2 * i]), blo(a[2 * i + 1]), bhi(a[2 * i + 1]));
    acc_planes(rg >> 4, 0)[((rg & 15) * 40 + warp * 5 + i) * 32 + lane] = make_uint2(a[2 * i], a[2 * i + 1]);
  }
  float mean, rstd;
  ln_stats(v, (uint32_t)__cvta_generic_to_shared(red), warp, lane, 1, mean, rstd);
  store_img<4, 2048>(xn_row_group(0, rg) + lane, v, warp, mean, rstd);
}
typedef CUresult (*EncodeFn)(CUtensorMap*, CUtensorMapDataType, cuuint32_t, void*, const cuuint64_t*, const cuuint64_t*, const cuuint32_t*,
                             const cuuint32_t*, CUtensorMapInterleave, CUtensorMapSwizzle, CUtensorMapL2promotion, CUtensorMapFloatOOBfill);
static CUtensorMap make_map(EncodeFn fn, const void* p, uint64_t inner, uint64_t outer, uint32_t bi, uint32_t bo) {
  CUtensorMap m;
  cuuint64_t dims[2] = {inner, outer}, str[1] = {inner * 2};
  cuuint32_t box[2] = {bi, bo}, es[2] = {1, 1};
  fn(&m, CU_TENSOR_MAP_DATA_TYPE_BFLOAT16, 2, (void*)p, dims, str, box, es, CU_TENSOR_MAP_INTERLEAVE_NONE, CU_TENSOR_MAP_SWIZZLE_128B,
     CU_TENSOR_MAP_L2_PROMOTION_L2_256B, CU_TENSOR_MAP_FLOAT_OOB_FILL_NONE);
  return m;
}
struct Tune {
  int lag = 11, excl = 7, gonly = 0, xl = 1, ronly = 0, pn = 30;
  int da = 100, db = 350, dc = 650, dd = 650, d2 = 2000, p1 = 400, p2 = 800;
  int ea = 60, eb = 310, ec = 550, ed = 550, e2 = 2200, q1 = 200, q2 = 400, d3 = 60, moff = 192, ds = 400, dh = 60, npf = 4, rot = 15;
};
static void fill_r(RParams& p, const Tune& t, int lag, int n0, int n1) {
  r_fill_desc(p);
  p.nslots = 0; p.d3 = t.d3; p.pn = t.pn; p.moff = t.moff; p.ds = t.ds; p.dh = t.dh;
  for (int c = 0; c < 5; c++) { p.d2[c] = t.d2 + (c == 0 ? 0 : c < 3 ? t.p1 : t.p2); p.d2[5 + c] = t.e2 + (c == 0 ? 0 : c < 3 ? t.q1 : t.q2); }
  const int d1[8] = {t.da, t.db, t.dc, t.dd, t.ea, t.eb, t.ec, t.ed};
  for (int i = 0; i < 8; i++) p.d1[i] = d1[i];
  int last[2] = {0, 0}, n = 0;
  for (int s0 = 0; s0 < NSEG + lag; s0++)
    for (int l = 0; l < 2; l++) {
      const int s = l ? s0 - lag : s0;
      if (s < 0 || s >= NSEG) continue;
      if (n >= n0 && n < n1) { p.slot[p.nslots] = s | (l << 6) | (last[l] << 8) | (((s & 3) == 3 ? C_O + l * NBLK + s / 4 : s == (l ? 61 : 1) ? C_HALF + l * NBLK + s / 4 : 0) << 16); last[l] = ++p.nslots; }
      n++;
    }
  for (int i = 0; i + 1 < p.nslots; i++) if (((p.slot[i] ^ p.slot[i + 1]) >> 6) & 1) p.slot[i] |= 128;
}
static uint32_t g_entry(int grp, int type, int layer, int blk, int i, int ks) {
  int n0 = i, kb0 = 0, kb1 = type == T_U ? 10 : 0;
  if (type == T_F1 || type == T_F2) kb0 = kb1 = ks + 1;
  if (type == T_A || type == T_D) {
    const int KB = type == T_A ? 96 : 24, sp = i / 5;
    n0 = i % 5 | (sp << 3); kb0 = sp * KB / ks; kb1 = (sp + 1) * KB / ks;
  }
  return type | (layer << 3) | (blk << 4) | (n0 << 9) | (kb0 << 16) | ((kb1 - kb0) << 23) | (grp ? E_GRP : 0);
}
static bool g_is_gemm(uint32_t e) { return (e & 7) == T_A || (e & 7) == T_U || (e & 7) == T_D; }
static void g_handover(uint32_t* e, int len) {
  uint32_t next = 0;
  for (int i = len - 1; i >= 0; i--)
    if (g_is_gemm(e[i])) { if ((e[i] & E_GRP) != next) e[i] |= E_HAND; next = e[i] & E_GRP; }
}
struct GList {
  GParams& g; uint32_t* tab; int ncol, stride, len, n[G_LATE], load[G_LATE], grp[G_LATE];
  GList(GParams& g_, uint32_t* t, int nc, int st, int l) : g(g_), tab(t), ncol(nc), stride(st), len(l) { for (int c = 0; c < nc; c++) { n[c] = load[c] = 0; grp[c] = 1; } }
  void add(int type, int lb, int ks, int c0, int c1, uint32_t flags = 0, int i0 = 0, int i1 = 999, int step = 1) {
    const int half = (flags & E_HALF) != 0, ln = type == T_F1 || type == T_F2;
    const int cnt = (type == T_U ? 24 : ln ? NF : 5 * ks) << half;
    if (type < T_F2) g.need[type + 1][lb] = cnt;
    int used[G_LATE] = {0};
    for (int i = i0; i < cnt && i < i1; i += step) {
      int best = c0;
      for (int c = c0; c < c1; c++) if (used[c] < used[best] || (used[c] == used[best] && load[c] < load[best])) best = c;
      used[best]++;
      if (!ln) grp[best] ^= 1;
      const uint32_t e = g_entry(grp[best], type, lb >> 4, lb & 15, i >> half, ks) | flags | (ln ? E_EXCL : 0) | ((i & half) ? E_UP : 0);
      if (n[best] >= len) abort();
      tab[best * stride + n[best]++] = e;
      load[best] += (((e >> 23) & 31) >> half) + 2;
    }
  }
  void finish() { for (int c = 0; c < ncol; c++) g_handover(tab + c * stride, len); }
};
static void fill_g(GParams& g, const Tune& t, void* out) {
  g.out = (__nv_bfloat16*)out; g.rot = t.rot;
  for (int b = 0; b < 2 * NBLK; b++) {
    g.need[T_A][b] = 96; g.need[T_F1][b] = 20; g.need[T_U][b] = NF; g.need[T_D][b] = 32; g.need[T_F2][b] = 15;
  }
  for (uint32_t& e : g.tab) e = T_NONE;
  GList pr(g, g.tab, G_EARLY, EL, PL);
  pr.add(T_A, 0, 7, 1, 36, E_HALF, 0, 999, 2); pr.add(T_A, 0, 7, 1, 36, E_HALF, 1, 999, 2); pr.add(T_F1, 0, 7, 20, 36); pr.add(T_U, 0, 0, 12, 36);
  pr.add(T_D, 0, 3, 20, 36); pr.add(T_F2, 0, 3, 20, 36);
  pr.finish();
  const int d = 3;
  const uint32_t xa = (t.excl & 1) ? E_EXCL : 0, xu = (t.excl & 2) ? E_EXCL : 0, xd = (t.excl & 4) ? E_EXCL : 0;
  for (int c = 0; c < G_EARLY; c++) {
    uint32_t* e = g.tab + c * EL + PL;
    if (c < 20) {
      *e++ = g_entry(0, T_A, 0, 0, c, 4) | xa;
      if (c < NF) *e++ = g_entry(0, T_F1, 0, 0, c, 4) | ((t.xl & 1) ? E_EXCL : 0);
      *e++ = g_entry(1, T_A, 1, d, c, 4);
      if (c >= 20 - NF) *e++ = g_entry(1, T_F1, 1, d, c - (20 - NF), 4);
    } else {
      const int j = c - 20;
      const uint32_t hf = E_HALF | ((j & 1) ? E_UP : 0);
      *e++ = g_entry(0, T_U, 0, 0, j, 0);
      *e++ = g_entry(1, T_U, 0, 0, 16 + j / 2, 0) | hf | xu;
      *e++ = g_entry(0, T_U, 1, d + 1, 16 + j / 2, 0) | hf;
      if (j < 15) *e++ = g_entry(1, T_D, 0, 0, j, 3) | xd;
      *e++ = g_entry(1, T_F2, 0, 0, j, 3) | ((t.xl & 2) ? E_EXCL : 0);
      if (j < 15) *e++ = g_entry(0, T_D, 1, d + 2, j, 3);
      *e++ = g_entry(1, T_U, 1, d + 1, j, 0);
      *e++ = g_entry(1, T_F2, 1, d + 2, j, 3);
    }
    g_handover(g.tab + c * EL + PL, ML);
  }
  GList dr(g, g.tab + PL + ML, G_EARLY, EL, DL);
  GList tl(g, g.tab + TAB_TAIL, G_LATE, TL, TL);
  const int L1 = NBLK;
  auto ufull = [&](int lb) { dr.add(T_U, lb, 0, 20, 36, 0, 0, 16); g.need[T_D][lb] = 32; };
  auto uhalf = [&](int lb) { dr.add(T_U, lb, 0, 20, 36, E_HALF, 32); g.need[T_D][lb] = 32; };
  dr.add(T_A, 15, 4, 0, 20, E_EXCL);
  dr.add(T_F1, 15, 4, 0, 16);
  dr.add(T_U, 15, 0, 12, 36, E_EXCL);
  dr.add(T_A, L1 + 12, 4, 0, 20); dr.add(T_F1, L1 + 12, 4, 0, 16);
  uhalf(L1 + 11);
  dr.add(T_D, 15, 3, 20, 36, E_EXCL); dr.add(T_F2, 15, 3, 20, 36);
  dr.add(T_A, L1 + 13, 4, 0, 20); dr.add(T_F1, L1 + 13, 4, 0, 20);
  ufull(L1 + 11);
  dr.add(T_D, L1 + 10, 3, 20, 36);
  ufull(L1 + 12); uhalf(L1 + 12);
  dr.add(T_A, L1 + 14, 4, 0, 20);
  dr.add(T_A, L1 + 15, 7, 0, 35, E_HALF, 0, 999, 2); dr.add(T_A, L1 + 15, 7, 0, 35, E_HALF | E_EXCL, 1, 999, 2);
  dr.add(T_F1, L1 + 14, 4, 0, 16);
  dr.add(T_F1, L1 + 15, 7, 20, 36);
  dr.add(T_F2, L1 + 10, 3, 0, 16); dr.add(T_F2, L1 + 11, 3, 4, 20); dr.add(T_F2, L1 + 12, 3, 0, 20);
  dr.add(T_D, L1 + 13, 3, 20, 36); dr.add(T_F2, L1 + 13, 3, 20, 36);
  dr.finish();
  tl.add(T_D, L1 + 11, 3, 0, 24); tl.add(T_D, L1 + 12, 3, 48, G_LATE);
  tl.add(T_U, L1 + 14, 0, 0, 24); tl.add(T_U, L1 + 13, 0, 24, 48);
  tl.add(T_D, L1 + 14, 4, 0, 48, E_HALF);
  tl.add(T_F2, L1 + 14, 4, 0, 48);
  tl.add(T_U, L1 + 15, 0, 48, G_LATE, E_HALF);
  tl.add(T_D, L1 + 15, 4, 48, G_LATE, E_HALF);
  tl.add(T_F2, L1 + 15, 4, 48, G_LATE);
  tl.finish();
}
static void launch_all(void* const* d_in, void* d_out, const Tune& t, cudaStream_t st) {
  static EncodeFn fn = nullptr;
  if (!fn) {
    void* f = nullptr;
    cudaDriverEntryPointQueryResult qr;
    cudaGetDriverEntryPoint("cuTensorMapEncodeTiled", &f, cudaEnableDefault, &qr);
    fn = (EncodeFn)f;
    cudaFuncSetAttribute(r_kernel, cudaFuncAttributeMaxDynamicSharedMemorySize, R_SMEM);
    cudaFuncSetAttribute(g_kernel, cudaFuncAttributeMaxDynamicSharedMemorySize, G_SMEM);
  }
  const CUtensorMap mq = make_map(fn, d_in[2], HD, DM, 64, 128), mk = make_map(fn, d_in[3], HD, DM, 64, 128), mv = make_map(fn, d_in[4], HD, DM, 64, 128),
                    mo = make_map(fn, d_in[5], DM, HD, 64, 64), mg = make_map(fn, d_in[8], FF, DM, 64, 64), mu = make_map(fn, d_in[9], FF, DM, 64, 64),
                    md = make_map(fn, d_in[10], DM, FF, 64, 64);
  prep_kernel<<<256, 256, 0, st>>>((const uint32_t*)d_in[0], (const uint4*)d_in[1], t.moff, (const char*)d_in[2], (const char*)d_in[3], (const char*)d_in[4], (const char*)d_in[5], t.npf);
  auto launch_r = [&](int lag, int n0, int n1) {
    RParams p;
    fill_r(p, t, lag, n0, n1);
    for (int i = 0; i < 4; i++) p.w[i] = (const char*)d_in[2 + i];
    cudaLaunchConfig_t cfg = {};
    cfg.gridDim = dim3(3, NH); cfg.blockDim = dim3(512); cfg.dynamicSmemBytes = R_SMEM; cfg.stream = st;
    cudaLaunchAttribute at[1];
    at[0].id = cudaLaunchAttributeClusterDimension; at[0].val.clusterDim.x = 3; at[0].val.clusterDim.y = 1; at[0].val.clusterDim.z = 1;
    cfg.attrs = at; cfg.numAttrs = 1;
    cudaLaunchKernelEx(&cfg, r_kernel, mq, mk, mv, mo, p);
  };
  auto launch_g = [&](const GParams& g, bool pdl) {
    cudaLaunchConfig_t cfg = {};
    cfg.gridDim = dim3(132); cfg.blockDim = dim3(640); cfg.dynamicSmemBytes = G_SMEM; cfg.stream = st;
    cudaLaunchAttribute at[2];
    at[0].id = cudaLaunchAttributeProgrammaticStreamSerialization; at[0].val.programmaticStreamSerializationAllowed = 1;
    cfg.attrs = at; cfg.numAttrs = pdl ? 1 : 0;
    cudaLaunchKernelEx(&cfg, g_kernel, mo, mg, mu, md, g);
  };
  GParams g;
  fill_g(g, t, d_out);
  launch_r(t.lag, 0, 2 * NSEG);
  launch_g(g, true);
}

extern "C" void kernel_launch(void* const* d_in, const int* in_sizes, int n_in, void* d_out, int out_size) {
  launch_all(d_in, d_out, Tune(), cudaStreamPerThread);
}
```

```cpp
#include <cuda_runtime.h>
#include <cuda_bf16.h>
#include <cuda.h>
#include <stdint.h>
#include <stdlib.h>

constexpr int SEQ = 2048, DM = 640, NH = 32, DH = 192, HD = NH * DH, FF = 1536;
constexpr int NSEG = 64, SEGL = 32, NMEM = 8;
constexpr int NBLK = 16;

#define DI __device__ __forceinline__

DI uint32_t smem_base() {
  extern __shared__ __align__(1024) unsigned char smem_raw[];
  uint32_t a;
  asm volatile("{.reg .u64 t; cvta.to.shared.u64 t, %1; cvt.u32.u64 %0, t;}" : "=r"(a) : "l"(smem_raw));
  return a;
}
DI uint32_t mapa(uint32_t a, uint32_t r) {
  uint32_t o;
  asm("mapa.shared::cluster.u32 %0, %1, %2;" : "=r"(o) : "r"(a), "r"(r));
  return o;
}
DI void mbar_init(uint32_t bar, uint32_t cnt) { asm volatile("mbarrier.init.shared::cta.b64 [%0], %1;" ::"r"(bar), "r"(cnt) : "memory"); }
DI void mbar_arrive(uint32_t bar) { asm volatile("mbarrier.arrive.shared::cta.b64 _, [%0];" ::"r"(bar) : "memory"); }
DI void mbar_arrive_remote(uint32_t bar) { asm volatile("mbarrier.arrive.release.cluster.shared::cluster.b64 _, [%0];" ::"r"(bar) : "memory"); }
DI void mbar_expect(uint32_t bar, uint32_t tx) { asm volatile("mbarrier.arrive.expect_tx.shared::cta.b64 _, [%0], %1;" ::"r"(bar), "r"(tx) : "memory"); }
DI void mbar_arrive_if(bool p, uint32_t bar) { asm volatile("{.reg .pred p; setp.ne.b32 p, %1, 0; @p mbarrier.arrive.shared::cta.b64 _, [%0];}" ::"r"(bar), "r"((int)p) : "memory"); }
DI void mbar_arrive_if(bool p, uint32_t bar, uint32_t cnt) {
  asm volatile("{.reg .pred p; setp.ne.b32 p, %1, 0; @p mbarrier.arrive.shared::cta.b64 _, [%0], %2;}" ::"r"(bar), "r"((int)p), "r"(cnt) : "memory");
}
DI void mbar_expect_if(bool p, uint32_t bar, uint32_t tx) {
  asm volatile("{.reg .pred p; setp.ne.b32 p, %2, 0; @p mbarrier.arrive.expect_tx.shared::cta.b64 _, [%0], %1;}" ::"r"(bar), "r"(tx), "r"((int)p) : "memory");
}
DI bool mbar_test(uint32_t bar, uint32_t par) {
  uint32_t ok;
  asm volatile("{.reg .pred p; mbarrier.test_wait.parity.shared::cta.b64 p, [%1], %2; selp.u32 %0, 1, 0, p;}" : "=r"(ok) : "r"(bar), "r"(par) : "memory");
  return ok;
}
DI void mbar_wait(uint32_t bar, uint32_t par) {
  asm volatile(
      "{.reg .pred p;\n"
      "LOOP:\n"
      "mbarrier.try_wait.parity.shared::cta.b64 p, [%0], %1;\n"
      "@!p bra LOOP;\n}" ::"r"(bar), "r"(par) : "memory");
}
DI void mbar_wait_wd(uint32_t bar, uint32_t par) {
  asm volatile(
      "{.reg .pred p; .reg .u32 c;\n"
      "mov.u32 c, 0;\n"
      "LOOP:\n"
      "mbarrier.try_wait.parity.shared::cta.b64 p, [%0], %1;\n"
      "@p bra DONE;\n"
      "add.u32 c, c, 1;\n"
      "setp.lt.u32 p, c, 4000000;\n"
      "@p bra LOOP;\n"
      "trap;\n"
      "DONE:\n}" ::"r"(bar), "r"(par) : "memory");
}
DI void fence_async_smem() { asm volatile("fence.proxy.async.shared::cta;" ::: "memory"); }
DI void fence_async_global() { asm volatile("fence.proxy.async.global;" ::: "memory"); }
DI void bar_sync(int id, int n) { asm volatile("bar.sync %0, %1;" ::"r"(id), "r"(n) : "memory"); }
DI void bar_arrive(int id, int n) { asm volatile("bar.arrive %0, %1;" ::"r"(id), "r"(n) : "memory"); }
DI void cluster_sync() { asm volatile("barrier.cluster.arrive.release.aligned; barrier.cluster.wait.acquire.aligned;" ::: "memory"); }
DI bool elect_one() {
  uint32_t p;
  asm volatile("{.reg .pred p; elect.sync _|p, 0xffffffff; selp.u32 %0, 1, 0, p;}" : "=r"(p));
  return p;
}
DI void bulk_g2s(uint32_t dst, const void* src, uint32_t bytes, uint32_t bar) {
  asm volatile("cp.async.bulk.shared::cluster.global.mbarrier::complete_tx::bytes [%0], [%1], %2, [%3];" ::"r"(dst), "l"(src), "r"(bytes), "r"(bar) : "memory");
}
DI void bulk_g2s_mc(uint32_t dst, const void* src, uint32_t bytes, uint32_t bar, uint16_t mask) {
  asm volatile("cp.async.bulk.shared::cluster.global.mbarrier::complete_tx::bytes.multicast::cluster [%0], [%1], %2, [%3], %4;" ::"r"(dst), "l"(src), "r"(bytes), "r"(bar), "h"(mask) : "memory");
}
DI void bulk_s2s(uint32_t dst, uint32_t src, uint32_t bytes, uint32_t bar) {
  asm volatile("cp.async.bulk.shared::cluster.shared::cta.mbarrier::complete_tx::bytes [%0], [%1], %2, [%3];" ::"r"(dst), "r"(src), "r"(bytes), "r"(bar) : "memory");
}
DI void tma_2d(uint32_t dst, const CUtensorMap* map, int c0, int c1, uint32_t bar) {
  asm volatile("cp.async.bulk.tensor.2d.shared::cluster.global.mbarrier::complete_tx::bytes [%0], [%1, {%3, %4}], [%2];" ::"r"(dst), "l"(map), "r"(bar), "r"(c0), "r"(c1) : "memory");
}
DI void tma_pf(const CUtensorMap* map, int c0, int c1) {
  asm volatile("cp.async.bulk.prefetch.tensor.2d.L2.global [%0, {%1, %2}];" ::"l"(map), "r"(c0), "r"(c1) : "memory");
}
DI void st_async4(uint32_t a, uint32_t x, uint32_t y, uint32_t z, uint32_t w, uint32_t bar) {
  asm volatile("st.async.shared::cluster.mbarrier::complete_tx::bytes.v4.b32 [%0], {%1,%2,%3,%4}, [%5];" ::"r"(a), "r"(x), "r"(y), "r"(z), "r"(w), "r"(bar) : "memory");
}
DI void st_async2(uint32_t a, uint32_t x, uint32_t y, uint32_t bar) {
  asm volatile("st.async.shared::cluster.mbarrier::complete_tx::bytes.v2.b32 [%0], {%1,%2}, [%3];" ::"r"(a), "r"(x), "r"(y), "r"(bar) : "memory");
}
DI void st_async1(uint32_t a, uint32_t x, uint32_t bar) {
  asm volatile("st.async.shared::cluster.mbarrier::complete_tx::bytes.b32 [%0], %1, [%2];" ::"r"(a), "r"(x), "r"(bar) : "memory");
}
DI void sts32(uint32_t a, uint32_t x) { asm volatile("st.shared.b32 [%0], %1;" ::"r"(a), "r"(x) : "memory"); }
DI void sts128(uint32_t a, uint4 v) { asm volatile("st.shared.v4.b32 [%0], {%1,%2,%3,%4};" ::"r"(a), "r"(v.x), "r"(v.y), "r"(v.z), "r"(v.w) : "memory"); }
DI uint32_t lds32(uint32_t a) { uint32_t v; asm volatile("ld.shared.b32 %0, [%1];" : "=r"(v) : "r"(a) : "memory"); return v; }
DI uint2 lds64(uint32_t a) { uint2 v; asm volatile("ld.shared.v2.b32 {%0,%1}, [%2];" : "=r"(v.x), "=r"(v.y) : "r"(a) : "memory"); return v; }
DI uint4 lds128(uint32_t a) { uint4 v; asm volatile("ld.shared.v4.b32 {%0,%1,%2,%3}, [%4];" : "=r"(v.x), "=r"(v.y), "=r"(v.z), "=r"(v.w) : "r"(a) : "memory"); return v; }
DI void stsm4(uint32_t a, uint32_t r0, uint32_t r1, uint32_t r2, uint32_t r3) {
  asm volatile("stmatrix.sync.aligned.m8n8.x4.shared.b16 [%0], {%1,%2,%3,%4};" ::"r"(a), "r"(r0), "r"(r1), "r"(r2), "r"(r3) : "memory");
}
DI void stsm2(uint32_t a, uint32_t r0, uint32_t r1) {
  asm volatile("stmatrix.sync.aligned.m8n8.x2.shared.b16 [%0], {%1,%2};" ::"r"(a), "r"(r0), "r"(r1) : "memory");
}
DI uint32_t movm(uint32_t a) { uint32_t d; asm volatile("movmatrix.sync.aligned.m8n8.trans.b16 %0, %1;" : "=r"(d) : "r"(a)); return d; }
DI uint32_t pack2(float lo, float hi) { uint32_t d; asm("cvt.rn.bf16x2.f32 %0, %1, %2;" : "=r"(d) : "f"(hi), "f"(lo)); return d; }
DI uint4 ld_rlx4(const void* p) {
  uint4 v;
  asm volatile("ld.relaxed.gpu.global.v4.u32 {%0,%1,%2,%3}, [%4];" : "=r"(v.x), "=r"(v.y), "=r"(v.z), "=r"(v.w) : "l"(p) : "memory");
  return v;
}
DI void st_rlx4(void* p, uint32_t x, uint32_t y, uint32_t z, uint32_t w) {
  asm volatile("st.relaxed.gpu.global.v4.u32 [%0], {%1,%2,%3,%4};" ::"l"(p), "r"(x), "r"(y), "r"(z), "r"(w) : "memory");
}
DI void st_rlx1(void* p, uint32_t x) { asm volatile("st.relaxed.gpu.global.u32 [%0], %1;" ::"l"(p), "r"(x) : "memory"); }
DI uint32_t ld_acq(const uint32_t* p) { uint32_t v; asm volatile("ld.acquire.gpu.global.u32 %0, [%1];" : "=r"(v) : "l"(p) : "memory"); return v; }
DI uint32_t ld_rlx(const uint32_t* p) { uint32_t v; asm volatile("ld.relaxed.gpu.global.u32 %0, [%1];" : "=r"(v) : "l"(p) : "memory"); return v; }
DI void red_rel(uint32_t* p, uint32_t v) { asm volatile("red.release.gpu.global.add.u32 [%0], %1;" ::"l"(p), "r"(v) : "memory"); }
DI void guard(uint32_t& g) { asm volatile("{.reg .pred p; add.u32 %0, %0, 1; setp.gt.u32 p, %0, 8000000; @p trap;}" : "+r"(g)); }
DI void poll_ge(const uint32_t* p, uint32_t target) {
  asm volatile(
      "{.reg .pred p; .reg .u32 v;\n"
      "LOOP:\n"
      "ld.acquire.gpu.global.u32 v, [%0];\n"
      "setp.lt.u32 p, v, %1;\n"
      "vote.sync.any.pred p, p, 0xffffffff;\n"
      "@p bra.uni LOOP;\n}" ::"l"(p), "r"(target) : "memory");
}
DI float ex2(float x) { float y; asm("ex2.approx.ftz.f32 %0, %1;" : "=f"(y) : "f"(x)); return y; }

DI void wg_fence() { asm volatile("wgmma.fence.sync.aligned;" ::: "memory"); }
DI void wg_commit() { asm volatile("wgmma.commit_group.sync.aligned;" ::: "memory"); }
template <int N> DI void wg_wait() { asm volatile("wgmma.wait_group.sync.aligned %0;" ::"n"(N) : "memory"); }
template <int N> DI void reg_fence(float* d) {
#pragma unroll
  for (int i = 0; i < N; i++) asm volatile("" : "+f"(d[i])::"memory");
}
__host__ __device__ constexpr uint64_t mkdesc(uint32_t addr, uint32_t lbo, uint32_t sbo, uint32_t sw) {
  return (uint64_t)((addr & 0x3FFFF) >> 4) | ((uint64_t)(lbo >> 4) << 16) | ((uint64_t)(sbo >> 4) << 32) | ((uint64_t)sw << 62);
}

#define ACC4(d, o) "+f"(d[o]), "+f"(d[o + 1]), "+f"(d[o + 2]), "+f"(d[o + 3])
#define ACC16(d, o) ACC4(d, o), ACC4(d, o + 4), ACC4(d, o + 8), ACC4(d, o + 12)
#define ACC20(d) ACC16(d, 0), ACC4(d, 16)

template <int TA, int TB> DI void wg_ss40(float* d, uint64_t da, uint64_t db, int sc) {
  asm volatile("{.reg .pred p; setp.ne.b32 p, %22, 0;\n"
               "wgmma.mma_async.sync.aligned.m64n40k16.f32.bf16.bf16 {%0,%1,%2,%3,%4,%5,%6,%7,%8,%9,%10,%11,%12,%13,%14,%15,%16,%17,%18,%19}, %20, %21, p, 1, 1, %23, %24;}"
               : ACC20(d) : "l"(da), "l"(db), "r"(sc), "n"(TA), "n"(TB));
}
DI void wg_rs40(float* d, uint32_t a0, uint32_t a1, uint32_t a2, uint32_t a3, uint64_t db, int sc) {
  asm volatile("{.reg .pred p; setp.ne.b32 p, %25, 0;\n"
               "wgmma.mma_async.sync.aligned.m64n40k16.f32.bf16.bf16 {%0,%1,%2,%3,%4,%5,%6,%7,%8,%9,%10,%11,%12,%13,%14,%15,%16,%17,%18,%19}, {%20,%21,%22,%23}, %24, p, 1, 1, 0;}"
               : ACC20(d) : "r"(a0), "r"(a1), "r"(a2), "r"(a3), "l"(db), "r"(sc));
}
DI void wg_rs32(float* d, uint32_t a0, uint32_t a1, uint32_t a2, uint32_t a3, uint64_t db, int sc) {
  asm volatile("{.reg .pred p; setp.ne.b32 p, %21, 0;\n"
               "wgmma.mma_async.sync.aligned.m64n32k16.f32.bf16.bf16 {%0,%1,%2,%3,%4,%5,%6,%7,%8,%9,%10,%11,%12,%13,%14,%15}, {%16,%17,%18,%19}, %20, p, 1, 1, 0;}"
               : ACC16(d, 0) : "r"(a0), "r"(a1), "r"(a2), "r"(a3), "l"(db), "r"(sc));
}
DI void wg_rs8(float* d, uint32_t a0, uint32_t a1, uint32_t a2, uint32_t a3, uint64_t db, int sc) {
  asm volatile("{.reg .pred p; setp.ne.b32 p, %9, 0;\n"
               "wgmma.mma_async.sync.aligned.m64n8k16.f32.bf16.bf16 {%0,%1,%2,%3}, {%4,%5,%6,%7}, %8, p, 1, 1, 0;}"
               : ACC4(d, 0) : "r"(a0), "r"(a1), "r"(a2), "r"(a3), "l"(db), "r"(sc));
}
DI void mma16816(float* c, const uint32_t* a, uint32_t b0, uint32_t b1) {
  asm volatile("mma.sync.aligned.m16n8k16.row.col.f32.bf16.bf16.f32 {%0,%1,%2,%3}, {%4,%5,%6,%7}, {%8,%9}, {%0,%1,%2,%3};"
               : ACC4(c, 0) : "r"(a[0]), "r"(a[1]), "r"(a[2]), "r"(a[3]), "r"(b0), "r"(b1));
}
DI void wg_ss8(float* d, uint64_t da, uint64_t db, int sc) {
  asm volatile("{.reg .pred p; setp.ne.b32 p, %6, 0;\n"
               "wgmma.mma_async.sync.aligned.m64n8k16.f32.bf16.bf16 {%0,%1,%2,%3}, %4, %5, p, 1, 1, 1, 1;}"
               : ACC4(d, 0) : "l"(da), "l"(db), "r"(sc));
}
DI void wg_rs16(float* d, uint32_t a0, uint32_t a1, uint32_t a2, uint32_t a3, uint64_t db, int sc) {
  asm volatile("{.reg .pred p; setp.ne.b32 p, %13, 0;\n"
               "wgmma.mma_async.sync.aligned.m64n16k16.f32.bf16.bf16 {%0,%1,%2,%3,%4,%5,%6,%7}, {%8,%9,%10,%11}, %12, p, 1, 1, 0;}"
               : ACC4(d, 0), ACC4(d, 4) : "r"(a0), "r"(a1), "r"(a2), "r"(a3), "l"(db), "r"(sc));
}
__device__ uint4 g_xn[2 * NSEG * 10 * 256];
__device__ uint4 g_oT[2 * NBLK * 96 * 1024];
constexpr int PART_RING = 96 * 256;
__device__ uint4 g_part[4 * PART_RING];
constexpr int MEM_OFF = 192;
#define P4 ~0u, ~0u, ~0u, ~0u
#define P16 P4, P4, P4, P4
#define P256 P16, P16, P16, P16, P16, P16, P16, P16, P16, P16, P16, P16, P16, P16, P16, P16
#define P2K P256, P256, P256, P256, P256, P256, P256, P256
#define P8K P2K, P2K, P2K, P2K
__device__ __align__(8192) uint32_t g_mem32[5 * 2 * 2 * 2048] = {P8K, P8K, P8K, P8K, P8K};
#define g_mem ((uint4*)g_mem32)
constexpr int C_XN = 0;
constexpr int C_O = C_XN + 2 * NBLK;
constexpr int C_HALF = C_O + 6 * 2 * NBLK;
constexpr int C_TOTAL = 512;
constexpr int CSTRIDE = 32;
__device__ uint32_t g_cnt[C_TOTAL * CSTRIDE];
constexpr uint32_t XN_TARGET = 128;

#define TRACE(c, n, i, v)
#define SLOG(i)
#define PROF(i)
#define PROFA(c)
#define PROFV(i, v)

constexpr uint32_t SMEM0 = 1024;
constexpr uint32_t SM_WK = 0, SM_WO = 81920, SM_H = 163840, SM_QT = 215040, QSTR = 1056  , SM_KT = SM_QT + 5 * QSTR + 1024,
                   SM_SR = SM_KT + 5120  , SM_PROF = SM_SR + 5760, R_SMEM = 232448,
                   SM_RED = SM_QT + 1024, SM_BAR = SM_RED + 768;
constexpr uint32_t SM_P = SM_KT, SM_OB = SM_QT + 3200;
constexpr uint32_t B_HFULL = SM_BAR, B_HEMPTY = SM_BAR + 40, B_MTRY = SM_BAR + 80, B_W = SM_BAR + 112, B_SR = B_W + 32,
                   B_PMEM = B_SR + 24, B_PTOK = B_SR + 32, B_OB = B_SR + 40, B_OPD = B_SR + 48, B_RFREE = B_SR + 56,
                   B_GATE = B_SR + 64, B_PSUM = B_SR + 72, B_END = B_SR + 80, B_PVI = B_SR + 88,
                   B_OPI = B_SR + 96, B_OTOK = B_SR + 112, SM_TOPI = B_SR + 128, B_PACE = SM_TOPI + 8,
                   SM_RS = SM_QT + 2 * QSTR + 1024;
static_assert(B_PACE + 32 <= SM_QT + 2 * QSTR, "barriers must fit the unused q row group");

struct RParams {
  uint64_t dH, dWK, dWO, dQT, dKT, dP, dOB[6];
  const char* w[4];
  const uint4* mem0;
  const uint32_t* x;
  int pf;
  int nslots, d3, pn, moff, ds, dh;
  int d2[10], d1[8];
  uint32_t slot[2 * NSEG];
};
static void r_fill_desc(RParams& p) {
  p.dH = mkdesc(SMEM0 + SM_H, 128, 2048, 0);
  p.dWK = mkdesc(SMEM0 + SM_WK, 1024, 1024, 1);
  p.dWO = mkdesc(SMEM0 + SM_WO, 1024, 1024, 1);
  for (int i = 0; i < 6; i++) p.dOB[i] = mkdesc(SMEM0 + SM_OB + (i < 3 ? 0 : (i - 3) * 1024), 128, 128, 0);
  p.dQT = mkdesc(SMEM0 + SM_QT, 128, QSTR, 0);
  p.dKT = mkdesc(SMEM0 + SM_KT, 128, 1024, 0);
  p.dP = mkdesc(SMEM0 + SM_P, 128, 640, 0);
}
DI uint64_t dadd(uint64_t d, int bytes) {
  uint64_t r;
  asm volatile("add.u64 %0, %1, %2;" : "=l"(r) : "l"(d), "l"((long long)(bytes / 16)));
  return r;
}
template <int BYTES> DI void dstep(uint64_t& d) { asm volatile("add.u64 %0, %0, %1;" : "+l"(d) : "n"((long long)(BYTES / 16))); }
__host__ __device__ constexpr int hoff(int ks) { return (ks >> 3) * 10240 + (ks & 7) * 256; }

DI int opaque(int v) { asm volatile("" : "+r"(v)); return v; }
DI uint32_t pin(uint32_t v, int lane) { return __shfl_sync(~0u, v + (lane >> 5), lane); }
DI char* pin(char* p, int lane) { return (char*)__shfl_sync(~0u, (unsigned long long)p, lane); }
DI float blo(uint32_t w) { return __uint_as_float(w << 16); }
DI float bhi(uint32_t w) { return __uint_as_float(w & 0xffff0000u); }
#define R_FB 1
#define PIN_DST 1
#define RG0 232
#define RG1 216
#define RG2 40
#define RG3 24
DI void ldsm4t(uint32_t* r, uint32_t a) {
  asm volatile("ldmatrix.sync.aligned.m8n8.x4.trans.shared.b16 {%0,%1,%2,%3}, [%4];" : "=r"(r[0]), "=r"(r[1]), "=r"(r[2]), "=r"(r[3]) : "r"(a) : "memory");
}
DI void st_tagged(void* p, float a, float b, uint32_t keep, uint32_t tagbit) {
  asm volatile("{.reg .b32 t; cvt.rn.bf16x2.f32 t, %2, %1; lop3.b32 t, t, %3, %4, 0xea; st.relaxed.gpu.global.b32 [%0], t;}" ::"l"(p), "f"(a), "f"(b),
               "r"(keep), "r"(tagbit) : "memory");
}
DI uint32_t lop_bad(uint32_t a, uint32_t b, uint32_t m) { uint32_t d; asm("lop3.b32 %0, %1, %2, %3, 0x7e;" : "=r"(d) : "r"(a), "r"(b), "r"(m)); return d; }
DI uint32_t lop_or3(uint32_t a, uint32_t b, uint32_t c) { uint32_t d; asm("lop3.b32 %0, %1, %2, %3, 0xfe;" : "=r"(d) : "r"(a), "r"(b), "r"(c)); return d; }
DI uint32_t clk() { uint32_t t; asm volatile("mov.u32 %0, %%clock;" : "=r"(t)); return t; }
DI void spin(uint32_t cyc) { const uint32_t t0 = clk(); while (__any_sync(~0u, clk() - t0 < cyc)) {} }
template <int NL> DI float2 poll_sum(const uint32_t* src, uint32_t tag, uint32_t even, uint32_t& g) {
  uint32_t r[NL];
  while (true) {
#pragma unroll
    for (int i = 0; i < NL; i++) r[i] = ld_rlx(src + i * 32);
    uint32_t bad = lop_or3(lop_bad(r[0], r[1], tag), lop_bad(r[2], r[3], tag), lop_bad(r[4], r[5], tag));
    if (NL == 12) bad = lop_or3(bad, lop_bad(r[6], r[7], tag), lop_bad(r[8], r[9], tag));
    asm volatile("lop3.b32 %0, %0, %1, %2, 0xa8;" : "+r"(bad) : "r"(lop_bad(r[NL - 2], r[NL - 1], tag)), "r"(even));
    if (!__any_sync(~0u, bad)) break;
    g++;
  }
  float x[NL / 2], y[NL / 2];
#pragma unroll
  for (int i = 0; i < NL / 2; i++) { x[i] = blo(r[2 * i]) + blo(r[2 * i + 1]); y[i] = bhi(r[2 * i]) + bhi(r[2 * i + 1]); }
  float2 u = make_float2((x[0] + x[1]) + (x[2] + x[3]), (y[0] + y[1]) + (y[2] + y[3]));
  if (NL == 12) { u.x += x[4] + x[5]; u.y += y[4] + y[5]; }
  return u;
}

constexpr int PLANE = 16 * 40 * 32, MAXPL = 13;
__device__ uint2 g_acc[(size_t)2 * NBLK * 2 * MAXPL * PLANE];
DI uint2* acc_planes(int lb, int d) { return g_acc + (size_t)((lb * 2 + d) * MAXPL) * PLANE; }
DI void ln_stats(const float4* v, uint32_t red, int warp, int lane, int bar, float& mean, float& rstd) {
  float s = 0.f;
#pragma unroll
  for (int i = 0; i < 5; i++) s += (v[i].x + v[i].y) + (v[i].z + v[i].w);
  s += __shfl_xor_sync(~0u, s, 1);
  s += __shfl_xor_sync(~0u, s, 2);
  s *= 1.f / 80;
  float q = 0.f;
#pragma unroll
  for (int i = 0; i < 5; i++) q += ((v[i].x - s) * (v[i].x - s) + (v[i].y - s) * (v[i].y - s)) + ((v[i].z - s) * (v[i].z - s) + (v[i].w - s) * (v[i].w - s));
  q += __shfl_xor_sync(~0u, q, 1);
  q += __shfl_xor_sync(~0u, q, 2);
  if ((lane & 3) == 0) asm volatile("st.shared.v2.f32 [%0], {%1,%2};" ::"r"(red + lane * 16 + warp * 8), "f"(s), "f"(q) : "memory");
  bar_sync(bar, 256);
  const uint4 t = lds128(red + lane * 16);
  const float m0 = __uint_as_float(t.x), m1 = __uint_as_float(t.z);
  mean = m0 + m1;
  mean += __shfl_xor_sync(~0u, mean, 1);
  mean += __shfl_xor_sync(~0u, mean, 2);
  mean *= 0.125f;
  q = __uint_as_float(t.y) + __uint_as_float(t.w) + 80.f * ((m0 - mean) * (m0 - mean) + (m1 - mean) * (m1 - mean));
  q += __shfl_xor_sync(~0u, q, 1);
  q += __shfl_xor_sync(~0u, q, 2);
  rstd = rsqrtf(q * (1.f / DM) + 1e-5f);
}
template <int SH, int STR> DI void store_img(uint32_t* dst, const float4* v, int warp, float mean, float rstd) {
#pragma unroll
  for (int i = 0; i < 5; i++) {
    const int U = 10 * warp + 2 * i;
    uint32_t* p = dst + (U >> SH) * STR + (U & ((1 << SH) - 1)) * 32;
    p[0] = pack2((v[i].x - mean) * rstd, (v[i].y - mean) * rstd);
    p[32] = pack2((v[i].z - mean) * rstd, (v[i].w - mean) * rstd);
  }
}
DI uint32_t* xn_row_group(int layer, int rg) { return (uint32_t*)(g_xn + (size_t)((layer * NSEG + (rg >> 2)) * 2560 + (rg & 3) * 128)); }

DI void first_ln(const uint32_t* a, int rg, uint32_t red, int warp, int lane, int bar) {
  float4 v[5];
#pragma unroll
  for (int i = 0; i < 5; i++) {
    v[i] = make_float4(blo(a[2 * i]), bhi(a[2 * i]), blo(a[2 * i + 1]), bhi(a[2 * i + 1]));
    acc_planes(rg >> 4, 0)[((rg & 15) * 40 + warp * 5 + i) * 32 + lane] = make_uint2(a[2 * i], a[2 * i + 1]);
  }
  float mean, rstd;
  ln_stats(v, red, warp, lane, bar, mean, rstd);
  store_img<4, 2048>(xn_row_group(0, rg) + lane, v, warp, mean, rstd);
}
#define QK_P0 32
#define QK_KB 0
struct QKOrder { int op[76]; };
__host__ __device__ constexpr QKOrder qk_order() {
  QKOrder o = {};
  int n = 0, k = 0, q = 0;
  for (; k < QK_P0; k++, q++) { o.op[n++] = 64 | k; o.op[n++] = q; }
  for (int i = 0; i < QK_KB; i++) o.op[n++] = 64 | k++;
  for (int i = 0; i < -QK_KB; i++) o.op[n++] = q++;
  const int nk = 40 - k, nq = 36 - q;
  for (int i = 0, dk = 0, dq = 0; i < nk + nq; i++) {
    if (dq * nk <= dk * nq + (QK_KB ? 0 : -nq) && dq < nq) { o.op[n++] = q++; dq++; } else if (dk < nk) { o.op[n++] = 64 | k++; dk++; } else { o.op[n++] = q++; dq++; }
  }
  return o;
}
__global__ void __launch_bounds__(512, 1)
r_kernel(const __grid_constant__ CUtensorMap mapWq, const __grid_constant__ CUtensorMap mapWk, const __grid_constant__ CUtensorMap mapWv,
         const __grid_constant__ CUtensorMap mapWo, const __grid_constant__ RParams prm) {
  const uint32_t sb = smem_base();
  const int wid = __shfl_sync(~0u, threadIdx.x >> 5, 0);
  const int lane0 = __shfl_sync(~0u, threadIdx.x & 31, threadIdx.x & 31);
  const int lane = lane0;
  const int warp = wid & 3, wg = wid >> 2;
  const uint32_t rank = blockIdx.x, head = blockIdx.y, cta = head * 3 + rank;
  const uint32_t peer1 = mapa(sb, rank == 2 ? 0 : rank + 1), peer2 = mapa(sb, rank == 0 ? 2 : rank - 1);
  const int nslots = prm.nslots;

  SLOG(0);
  if (threadIdx.x == 384) {
    if ((sb & 0x3FFFF) != SMEM0) __trap();
    for (int c = 0; c < 5; c++) { mbar_init(sb + B_HFULL + 8 * c, 2); mbar_init(sb + B_HEMPTY + 8 * c, c == 4 ? 8 : 4); }
    for (int c = 0; c < 11; c++) mbar_init(sb + B_MTRY + 8 * c, 1);
    mbar_init(sb + B_PTOK, rank == 0 ? 3 : 2); mbar_init(sb + B_OB, 5); mbar_init(sb + B_OPD, 4);
    mbar_init(sb + B_OPI, 1); mbar_init(sb + B_OPI + 8, 1); mbar_init(sb + B_RFREE, 1); mbar_init(sb + B_GATE, 1); mbar_init(sb + B_PMEM, 2); mbar_init(sb + B_PSUM, 2); mbar_init(sb + B_PVI, 1); mbar_init(sb + B_OTOK, 4); mbar_init(sb + B_OTOK + 8, 4); mbar_init(sb + B_END, 15);
    for (int c = 0; c < 4; c++) mbar_init(sb + B_PACE + 8 * c, 1);
    asm volatile("fence.mbarrier_init.release.cluster;" ::: "memory");
    fence_async_smem();
  }
  asm volatile("griddepcontrol.launch_dependents;");
  asm volatile("barrier.cluster.arrive.release.aligned;" ::: "memory");

  if (wg < 2) {
  {
    uint32_t xa[10];
    const uint32_t* src = prm.x + (size_t)(cta * 8 + (lane >> 2)) * (DM / 2) + wid * 40 + (lane & 3);
#pragma unroll
    for (int i = 0; i < 10; i++) xa[i] = __ldg(src + i * 4);
    asm volatile("barrier.cluster.wait.acquire.aligned;" ::: "memory");
    first_ln(xa, cta, sb + SM_SR, wid, lane, 8);
    bar_arrive(10, 288);
  }
  if (wg == 0) {
    asm volatile("setmaxnreg.inc.sync.aligned.u32 %0;" ::"n"(RG0));
    uint32_t wq[160];
    SLOG(1);
    mbar_wait(sb + B_W, 0);
    SLOG(2);
    {
      const uint32_t ld_off = ((lane >> 4) * 8 + (lane & 7)) * 128 + (((2 * warp + ((lane >> 3) & 1)) ^ (lane & 7)) << 4);
#pragma unroll
      for (int ks = 0; ks < 40; ks++) ldsm4t(wq + 4 * ks, sb + SM_WO + ks * 2048 + ld_off);
    }
    fence_async_smem();
    bar_arrive(5, 160);
    mbar_wait(sb + B_W + 16, 0);
    SLOG(3);
    const uint32_t st_addr = pin(sb + SM_QT + (lane >> 4) * 1024 + (2 * warp + ((lane >> 3) & 1)) * 128 + (lane & 7) * 16, lane);
    const uint32_t sq_addr = pin(sb + SM_QT + (2 + (lane & 3)) * QSTR + warp * 256 + (lane >> 2) * 16, lane);
    const uint32_t to_lo = warp == 0 ? peer1 : mapa(sb, warp == 2 ? 2 : 0), to_hi = warp == 0 ? peer2 : mapa(sb, warp == 1 ? 1 : 0);
    const uint32_t sr_off = SM_SR + warp * 1920 + rank * 640, sr_bar = B_SR + warp * 8;
    const uint32_t sa0 = pin(to_lo + sr_off + lane * 16, lane), sb0 = pin(to_lo + sr_bar, lane), sa1 = pin(to_lo + sr_off + 512 + lane * 4, lane), sb1 = pin(sb0, lane);
    const uint32_t sa2 = pin(to_hi + sr_off + lane * 16, lane), sb2 = pin(to_hi + sr_bar, lane), sa3 = pin(to_hi + sr_off + 512 + lane * 4, lane), sb3 = pin(sb2, lane);
#pragma unroll 1
    for (int n = 0; n < nslots; n++) {
      const uint32_t par = n & 1;
      PROFA(warp == PW);
      float qa[20], ka[20];
      uint64_t rk = prm.dWK, rh = prm.dH, rq;
      auto K = [&](int ks) { wg_ss40<1, 0>(ka, rk, rh, ks != 0); };
      auto Q = [&](int ks, uint64_t db) { wg_rs40(qa, wq[4 * ks], wq[4 * ks + 1], wq[4 * ks + 2], wq[4 * ks + 3], db, ks != 0); };
      auto next = [&](uint64_t& d, int ks) { if ((ks & 7) == 7) dstep<10240 - 7 * 256>(d); else dstep<256>(d); };
      constexpr QKOrder ord = qk_order();
      auto first = [&](int g, int c) { for (int i = 0; i < 76; i++) if ((ord.op[i] & 63) >> 3 == c) return i >> 2 == g; return false; };
      bool ok = true;
      mbar_wait(sb + B_HFULL, par);
#pragma unroll
      for (int g = 0; g < 19; g++) {
        if (!ok) {
#pragma unroll
          for (int c = 1; c < 5; c++) if (first(g, c)) mbar_wait(sb + B_HFULL + 8 * c, par);
          mbar_wait(sb + B_GATE, 1);
        }
        if (g == 0) PROF(0);
        if (g < 18) ok = mbar_test(sb + B_GATE, 1);
#pragma unroll
        for (int c = 1; c < 5; c++) if (first(g + 1, c)) ok &= mbar_test(sb + B_HFULL + 8 * c, par);
        wg_fence();
#pragma unroll
        for (int i = 4 * g; i < 4 * g + 4; i++) {
          const int ks = ord.op[i] & 63;
          if (i < 2 * QK_P0) {
            if (ord.op[i] & 64) K(ks);
            else { Q(ks, rh); dstep<2048>(rk); next(rh, ks); if (i == 2 * QK_P0 - 1) rq = rh; }
          } else if (ord.op[i] & 64) { K(ks); if (ks < 39) { dstep<2048>(rk); next(rh, ks); } }
          else { Q(ks, rq); next(rq, ks); }
        }
        if (g == 17) wg_commit();
      }
      wg_commit();
#pragma unroll
      for (int ks = 36; ks < 40; ks++) { Q(ks, rq); if (ks < 39) dstep<256>(rq); }
      wg_commit();
      wg_wait<2>();
      bar_arrive(2, 256);
      mbar_wait(sb + B_OPD, par ^ 1);
      wg_wait<1>();
      reg_fence<20>(ka);
      stsm2(st_addr + (SM_KT - SM_QT), pack2(ka[0], ka[1]), pack2(ka[2], ka[3]));
      stsm4(st_addr + (SM_KT - SM_QT) + 1024, pack2(ka[4], ka[5]), pack2(ka[6], ka[7]), pack2(ka[8], ka[9]), pack2(ka[10], ka[11]));
      stsm4(st_addr + (SM_KT - SM_QT) + 3072, pack2(ka[12], ka[13]), pack2(ka[14], ka[15]), pack2(ka[16], ka[17]), pack2(ka[18], ka[19]));
      wg_wait<0>();
      reg_fence<20>(qa);
      PROF(9);
      stsm2(st_addr, pack2(qa[0], qa[1]), pack2(qa[2], qa[3]));
      sts128(sq_addr, make_uint4(pack2(qa[4], qa[5]), pack2(qa[8], qa[9]), pack2(qa[12], qa[13]), pack2(qa[16], qa[17])));
      sts128(sq_addr + 128, make_uint4(pack2(qa[6], qa[7]), pack2(qa[10], qa[11]), pack2(qa[14], qa[15]), pack2(qa[18], qa[19])));
      mbar_arrive_if(lane == 0, sb + B_HEMPTY + 32);
      fence_async_smem();
      bar_sync(1, 128);
      PROF(1);
      wg_fence();
#pragma unroll
      for (int k = 0; k < 4; k++) wg_ss40<1, 1>(qa, dadd(prm.dQT, k * 256), dadd(prm.dKT, k * 256), k != 0);
      wg_commit();
      bar_arrive(7, 256);
      wg_wait<0>();
      reg_fence<20>(qa);
      PROF(3);
      if (warp < 3) {
        uint32_t p[5];
#pragma unroll
        for (int j = 0; j < 5; j++) p[j] = pack2(qa[4 * j], qa[4 * j + 1]);
        if (warp == 0) {
          st_async4(sa0, p[0], p[1], p[2], p[3], sb0);
          st_async4(sa2, p[0], p[1], p[2], p[3], sb2);
          st_async1(sa1, p[4], sb1);
          st_async1(sa3, p[4], sb3);
          sts128(sb + sr_off + lane * 16, make_uint4(p[0], p[1], p[2], p[3]));
          sts32(sb + sr_off + 512 + lane * 4, p[4]);
          __syncwarp();
          mbar_expect_if(lane == 0, sb + B_SR, 1280);
        } else {
          uint32_t h[5];
#pragma unroll
          for (int j = 0; j < 5; j++) h[j] = pack2(qa[4 * j + 2], qa[4 * j + 3]);
          spin(prm.d3);
          st_async4(sa0, p[0], p[1], p[2], p[3], sb0);
          st_async4(sa2, h[0], h[1], h[2], h[3], sb2);
          st_async1(sa1, p[4], sb1);
          st_async1(sa3, h[4], sb3);
        }
      }
    }
  } else {
    asm volatile("setmaxnreg.inc.sync.aligned.u32 %0;" ::"n"(RG1));
    uint32_t wv[160];
    mbar_wait(sb + B_W + 8, 0);
    SLOG(4);
    {
      const uint32_t ld_off = ((lane >> 4) * 8 + (lane & 7)) * 128 + (((2 * warp + ((lane >> 3) & 1)) ^ (lane & 7)) << 4);
#pragma unroll
      for (int ks = 0; ks < 40; ks++) ldsm4t(wv + 4 * ks, sb + SM_WO + ks * 2048 + ld_off);
    }
    fence_async_smem();
    bar_arrive(6, 160);
    const uint64_t dH = prm.dH;
    uint32_t op[8];
    const uint32_t ob_off = SM_OB + (4 * rank + warp) * 256 + lane * 4;
    const uint32_t oa0 = pin(peer1 + ob_off, lane), ob0 = pin(peer1 + B_OB, lane), oa1 = pin(peer2 + ob_off, lane), ob1 = pin(peer2 + B_OB, lane);
    const uint32_t oa2 = pin(oa0 + 128, lane), ob2 = pin(ob0, lane), oa3 = pin(oa1 + 128, lane), ob3 = pin(ob1, lane);
    const uint32_t o_loc = pin(sb + ob_off, lane), rs_addr = pin(sb + SM_RS + (lane & 3) * 8, lane);
    const uint32_t tok_off = pin((cta * 1024 + 64 * warp + (lane ^ (lane >> 3))) * 16, lane), keep = pin((lane & 1) ? ~0u : ~1u, lane);
    const uint32_t pb_off = pin((8 * rank + 2 * warp) * 4096 + head * 128 + lane * 4, lane);
    const uint32_t ph_off = pin(72 * 4096 + 2 * warp * 12288 + cta * 64 + (lane & 2) * 3072 + (lane >> 2) * 8 + (lane & 1) * 4, lane);
    auto store_tok = [&](int m, int lane) {
      const uint32_t ls = prm.slot[m] & 127, sig = prm.slot[m] >> 16;
      uint4* dst = (uint4*)((char*)(g_oT + (size_t)((ls >> 2) * (96 * 1024) + (ls & 3) * 256)) + tok_off);
      dst[0] = make_uint4(op[0], op[1], op[2], op[3]);
      dst[32] = make_uint4(op[4], op[5], op[6], op[7]);
      __syncwarp();
      mbar_arrive_if(sig && lane == 0, sb + B_OTOK + (ls >> 6) * 8);
    };
#pragma unroll 1
    for (int n = 0; n < nslots; n++) {
      const uint32_t par = n & 1;
      const int lane = opaque(lane0);
      PROFA(warp == PW);
      float va[20];
      mbar_expect_if(warp == 0 && lane == 0, sb + B_PTOK, rank == 0 ? 1280 : 1920);
      bar_sync(2, 256);
#pragma unroll
      for (int g = 0; g < 10; g++) {
        wg_fence();
#pragma unroll
        for (int ks = 4 * g; ks < 4 * g + 4; ks++) { wg_rs40(va, wv[4 * ks], wv[4 * ks + 1], wv[4 * ks + 2], wv[4 * ks + 3], dadd(dH, hoff(ks)), ks != 0); }
        wg_commit();
        if (g >= 2 && !(g & 1)) {
          wg_wait<1>();
          if (lane == 0) mbar_arrive(sb + B_HEMPTY + 8 * (g / 2 - 1));
        }
        if (g == 2) bar_sync(7, 256);
      }
      wg_wait<0>();
      reg_fence<20>(va);
      if (lane == 0) mbar_arrive(sb + B_HEMPTY + 32);
      PROF(10);
      uint32_t vf[10];
#pragma unroll
      for (int j = 0; j < 10; j++) {
        const int i = (j + 4) % 10;
        asm volatile("cvt.rn.bf16x2.f32 %0, %1, %2;" : "=r"(vf[i]) : "f"(va[2 * i + 1]), "f"(va[2 * i]));
        if (j == 5) mbar_wait(sb + B_W + 8, 0);
      }
      uint32_t z0, z1;
      asm volatile("shr.u32 %0, %2, 5; shr.u32 %1, %2, 6;" : "=r"(z0), "=r"(z1) : "r"(lane));
      const uint32_t info = prm.slot[n];
      const uint32_t tagbit = ~(info >> 1) & ~keep;
      char* const ring = (char*)(g_part + (size_t)((((info >> 5) & 2) + (info & 1)) * PART_RING));
      char* const pb = pin(ring + pb_off, lane);
      char* const ph = ring + ph_off;
      mbar_wait(sb + B_PMEM, par);
      float om[4];
      wg_fence();
      wg_rs8(om, vf[0], vf[1], vf[2], vf[3], prm.dP, 0);
      wg_rs8(om, vf[4], vf[5], vf[6], vf[7], dadd(prm.dP, 256), 1);
      wg_rs8(om, vf[8], vf[9], z0, z1, dadd(prm.dP, 512 - (128 << 16)), 1);
      wg_commit();
      {
        mbar_wait(sb + B_PSUM, par);
        const uint2 rs = lds64(rs_addr);
        wg_wait<0>();
        reg_fence<4>(om);
        const float r0 = __uint_as_float(rs.x), r1 = __uint_as_float(rs.y);
        const uint32_t b0 = pack2(om[0] * r0, om[1] * r1), b1 = pack2(om[2] * r0, om[3] * r1);
        st_async1(oa0, b0, ob0);
        st_async1(oa1, b0, ob1);
        st_async1(oa2, b1, ob2);
        st_async1(oa3, b1, ob3);
        sts32(o_loc, b0);
        sts32(o_loc + 128, b1);
        fence_async_smem();
        __syncwarp();
        mbar_arrive_if(lane == 0, sb + B_OB);
      }
      PROF(11);
      {
        float c[8];
        if (n == 0) { SLOG(5); mbar_wait(sb + B_W + 24, 0); SLOG(6); }
        mbar_wait(sb + B_OB, par);
        asm volatile("fence.proxy.async::generic.acquire.sync_restrict::shared::cluster.cluster;" ::: "memory");
        PROF(16);
        if ((info & 63) == NSEG - 1) {
          mbar_wait(sb + B_OPI + par * 8, (n >> 1) & 1);
          mbar_arrive_if(warp == 3 && lane == 0, sb + B_GATE);
#pragma unroll
          for (int p = 0; p < 6; p++) st_rlx1(pb + (p >> 1) * 98304 + (p & 1) * 4096, tagbit);
          st_rlx1(ph, tagbit);
          st_rlx1(ph + 12288, tagbit);
        } else {
#pragma unroll
        for (int p = 0; p < 4; p++) {
          float* const cur = c + 4 * (p & 1);
          float* const prv = c + 4 * (~p & 1);
          if (p == 2) mbar_wait(sb + B_OPI + par * 8, (n >> 1) & 1);
          wg_fence();
#pragma unroll
          for (int ks = 0; ks < (p < 3 ? 12 : 4); ks++) {
            wg_ss8(cur, dadd(prm.dWO, p * 24576 + ks * 2048), dadd(prm.dOB[p < 3 ? p : 3 + rank], ks * 256), ks != 0);
            if (p == 3 && ks == 3) mbar_arrive_if(warp == 3 && lane == 0, sb + B_GATE);
            if (p > 0 && ks == 3) {
              wg_commit();
              wg_wait<1>();
              reg_fence<4>(prv);
              st_tagged(pb + (p - 1) * 98304, prv[0], prv[1], keep, tagbit);
              st_tagged(pb + (p - 1) * 98304 + 4096, prv[2], prv[3], keep, tagbit);
            }
          }
          if (p < 3) wg_commit();
        }
        wg_wait<0>();
        reg_fence<4>(c + 4);
        st_tagged(ph, c[4], c[5], keep, tagbit);
        st_tagged(ph + 12288, c[6], c[7], keep, tagbit);
        }
        PROF(17);
      }
      mbar_wait(sb + B_PTOK, par);
      PROF(12);
      {
        float ot[16];
        wg_fence();
        wg_rs32(ot, vf[0], vf[1], vf[2], vf[3], dadd(prm.dP, 640), 0);
        wg_rs32(ot, vf[4], vf[5], vf[6], vf[7], dadd(prm.dP, 640 + 256), 1);
        wg_rs32(ot, vf[8], vf[9], z0, z1, dadd(prm.dP, 640 + 512 - (128 << 16)), 1);
        wg_commit();
        wg_wait<0>();
        reg_fence<16>(ot);
#pragma unroll
        for (int i = 0; i < 8; i++) op[(i & 1) * 4 + (i >> 1)] = pack2(ot[2 * i], ot[2 * i + 1]);
      }
      if (lane == 0) mbar_arrive(sb + B_OPD);
      PROF(13);
      if (info & 128) spin(prm.ds);
      store_tok(n, lane);
    }
  }
  } else if (wg == 2) {
    asm volatile("setmaxnreg.dec.sync.aligned.u32 %0;" ::"n"(RG2));
    asm volatile("barrier.cluster.wait.acquire.aligned;" ::: "memory");
    if (warp == 1) {
      const uint32_t depth = prm.pf & 7;
#pragma unroll 1
      for (uint32_t i = 0; i < 20 + depth; i++) {
        if (i >= depth) {
          const uint32_t j = i - depth;
          mbar_wait_wd(sb + B_PACE + 8 * (j & 3), (j >> 2) & 1);
          if (j % 5 == 4) mbar_arrive_if(lane == 0 && (j != 14 || depth == 1), sb + B_W + (j == 4 ? 0 : j == 9 ? 16 : j == 14 ? 8 : 24));
        }
        if (i >= 20) continue;
        const uint32_t m = i / 5, k = i % 5, bar = sb + B_PACE + 8 * (i & 3);
        if (i == 10) bar_sync(5, 160);
        if (i == 15) {
          if ((prm.pf & 8) && elect_one())
            for (int q = 0; q < 4; q++) tma_pf(&mapWo, (q / 3 * 3 + rank) * 64, head * DH + q % 3 * 64);
#pragma unroll 1
          for (uint32_t j = 16 - depth; j < 15; j++) mbar_wait_wd(sb + B_PACE + 8 * (j & 3), (j >> 2) & 1);
          mbar_arrive_if(lane == 0 && depth > 1, sb + B_W + 8);
          bar_sync(6, 160);
        }
        if (elect_one()) {
          mbar_expect(bar, 16384);
          if (m < 3) tma_2d(sb + (m == 1 ? SM_WK : SM_WO) + k * 16384, m == 0 ? &mapWq : m == 1 ? &mapWk : &mapWv, cta * 64, k * 128, bar);
          else
            for (uint32_t q = 2 * k; q < 2 * k + 2; q++)
              tma_2d(sb + SM_WO + q * 8192, &mapWo, q < 9 ? (q / 3 * 3 + rank) * 64 : 576, head * DH + (q < 9 ? q % 3 : rank) * 64, bar);
        }
      }
    }
    if (warp == 2 && cta < 80 && lane < 16)
      g_mem[(cta >> 4) * 2048 + (lane >> 3) * 1024 + prm.moff + (cta & 15) * 8 + (lane & 7)] = prm.mem0[(lane & 7) * 80 + cta];
    if (warp == 3) {
      bar_sync(10, 288);
      if (lane == 0) red_rel(&g_cnt[(C_XN + (cta >> 4)) * CSTRIDE], 8);
    }
    const uint32_t grp = warp == 1 ? 1 + rank : 4 - (rank >> 1);
    constexpr float SC = 0.07216878364870322f * 1.4426950408889634f;
    const bool split = cta >= 72;
    const uint32_t wd = split ? 72 * 16 + cta * 16 : cta * 32;
    const uint32_t src_off = pin(split ? 72 * 4096 + (cta - 72) * 6144 + warp * 1536 + (lane & 2) * 32 + (lane >> 2) * 8 + (lane & 1) * 4 : cta * 4096 + warp * 1024 + lane * 4, lane);
    const uint32_t dst_off = pin(((wd >> 9) * 8192 + prm.moff * 4 + (wd & 511) + lane) * 4, lane);
    const uint32_t red = pin(sb + SM_RED + (warp < 2 ? 0 : (warp - 1) * 256) + lane * 8, lane);
    const uint32_t fl = (warp & 2) * 8 + (lane >> 3) * 4 + (lane & 3), hf = lane & 4;
    const uint32_t s0 = pin(sb + SM_SR + fl * 16 + hf * 2, lane), s1 = pin(sb + fl * 4, lane), pd = pin(s1 + hf * 64, lane);
    const uint32_t even = pin(~lane & 1, lane);
    uint32_t nred = 0;
    const uint32_t arm = pin(warp == 0 && (lane == 5 || ((lane == 1 || lane == 2) && lane + rank != 3)) ? sb + B_SR + lane * 8 : 0, lane);
#pragma unroll 1
    for (int n = 0; n < nslots; n++) {
      const uint32_t par = n & 1;
      const int lane = opaque(lane0);
      PROFA(warp == PW2);
      const uint32_t info = prm.slot[n], s = info & 63, l = (info >> 6) & 1;
      {
        mbar_expect_if(arm, arm, lane == 5 ? 2048 : 1920);
        if (warp == 0 || warp == 3) {
          mbar_wait(sb + B_SR, par);
          PROF(4);
          const uint2 a0 = lds64(s0), a1 = lds64(s0 + 640), a2 = lds64(s0 + 1280);
          const uint32_t b0 = lds32(s1 + SM_SR + 512), b1 = lds32(s1 + SM_SR + 1152), b2 = lds32(s1 + SM_SR + 1792);
          float v[6];
          v[0] = blo(a0.x) + blo(a1.x) + blo(a2.x); v[1] = bhi(a0.x) + bhi(a1.x) + bhi(a2.x);
          v[2] = blo(a0.y) + blo(a1.y) + blo(a2.y); v[3] = bhi(a0.y) + bhi(a1.y) + bhi(a2.y);
          v[4] = blo(b0) + blo(b1) + blo(b2); v[5] = bhi(b0) + bhi(b1) + bhi(b2);
          float m = fmaxf(fmaxf(v[0], v[1]), fmaxf(v[2], v[3]));
          m = fmaxf(fmaxf(m, __shfl_xor_sync(~0u, m, 4)), fmaxf(v[4], v[5]));
          {
            const float m1 = __shfl_xor_sync(~0u, m, 1), m2 = __shfl_xor_sync(~0u, m, 2), m3 = __shfl_xor_sync(~0u, m, 3);
            m = fmaxf(fmaxf(m, m1), fmaxf(m2, m3));
          }
          const float ms = -m * SC;
#pragma unroll
          for (int i = 0; i < 6; i++) v[i] = ex2(fmaf(v[i], SC, ms));
          float sum = (v[0] + v[1]) + (v[2] + v[3]);
          const float so = __shfl_xor_sync(~0u, sum, 4);
          sts32(pd + SM_P, pack2(v[0], v[1]));
          sts32(pd + SM_P + 128, pack2(v[2], v[3]));
          sts32(s1 + SM_P + 512, pack2(v[4], v[5]));
          fence_async_smem();
          __syncwarp();
          mbar_arrive_if(lane == 0, sb + B_PMEM);
          PROF(5);
          sum += so + (v[4] + v[5]);
          {
            const float t1 = __shfl_xor_sync(~0u, sum, 1), t2 = __shfl_xor_sync(~0u, sum, 2), t3 = __shfl_xor_sync(~0u, sum, 3);
            sum = (sum + t1) + (t2 + t3);
          }
          float r;
          asm("rcp.approx.ftz.f32 %0, %1;" : "=f"(r) : "f"(sum));
          sts32(sb + SM_RS + (warp & 2) * 8 + (lane >> 3) * 4, __float_as_uint(r));
          __syncwarp();
          mbar_arrive_if(lane == 0, sb + B_PSUM);
        } else {
          if (warp + rank != 3) {
            const uint32_t src = sb + SM_SR + warp * 1920;
            mbar_wait(sb + B_SR + warp * 8, par);
            const uint4 a0 = lds128(src + lane * 16), a1 = lds128(src + 640 + lane * 16), a2 = lds128(src + 1280 + lane * 16);
            const uint32_t b0 = lds32(src + 512 + lane * 4), b1 = lds32(src + 1152 + lane * 4), b2 = lds32(src + 1792 + lane * 4);
            float v[10];
            v[0] = blo(a0.x) + blo(a1.x) + blo(a2.x); v[1] = bhi(a0.x) + bhi(a1.x) + bhi(a2.x);
            v[2] = blo(a0.y) + blo(a1.y) + blo(a2.y); v[3] = bhi(a0.y) + bhi(a1.y) + bhi(a2.y);
            v[4] = blo(a0.z) + blo(a1.z) + blo(a2.z); v[5] = bhi(a0.z) + bhi(a1.z) + bhi(a2.z);
            v[6] = blo(a0.w) + blo(a1.w) + blo(a2.w); v[7] = bhi(a0.w) + bhi(a1.w) + bhi(a2.w);
            v[8] = blo(b0) + blo(b1) + blo(b2); v[9] = bhi(b0) + bhi(b1) + bhi(b2);
            {
              const int lim = 6 + 2 * grp + (lane & 24) + ((lane >> 2) & 1) - 2 * (lane & 3);
#pragma unroll
              for (int i = 2; i < 10; i++) if ((i >> 1) * 8 + (i & 1) > lim) v[i] = -INFINITY;
            }
            float m = fmaxf(fmaxf(fmaxf(v[0], v[1]), fmaxf(v[2], v[3])), fmaxf(fmaxf(v[4], v[5]), fmaxf(v[6], v[7])));
            m = fmaxf(m, fmaxf(v[8], v[9]));
            {
              const float m1 = __shfl_xor_sync(~0u, m, 1), m2 = __shfl_xor_sync(~0u, m, 2), m3 = __shfl_xor_sync(~0u, m, 3);
              m = fmaxf(fmaxf(m, m1), fmaxf(m2, m3));
            }
            const float ms = -m * SC;
#pragma unroll
            for (int i = 0; i < 10; i++) v[i] = ex2(fmaf(v[i], SC, ms));
            float sum = ((v[0] + v[1]) + (v[2] + v[3])) + ((v[4] + v[5]) + (v[6] + v[7])) + (v[8] + v[9]);
            {
              const float s1 = __shfl_xor_sync(~0u, sum, 1), s2 = __shfl_xor_sync(~0u, sum, 2), s3 = __shfl_xor_sync(~0u, sum, 3);
              sum = (sum + s1) + (s2 + s3);
            }
            float r;
            asm("rcp.approx.ftz.f32 %0, %1;" : "=f"(r) : "f"(sum));
            {
              const uint32_t row = SM_P + grp * 640;
#pragma unroll
              for (int j = 0; j < 5; j++) sts32(sb + row + j * 128 + lane * 4, pack2(v[2 * j] * r, v[2 * j + 1] * r));
              fence_async_smem();
              __syncwarp();
              mbar_arrive_if(lane == 0, sb + B_PTOK);
              if (elect_one()) {
                bulk_s2s(peer1 + row, sb + row, 640, peer1 + B_PTOK);
                bulk_s2s(peer2 + row, sb + row, 640, peer2 + B_PTOK);
              }
            }
          }
        }
      }
      const uint32_t* const src = (const uint32_t*)((char*)(g_part + (size_t)((l * 2 + (s & 1)) * PART_RING)) + src_off);
      uint32_t* const dst = (uint32_t*)pin((char*)(g_mem + l * 1024 + (~s & 1) * 512) + dst_off, lane);
      {
        const uint32_t d1 = prm.d1[cta / 24 + ((info >> 5) & 4)];
        if (warp == 3) {
          mbar_wait(sb + B_OB, par);
          mbar_arrive_if(lane == 0, sb + B_GATE);
          sts32(sb + SM_TOPI + par * 4, clk());
          __syncwarp();
          mbar_arrive_if(lane == 0, sb + B_OPI + par * 8);
          TRACE(true, n, 0, gtl());
        }
        const bool reduce = cta < 88 && s != NSEG - 1;
        if (reduce || warp == 0) mbar_wait(sb + B_OPI + par * 8, (n >> 1) & 1);
        if (!reduce) continue;
        mbar_wait(sb + B_RFREE, (nred++ & 1) ^ 1);
        mbar_wait(sb + B_GATE, 1);
        if (d1) spin(d1);
      }
      {
        uint32_t g = 0;
        float2 u;
        PROF(14);
        if (!split) {
          u = poll_sum<8>(src, ~(s >> 1), even, g);
        } else {
          u = poll_sum<12>(src, ~(s >> 1), even, g);
          u.x += __shfl_xor_sync(~0u, u.x, 2);
          u.y += __shfl_xor_sync(~0u, u.y, 2);
        }
        PROF(18);
        if (warp != 1) {
          asm volatile("st.shared.v2.f32 [%0], {%1,%2};" ::"r"(red), "f"(u.x), "f"(u.y) : "memory");
          bar_arrive(3, 128);
        } else {
          bar_sync(3, 128);
          const uint2 o0 = lds64(red), o1 = lds64(red + 256), o2 = lds64(red + 512);
          const uint32_t w = movm(pack2((u.x + __uint_as_float(o0.x)) + (__uint_as_float(o1.x) + __uint_as_float(o2.x)),
                                        (u.y + __uint_as_float(o0.y)) + (__uint_as_float(o1.y) + __uint_as_float(o2.y))));
          if (!split || lane < 16) {
            st_rlx1(dst, w);
            st_rlx1(dst + ((s & 1) ? 2048 : -2048), ~0u);
          }
          mbar_arrive_if(lane == 0, sb + B_RFREE);
        }
        PROF(19);
        PROFV(2, g);
        TRACE(warp == 1, n, 1, gtl());
        TRACE(g, n, 2, g);
      }
    }
  } else {
    asm volatile("setmaxnreg.dec.sync.aligned.u32 %0;" ::"n"(RG3));
    asm volatile("barrier.cluster.wait.acquire.aligned;" ::: "memory");
    const uint32_t chk = lane * 32 + ((lane >> 2) << 2);
    const uint32_t bar = sb + B_MTRY + 8 * warp;
    uint32_t mph = 0, waited = 0, pub = 0, pph = 0;
    auto publish = [&](uint32_t upto) {
#pragma unroll 1
      for (; pub < upto; pub++) {
        const uint32_t e = prm.slot[pub], l = (e >> 6) & 1;
        if (warp == 3 && (e >> 16)) {
          mbar_wait_wd(sb + B_OTOK + l * 8, (pph >> l) & 1);
          pph ^= 1 << l;
          if (elect_one()) red_rel(&g_cnt[(e >> 16) * CSTRIDE], 1);
        }
      }
    };
#pragma unroll 1
    for (int m = 0; m < nslots; m++) {
      const uint32_t info = prm.slot[m], prod = (info >> 8) & 255, ls = info & 127;
      uint32_t g = 0;
#pragma unroll 1
      for (; waited < prod && waited + 1 < m; waited++) mbar_wait_wd(sb + B_OPI + (waited & 1) * 8, (waited >> 1) & 1);
      uint32_t t0 = lds32(sb + SM_TOPI + (~waited & 1) * 4);
      publish(waited);
      if ((ls & 3) == 0) {
        while (__any_sync(~0u, ld_acq(&g_cnt[(C_XN + (ls >> 2)) * CSTRIDE]) < XN_TARGET)) guard(g);
        fence_async_global();
      }
#pragma unroll 1
      for (uint32_t c = warp; c < 5; c += 4) {
        const uint32_t dst = sb + SM_H + c * 10240, full = sb + B_HFULL + 8 * c;
        const uint4* src = g_mem + (c * 2048 + (ls >> 6) * 1024 + (ls & 1) * 512 + prm.moff);
        const uint32_t d = prod ? prm.d2[(m - prod) * 5 + c] : 0;
        const uint4* tok = g_xn + (size_t)(ls * 2560 + c * 512);
        const uint32_t pp = (m & 1) ^ 1;
        const bool single = waited < prod;
        mbar_wait_wd(full, pp);
        mbar_expect_if(lane < 2, lane ? bar : full, lane ? 2048 : 8192);
        if (!single) while (__any_sync(~0u, clk() - t0 < d)) {}
        if (c >= 2) mbar_wait_wd(sb + B_HEMPTY + 8 * c, pp);
        mbar_wait_wd(sb + (c < 2 ? B_HEMPTY + 8 * c : c == 2 && !single ? B_PMEM : B_OB), pp);
        if (c != 2 || single) { if (elect_one()) bulk_g2s(dst + 2048, tok, 8192, full); }
        if (single) {
          mbar_wait_wd(sb + B_OPI + (waited & 1) * 8, (waited >> 1) & 1);
          waited++;
          t0 = lds32(sb + SM_TOPI + (~waited & 1) * 4);
          publish(waited);
          while (__any_sync(~0u, clk() - t0 < d)) {}
        }
        else if (c < 2) spin(prm.dh);
        if (elect_one()) bulk_g2s(dst, src, 2048, bar);
        if (c == 2 && !single) {
          mbar_wait_wd(sb + B_OB, pp);
          if (elect_one()) bulk_g2s(dst + 2048, tok, 8192, full);
        }
        g = 0;
        while (true) {
          mbar_wait_wd(bar, mph);
          mph ^= 1;
          const uint32_t v0 = lds32(dst + chk), v1 = lds32(dst + chk + 1024);
          if (__all_sync(~0u, v0 != ~0u && v1 != ~0u)) break;
          if (elect_one()) {
            mbar_expect(bar, 2048);
            bulk_g2s(dst, src, 2048, bar);
          }
          guard(g);
        }
        mbar_arrive_if(lane == 0, full);
        TRACE(c < 2, m, 3 + 2 * c, gtl());
        TRACE(c < 2, m, 4 + 2 * c, g);
      }
    }
    publish(nslots);
    if (warp == 0) mbar_wait_wd(sb + B_END, 0);
  }
  __syncwarp();
  if (wid != 12 && lane0 == 0) mbar_arrive(sb + B_END);
  cluster_sync();
}
__device__ uint32_t g_xa[NBLK * 10 * 4096];
__device__ uint32_t g_h[NBLK * 24 * 4096];

enum { T_A = 0, T_F1 = 1, T_U = 2, T_D = 3, T_F2 = 4, T_NONE = 7 };
__host__ __device__ constexpr int c_phase(int type, int lb) { return C_O + type * 32 + lb; }
constexpr int C_TICKET = c_phase(5, 0), C_EXIT = C_TICKET + 1, C_USED = C_HALF + 2 * NBLK;
constexpr int G_NST = 7;
constexpr uint32_t GS_RED = G_NST * 32768, GS_BAR = GS_RED + 1088, G_SMEM = GS_BAR + 224;
constexpr uint32_t GB_FULL = GS_BAR, GB_EMPTY = GS_BAR + 64, GB_ORD = GS_BAR + 128, GB_READY = GS_BAR + 144, GB_ACK = GS_BAR + 152, GB_GATE = GS_BAR + 160, GB_SIG = GS_BAR + 176, GB_SACK = GS_BAR + 192,
                   GS_SIG = GS_BAR + 208, GS_COL = GS_BAR + 216;
#define FPL 6
constexpr int NF = 16;
constexpr int G_EARLY = 36;
constexpr int G_LATE = 96, PL = 6, ML = 8, DL = 24, TL = 10;
constexpr int GRC = 112, GRP = 32;
constexpr uint32_t E_UP = 1u << 8, E_HALF = 1u << 28, E_GRP = 1u << 29, E_HAND = 1u << 30, E_EXCL = 1u << 31;

struct GParams {
  __nv_bfloat16* out;
  const uint32_t* x;
  int moff, gd;
  int pend;
  uint8_t perm[G_EARLY], first[9];
  uint8_t need[5][2 * NBLK];
  uint32_t tab[G_EARLY * (PL + ML + DL) + G_LATE * TL];
};
constexpr int EL = PL + ML + DL, TAB_TAIL = G_EARLY * EL;
struct GIter {
  int p, left, period;
  uint32_t e, type, lb, n0, kb0, nkb;
  bool gemm, valid;
  DI GIter(const GParams& prm, int col) {
    if (col < G_EARLY) { p = col * EL; left = PL; period = 0; }
    else { p = TAB_TAIL + (col - G_EARLY) * TL; left = TL; period = prm.pend; }
  }
  DI bool next(const GParams& prm, int col) {
    do {
      if (left == 0) {
        if (++period > prm.pend) return false;
        left = period < prm.pend ? ML : DL;
        if (period > 1 && period < prm.pend) p -= ML;
      }
      e = prm.tab[p++]; left--;
    } while ((e & 7) == T_NONE);
    const int b = (e >> 4) & 15, blk = period < prm.pend ? period - b : b;
    type = e & 7; valid = blk >= 0; lb = (e & 8) * 2 + (blk & 15); n0 = (e >> 9) & 127; kb0 = (e >> 16) & 127;
    gemm = type != T_F1 && type != T_F2;
    nkb = valid ? (e >> 23) & 31 : 0;
    return true;
  }
  DI int id_(int pend) const { return period < pend ? period * 10 + ML - left : 160 + DL - left; }
};

#define GLOG(nt, i, v)
template <int TA> DI void wg_ss128(float* d, uint64_t da, uint64_t db, int sc) {
  asm volatile("{.reg .pred p; setp.ne.b32 p, %66, 0;\n"
               "wgmma.mma_async.sync.aligned.m64n128k16.f32.bf16.bf16 "
               "{%0,%1,%2,%3,%4,%5,%6,%7,%8,%9,%10,%11,%12,%13,%14,%15,%16,%17,%18,%19,%20,%21,%22,%23,%24,%25,%26,%27,%28,%29,%30,%31,"
               "%32,%33,%34,%35,%36,%37,%38,%39,%40,%41,%42,%43,%44,%45,%46,%47,%48,%49,%50,%51,%52,%53,%54,%55,%56,%57,%58,%59,%60,%61,%62,%63}, "
               "%64, %65, p, 1, 1, %67, 1;}"
               : ACC16(d, 0), ACC16(d, 16), ACC16(d, 32), ACC16(d, 48) : "l"(da), "l"(db), "r"(sc), "n"(TA));
}

template <int TA> DI void g_mainloop(float* acc, uint32_t sb, uint32_t hand, uint32_t gate, int nkb, int cw, int lane, uint32_t st, uint32_t ph) {
  const uint64_t da0 = (TA ? mkdesc(SMEM0, 4096, 512, 2) : mkdesc(SMEM0, 128, 1024, 0)) + (cw >> 2) * 512;
  const uint64_t db0 = mkdesc(SMEM0 + 16384, 8192, 1024, 1);
  uint32_t prev = 0;
#pragma unroll 1
  for (int kb = 0; kb < nkb; kb++) {
    mbar_wait(sb + GB_FULL + 8 * st, ph);
    mbar_wait(gate, 1);
    const uint64_t da = da0 + st * 2048, db = db0 + st * 2048;
    wg_fence();
#pragma unroll
    for (int k = 0; k < 4; k++) wg_ss128<TA>(acc, da + k * (TA ? 64 : 16), db + k * 128, 1);
    wg_commit();
    mbar_arrive_if(hand && kb == nkb - 1 && lane == 0, hand);
    wg_wait<1>();
    mbar_arrive_if(kb > 0 && lane == 0, sb + GB_EMPTY + 8 * prev);
    prev = st;
    if (++st == G_NST) { st = 0; ph ^= 1; }
  }
  wg_wait<0>();
  reg_fence<64>(acc);
  mbar_arrive_if(lane == 0, sb + GB_EMPTY + 8 * prev);
}

__global__ void __launch_bounds__(640, 1)
g_kernel(const __grid_constant__ CUtensorMap mapWo, const __grid_constant__ CUtensorMap mapWg, const __grid_constant__ CUtensorMap mapWu,
         const __grid_constant__ CUtensorMap mapWd, const __grid_constant__ GParams prm) {
  const uint32_t sb = smem_base();
  const int wid = __shfl_sync(~0u, threadIdx.x >> 5, 0), lane = threadIdx.x & 31;
  if (threadIdx.x == 0) {
    if ((sb & 0x3FFFF) != SMEM0) __trap();
    {
      uint32_t sm; asm volatile("mov.u32 %0, %%smid;" : "=r"(sm));
      uint32_t* const tk = &g_cnt[C_TICKET * CSTRIDE];
      uint32_t c = atomicAdd(tk, 1);
      if (c < G_EARLY) {
        const uint32_t k = sm < 64 ? (sm >> 1) & 7 : sm < 120 ? 1 + ((sm - 64) >> 1) % 7 : sm < 124 ? 1 + ((sm >> 1) & 1) : 0;
        const uint32_t t = atomicAdd(tk + 1 + k, 1);
        atomicAdd(tk + 9, 1);
        if (t < prm.first[k + 1] - prm.first[k]) c = prm.perm[prm.first[k] + t];
        else {
          uint32_t o = atomicAdd(tk + 10, 1), g = 0;
          while (ld_acq(tk + 9) < G_EARLY) guard(g);
          for (int j = 0; j < 8; j++)
            for (uint32_t i = prm.first[j] + ld_acq(tk + 1 + j); i < prm.first[j + 1]; i++) if (o-- == 0) c = prm.perm[i];
        }
      }
      sts32(sb + GS_COL, c);
    }
    for (int i = 0; i < G_NST; i++) { mbar_init(sb + GB_FULL + 8 * i, 1); mbar_init(sb + GB_EMPTY + 8 * i, 8); }
    mbar_init(sb + GB_ORD, 8); mbar_init(sb + GB_ORD + 8, 8); mbar_init(sb + GB_READY, 1); mbar_init(sb + GB_ACK, 1);
    mbar_init(sb + GB_GATE, 1); mbar_init(sb + GB_GATE + 8, 1);
    mbar_init(sb + GB_SIG, 8); mbar_init(sb + GB_SIG + 8, 8); mbar_init(sb + GB_SACK, 1); mbar_init(sb + GB_SACK + 8, 1);
    fence_async_smem();
  }
  __syncthreads();
  const int col = __shfl_sync(~0u, lds32(sb + GS_COL), 0);

  if (wid >= 16) {
    GIter t(prm, col);
    asm volatile("setmaxnreg.dec.sync.aligned.u32 %0;" ::"n"(GRP));
    uint32_t st = 0, ph = 1, k = 0;
    if (wid == 16) {
      while (t.next(prm, col)) {
        const CUtensorMap* m0 = t.type == T_A ? &mapWo : t.type == T_U ? &mapWg : &mapWd;
        const CUtensorMap* m1 = t.type == T_U ? &mapWu : m0;
        const int c0 = t.type == T_U ? t.n0 * 64 : (t.n0 & 7) * 128, c1 = t.type == T_U ? c0 : c0 + 64;
        if ((t.e & (E_HALF | E_UP)) == E_UP) poll_ge(&g_cnt[c_phase(t.type, t.lb) * CSTRIDE], prm.need[t.type][t.lb]);
#pragma unroll 1
        for (uint32_t kb = t.kb0; kb < t.kb0 + t.nkb; kb++) {
          mbar_wait(sb + GB_EMPTY + 8 * st, ph);
          if (elect_one()) {
            const uint32_t full = sb + GB_FULL + 8 * st, dst = sb + st * 32768;
            mbar_expect(full, (t.e & E_HALF) ? 24576 : 32768);
            tma_2d(dst + 16384, m0, c0, kb * 64, full);
            tma_2d(dst + 24576, m1, c1, kb * 64, full);
          }
          if (++st == G_NST) { st = 0; ph ^= 1; }
        }
      }
    } else if (wid == 17) {
      while (t.next(prm, col)) {
        if (!t.nkb) continue;
        const char* asrc = t.type == T_A ? (const char*)g_oT + (size_t)t.lb * (96 * 16384)
                         : t.type == T_U ? (const char*)g_xa + (size_t)(t.lb & 15) * (10 * 16384) : (const char*)g_h + (size_t)(t.lb & 15) * (24 * 16384);
        const uint32_t up = (t.e & E_HALF) ? (t.e & E_UP) * 32 : 0;
        GLOG(t.id_(prm.pend), 1, gtime());
        mbar_wait(sb + GB_READY, k & 1);
        mbar_arrive_if(lane == 0, sb + GB_ACK);
        k++;
#pragma unroll 1
        for (uint32_t kb = t.kb0; kb < t.kb0 + t.nkb; kb++) {
          mbar_wait(sb + GB_EMPTY + 8 * st, ph);
          if (elect_one()) bulk_g2s(sb + st * 32768 + up, asrc + (size_t)kb * 16384 + up, (t.e & E_HALF) ? 8192 : 16384, sb + GB_FULL + 8 * st);
          if (++st == G_NST) { st = 0; ph ^= 1; }
        }
      }
    } else if (wid == 18) {
      while (t.next(prm, col)) {
        if (!t.nkb) continue;
        const bool lower = t.type == T_A && (t.e & (E_HALF | E_UP)) == E_HALF;
        poll_ge(&g_cnt[(lower ? C_HALF + t.lb : c_phase(t.type, t.lb)) * CSTRIDE], prm.need[t.type][t.lb]);
        fence_async_global();
        GLOG(t.id_(prm.pend), 2, gtime());
        mbar_wait(sb + GB_ACK, (k & 1) ^ 1);
        mbar_arrive_if(lane == 0, sb + GB_READY);
        k++;
      }
    } else {
      uint32_t live = 3, par = 0, g = 0;
      while (live) {
        const bool ev = lane < 2 && ((live >> lane) & 1) && mbar_test(sb + GB_SIG + 8 * lane, (par >> lane) & 1);
        const uint32_t evs = __ballot_sync(~0u, ev);
        if (!evs) { guard(g); continue; }
        const uint32_t msg = ev ? lds32(sb + GS_SIG + 4 * lane) : 0;
        mbar_arrive_if(ev, sb + GB_SACK + 8 * lane);
        mbar_arrive_if(msg >> 31, sb + GB_GATE + 8 * lane);
        if (msg) red_rel(&g_cnt[(msg & 0xffff) * CSTRIDE], (msg >> 16) & 255);
        par ^= evs;
        live &= ~__ballot_sync(~0u, ev && !msg);
        g = 0;
      }
      asm volatile("griddepcontrol.wait;" ::: "memory");
      if (col < 80 && lane < 16) g_mem[(col >> 4) * 2048 + (lane >> 3) * 1024 + 512 + prm.moff + (col & 15) * 8 + (lane & 7)] = make_uint4(~0u, ~0u, ~0u, ~0u);
      uint32_t last = 0;
      if (lane == 0) last = atomicAdd(&g_cnt[C_EXIT * CSTRIDE], 1) == gridDim.x - 1;
      if (__shfl_sync(~0u, last, 0)) {
        g_cnt[C_TICKET * CSTRIDE + lane] = 0;
        for (int i = lane; i < C_USED; i += 32) g_cnt[i * CSTRIDE] = 0;
      }
    }
  } else {
    asm volatile("setmaxnreg.inc.sync.aligned.u32 %0;" ::"n"(GRC));
    const int cw = wid & 7, wk = wid >> 3;
    GIter t(prm, col);
    uint32_t pos = 0, seen = 0, waited = 0;
    uint32_t nsig = 0;
    auto signal = [&](uint32_t msg) {
      mbar_wait(sb + GB_SACK + 8 * wk, (nsig++ & 1) ^ 1);
      if (cw == 0) sts32(sb + GS_SIG + 4 * wk, msg);
      __syncwarp();
      mbar_arrive_if(lane == 0, sb + GB_SIG + 8 * wk);
    };
    if (col < G_EARLY) {
      spin(prm.gd);
#pragma unroll 1
      for (int rg = 96 + col * 2 + wk; rg < 256; rg += 2 * G_EARLY) {
        uint32_t a[10];
        const uint32_t* src = prm.x + (size_t)(rg * 8 + (lane >> 2)) * (DM / 2) + cw * 40 + (lane & 3);
#pragma unroll
        for (int i = 0; i < 10; i++) a[i] = __ldg(src + i * 4);
        first_ln(a, rg, sb + GS_RED + wk * 512, cw, lane, 1 + wk);
        signal((C_XN + (rg >> 4)) | ((XN_TARGET / NF) << 16));
        bar_sync(1 + wk, 256);
      }
    }
    while (t.next(prm, col)) {
      const uint32_t pos0 = pos;
      pos = (pos + t.nkb) % (2 * G_NST);
      if (((t.e >> 29) & 1) != wk) { seen += (t.e >> 30) & 1; continue; }
      const uint32_t type = t.type, blk = t.lb & 15, layer = t.lb >> 4, n0 = t.n0;
      if (cw == 0 && t.valid) GLOG(t.id_(prm.pend), 0, 0x80000000u | type | (t.lb << 3) | (n0 << 8) | (t.nkb << 16));
      if (!t.gemm) {
        if (!t.valid) continue;
        const int rg = blk * 16 + n0;
        float4 v[5];
        const int off = (n0 * 40 + cw * 5) * 32 + lane, npl = t.kb0;
        const uint2* src = acc_planes(t.lb, type == T_F2) + off;
        if (cw == 0) {
          poll_ge(&g_cnt[c_phase(type, t.lb) * CSTRIDE], prm.need[type][t.lb]);
          mbar_arrive_if((t.e & E_EXCL) && lane == 0, sb + GB_GATE + 8 * wk);
          GLOG(t.id_(prm.pend), 2, gtime()); GLOG(t.id_(prm.pend), 3, gtime());
        }
        bar_sync(1 + wk, 256);
        {
          const uint32_t eye = (lane >> 3) == (lane & 3) ? ((lane & 4) ? 0x3f800000u : 0x00003f80u) : 0u;
#pragma unroll
          for (int i = 0; i < 5; i++) v[i] = make_float4(0.f, 0.f, 0.f, 0.f);
#pragma unroll 1
          for (int p0 = 0; p0 < npl; p0 += FPL) {
            uint32_t r[FPL / 2][5][4];
#pragma unroll
            for (int p = 0; p < FPL; p++)
#pragma unroll
              for (int i = 0; i < 5; i++) {
                const uint2 w = p0 + p < npl ? __ldcg(src + (size_t)(p0 + p) * PLANE + i * 32) : make_uint2(0, 0);
                r[p >> 1][i][(p & 1) * 2] = w.x; r[p >> 1][i][(p & 1) * 2 + 1] = w.y;
              }
#pragma unroll
            for (int p = 0; p < FPL / 2; p++) {
              if (p0 + 2 * p >= npl) break;
              if (t.e & E_EXCL) {
#pragma unroll
                for (int i = 0; i < 5; i++) mma16816(&v[i].x, r[p][i], eye, eye);
              } else {
#pragma unroll
                for (int i = 0; i < 5; i++) {
                  const uint32_t* w = r[p][i];
                  v[i].x += blo(w[0]) + blo(w[2]); v[i].y += bhi(w[0]) + bhi(w[2]); v[i].z += blo(w[1]) + blo(w[3]); v[i].w += bhi(w[1]) + bhi(w[3]);
                }
              }
            }
          }
        }
        if (type == T_F2 && layer == 1) {
          uint2* dst = (uint2*)prm.out + (size_t)(rg * 8 + (lane >> 2)) * (DM / 4) + cw * 20 + (lane & 1) * 2 + ((lane >> 1) & 1);
#pragma unroll
          for (int i = 0; i < 5; i++) {
            const uint32_t a = pack2(v[i].x, v[i].y), b = pack2(v[i].z, v[i].w);
            const uint32_t o = __shfl_xor_sync(~0u, (lane & 1) ? a : b, 1);
            dst[i * 4] = (lane & 1) ? make_uint2(o, b) : make_uint2(a, o);
          }
        } else {
          uint2* nx = (type == T_F1 ? acc_planes(t.lb, 1) : acc_planes(NBLK + blk, 0)) + off;
#pragma unroll
          for (int i = 0; i < 5; i++) {
            const uint2 w = make_uint2(pack2(v[i].x, v[i].y), pack2(v[i].z, v[i].w));
            nx[i * 32] = w;
            v[i] = make_float4(blo(w.x), bhi(w.x), blo(w.y), bhi(w.y));
          }
          float mean, rstd;
          ln_stats(v, sb + GS_RED + wk * 512, cw, lane, 1 + wk, mean, rstd);
          if (type == T_F2) store_img<4, 2048>(xn_row_group(1, rg) + lane, v, cw, mean, rstd);
          else store_img<3, 4096>(g_xa + (size_t)(blk * 10 * 4096 + n0 * 256) + lane, v, cw, mean, rstd);
        }
      } else {
        float acc[64];
#pragma unroll
        for (int j = 0; j < 64; j++) acc[j] = 0.f;
        if (waited != seen) { mbar_wait(sb + GB_ORD + 8 * (wk ^ 1), waited & 1); waited++; }
        const uint32_t hand = (t.e & E_HAND) ? sb + GB_ORD + 8 * wk : 0;
        if (!t.valid) { mbar_arrive_if(hand && lane == 0, hand); continue; }
        if (cw == 0) GLOG(t.id_(prm.pend), 3, gtime());
        const uint32_t ph = pos0 >= G_NST, st = pos0 - ph * G_NST, early = (t.e & E_EXCL) ? 0 : hand;
        const bool idle = (t.e & E_HALF) && ((t.e >> 8) & 1) != (cw >> 2);
        if (idle) {
          uint32_t s2 = st, p2 = ph;
#pragma unroll 1
          for (uint32_t kb = 0; kb < t.nkb; kb++) {
            mbar_wait(sb + GB_FULL + 8 * s2, p2);
            mbar_arrive_if(lane == 0, sb + GB_EMPTY + 8 * s2);
            if (++s2 == G_NST) { s2 = 0; p2 ^= 1; }
          }
          mbar_arrive_if(early && lane == 0, early);
        } else if (type == T_A) g_mainloop<1>(acc, sb, early, sb + GB_GATE + 8 * (wk ^ 1), t.nkb, cw, lane, st, ph);
        else g_mainloop<0>(acc, sb, early, sb + GB_GATE + 8 * (wk ^ 1), t.nkb, cw, lane, st, ph);
        if (cw == 0) GLOG(t.id_(prm.pend), 4, gtime());
        if (idle) {
        } else if (type == T_U) {
          uint32_t* dst = g_h + (size_t)((blk * 24 + n0) * 4096 + cw * 512) + lane;
#pragma unroll
          for (int j = 0; j < 8; j++) {
            float h[4];
#pragma unroll
            for (int e = 0; e < 4; e++) {
              float th;
              asm("tanh.approx.f32 %0, %1;" : "=f"(th) : "f"(0.5f * acc[4 * j + e]));
              h[e] = acc[32 + 4 * j + e] * fmaf(th, 0.5f, 0.5f);
            }
            dst[j * 32] = pack2(h[0], h[1]);
            dst[j * 32 + 256] = pack2(h[2], h[3]);
          }
        } else {
          uint2* dst = acc_planes(t.lb, type == T_D) + (size_t)((1 + (n0 >> 3)) * PLANE + (2 * cw * 40 + (n0 & 7) * 8) * 32) + lane;
#pragma unroll
          for (int j = 0; j < 16; j++) {
            const float* a = acc + (j >> 1) * 8 + (j & 1) * 2;
            dst[(j >> 1) * 32 + (j & 1) * 1280] = make_uint2(pack2(a[0], a[1]), pack2(a[4], a[5]));
          }
        }
        mbar_arrive_if(hand != early && lane == 0, hand);
      }
      if (cw == 0) GLOG(t.id_(prm.pend), 5, gtime());
      if (cw == 0) GLOG(t.id_(prm.pend), 6, gtime());
      if (type == T_F2 && layer == 1) mbar_arrive_if((t.e & E_EXCL) && cw == 0 && lane == 0, sb + GB_GATE + 8 * wk);
      else
        signal((type != T_F2 ? c_phase(type + 1, t.lb) | (1 << 16) : (C_XN + NBLK + blk) | ((XN_TARGET / NF) << 16)) | (t.gemm ? 0 : t.e & E_EXCL));
    }
    signal(0);
  }
}

typedef CUresult (*EncodeFn)(CUtensorMap*, CUtensorMapDataType, cuuint32_t, void*, const cuuint64_t*, const cuuint64_t*, const cuuint32_t*,
                             const cuuint32_t*, CUtensorMapInterleave, CUtensorMapSwizzle, CUtensorMapL2promotion, CUtensorMapFloatOOBfill);
static CUtensorMap make_map(EncodeFn fn, const void* p, uint64_t inner, uint64_t outer, uint32_t bi, uint32_t bo) {
  CUtensorMap m;
  cuuint64_t dims[2] = {inner, outer}, str[1] = {inner * 2};
  cuuint32_t box[2] = {bi, bo}, es[2] = {1, 1};
  fn(&m, CU_TENSOR_MAP_DATA_TYPE_BFLOAT16, 2, (void*)p, dims, str, box, es, CU_TENSOR_MAP_INTERLEAVE_NONE, CU_TENSOR_MAP_SWIZZLE_128B,
     CU_TENSOR_MAP_L2_PROMOTION_L2_256B, CU_TENSOR_MAP_FLOAT_OOB_FILL_NONE);
  return m;
}
struct Tune {
  int lag = 11, excl = 7, gonly = 0, xl = 1, ronly = 0, pn = 30;
  int da = 100, db = 350, dc = 650, dd = 650, d2 = 2000, p1 = 400, p2 = 800;
  int ea = 60, eb = 310, ec = 550, ed = 550, e2 = 2200, q1 = 200, q2 = 400, d3 = 60, moff = 192, ds = 400, dh = 60, pa = 0, pb = 0, pc = 0, pd = 0, pe = 0, pf = 0, pg = 0, ph = 0, hold = 1, wpf = 4, gd = 22000;
};
static void fill_r(RParams& p, const Tune& t, int lag, int n0, int n1) {
  r_fill_desc(p);
  p.nslots = 0; p.d3 = t.d3; p.pn = t.pn; p.moff = t.moff; p.ds = t.ds; p.dh = t.dh;
  for (int c = 0; c < 5; c++) { p.d2[c] = t.d2 + (c == 0 ? 0 : c < 3 ? t.p1 : t.p2); p.d2[5 + c] = t.e2 + (c == 0 ? 0 : c < 3 ? t.q1 : t.q2); }
  const int d1[8] = {t.da, t.db, t.dc, t.dd, t.ea, t.eb, t.ec, t.ed};
  for (int i = 0; i < 8; i++) p.d1[i] = d1[i];
  int last[2] = {0, 0}, n = 0;
  for (int s0 = 0; s0 < NSEG + lag; s0++)
    for (int l = 0; l < 2; l++) {
      const int s = l ? s0 - lag : s0;
      if (s < 0 || s >= NSEG) continue;
      if (n >= n0 && n < n1) { p.slot[p.nslots] = s | (l << 6) | (last[l] << 8) | (((s & 3) == 3 ? C_O + l * NBLK + s / 4 : s == (l ? 61 : 1) ? C_HALF + l * NBLK + s / 4 : 0) << 16); last[l] = ++p.nslots; }
      n++;
    }
  for (int i = 0; i + 1 < p.nslots; i++) if (((p.slot[i] ^ p.slot[i + 1]) >> 6) & 1) p.slot[i] |= 128;
}
static uint32_t g_entry(int grp, int type, int layer, int blk, int i, int ks) {
  int n0 = i, kb0 = 0, kb1 = type == T_U ? 10 : 0;
  if (type == T_F1 || type == T_F2) kb0 = kb1 = ks + 1;
  if (type == T_A || type == T_D) {
    const int KB = type == T_A ? 96 : 24, sp = i / 5;
    n0 = i % 5 | (sp << 3); kb0 = sp * KB / ks; kb1 = (sp + 1) * KB / ks;
  }
  return type | (layer << 3) | (blk << 4) | (n0 << 9) | (kb0 << 16) | ((kb1 - kb0) << 23) | (grp ? E_GRP : 0);
}
static bool g_is_gemm(uint32_t e) { return (e & 7) == T_A || (e & 7) == T_U || (e & 7) == T_D; }
static void g_handover(uint32_t* e, int len) {
  uint32_t next = 0;
  for (int i = len - 1; i >= 0; i--)
    if (g_is_gemm(e[i])) { if ((e[i] & E_GRP) != next) e[i] |= E_HAND; next = e[i] & E_GRP; }
}
struct GList {
  GParams& g; uint32_t* tab; int ncol, stride, len, n[G_LATE], load[G_LATE], grp[G_LATE];
  GList(GParams& g_, uint32_t* t, int nc, int st, int l) : g(g_), tab(t), ncol(nc), stride(st), len(l) { for (int c = 0; c < nc; c++) { n[c] = load[c] = 0; grp[c] = 1; } }
  void add(int type, int lb, int ks, int c0, int c1, uint32_t flags = 0, int i0 = 0, int i1 = 999, int step = 1) {
    const int half = (flags & E_HALF) != 0, ln = type == T_F1 || type == T_F2;
    const int cnt = (type == T_U ? 24 : ln ? NF : 5 * ks) << half;
    if (type < T_F2) g.need[type + 1][lb] = cnt;
    int used[G_LATE] = {0};
    for (int i = i0; i < cnt && i < i1; i += step) {
      int best = c0;
      for (int c = c0; c < c1; c++) if (used[c] < used[best] || (used[c] == used[best] && load[c] < load[best])) best = c;
      used[best]++;
      if (!ln) grp[best] ^= 1;
      const uint32_t e = g_entry(grp[best], type, lb >> 4, lb & 15, i >> half, ks) | flags | (ln ? E_EXCL : 0) | ((i & half) ? E_UP : 0);
      if (n[best] >= len) abort();
      tab[best * stride + n[best]++] = e;
      load[best] += (((e >> 23) & 31) >> half) + 2;
    }
  }
  void finish() { for (int c = 0; c < ncol; c++) g_handover(tab + c * stride, len); }
};
static void fill_g(GParams& g, const Tune& t, void* out) {
  g.out = (__nv_bfloat16*)out;  g.pend = NBLK - 1;
  for (int b = 0; b < 2 * NBLK; b++) {
    g.need[T_A][b] = 96; g.need[T_F1][b] = 20; g.need[T_U][b] = NF; g.need[T_D][b] = 32; g.need[T_F2][b] = 15;
  }
  {
    const uint8_t perm[G_EARLY] = {0, 1, 2, 3, 16, 17, 18, 19, 34, 35, 4, 20, 21, 15, 22, 23, 5, 6, 7, 8, 9, 24, 25, 26, 10, 11, 12, 13, 14, 27, 28, 29, 30, 31, 32, 33};
    const uint8_t first[9] = {0, 10, 13, 16, 20, 24, 28, 32, 36};
    const int* pk = &t.pa;
    for (int i = 0; i < G_EARLY; i++) g.perm[i] = t.pa ? (pk[i / 5] >> (6 * (i % 5))) & 63 : perm[i];
    for (int i = 0; i < 9; i++) g.first[i] = first[i];
  }
  for (uint32_t& e : g.tab) e = T_NONE;
  GList pr(g, g.tab, G_EARLY, EL, PL);
  pr.add(T_A, 0, 7, 1, 36, E_HALF, 0, 999, 2); pr.add(T_A, 0, 7, 1, 36, E_HALF, 1, 999, 2); pr.add(T_F1, 0, 7, 20, 36); pr.add(T_U, 0, 0, 12, 36);
  pr.add(T_D, 0, 3, 20, 36); pr.add(T_F2, 0, 3, 20, 36);
  pr.finish();
  const int d = 3;
  const uint32_t xa = (t.excl & 1) ? E_EXCL : 0, xu = (t.excl & 2) ? E_EXCL : 0, xd = (t.excl & 4) ? E_EXCL : 0;
  for (int c = 0; c < G_EARLY; c++) {
    uint32_t* e = g.tab + c * EL + PL;
    if (c < 20) {
      *e++ = g_entry(0, T_A, 0, 0, c, 4) | xa;
      if (c < NF) *e++ = g_entry(0, T_F1, 0, 0, c, 4) | ((t.xl & 1) ? E_EXCL : 0);
      *e++ = g_entry(1, T_A, 1, d, c, 4);
      if (c >= 20 - NF) *e++ = g_entry(1, T_F1, 1, d, c - (20 - NF), 4);
    } else {
      const int j = c - 20;
      const uint32_t hf = E_HALF | ((j & 1) ? E_UP : 0);
      *e++ = g_entry(0, T_U, 0, 0, j, 0);
      *e++ = g_entry(1, T_U, 0, 0, 16 + j / 2, 0) | hf | xu;
      *e++ = g_entry(0, T_U, 1, d + 1, 16 + j / 2, 0) | hf;
      if (j < 15) *e++ = g_entry(1, T_D, 0, 0, j, 3) | xd;
      *e++ = g_entry(1, T_F2, 0, 0, j, 3) | ((t.xl & 2) ? E_EXCL : 0);
      if (j < 15) *e++ = g_entry(0, T_D, 1, d + 2, j, 3);
      *e++ = g_entry(0, T_U, 1, d + 1, j, 0);
      *e++ = g_entry(1, T_F2, 1, d + 2, j, 3);
    }
    g_handover(g.tab + c * EL + PL, ML);
  }
  GList dr(g, g.tab + PL + ML, G_EARLY, EL, DL);
  GList tl(g, g.tab + TAB_TAIL, G_LATE, TL, TL);
  const int L1 = NBLK;
  auto ufull = [&](int lb) { dr.add(T_U, lb, 0, 20, 36, 0, 0, 16); g.need[T_D][lb] = 32; };
  auto uhalf = [&](int lb) { dr.add(T_U, lb, 0, 20, 36, E_HALF, 32); g.need[T_D][lb] = 32; };
  dr.add(T_A, 15, 4, 0, 20, E_EXCL);
  dr.add(T_F1, 15, 4, 0, 16);
  dr.add(T_U, 15, 0, 12, 36, E_EXCL);
  dr.add(T_A, L1 + 12, 4, 0, 20); dr.add(T_F1, L1 + 12, 4, 0, 16);
  uhalf(L1 + 11);
  dr.add(T_D, 15, 3, 20, 36, E_EXCL); dr.add(T_F2, 15, 3, 20, 36);
  dr.add(T_A, L1 + 13, 4, 0, 20); dr.add(T_F1, L1 + 13, 4, 0, 20);
  ufull(L1 + 11);
  dr.add(T_D, L1 + 10, 3, 20, 36);
  ufull(L1 + 12); uhalf(L1 + 12);
  dr.add(T_A, L1 + 14, 4, 0, 20);
  dr.add(T_A, L1 + 15, 7, 0, 35, E_HALF, 0, 999, 2); dr.add(T_A, L1 + 15, 7, 0, 35, E_HALF | E_EXCL, 1, 999, 2);
  dr.add(T_F1, L1 + 14, 4, 0, 16);
  dr.add(T_F1, L1 + 15, 7, 20, 36);
  dr.add(T_F2, L1 + 10, 3, 0, 16); dr.add(T_F2, L1 + 11, 3, 4, 20); dr.add(T_F2, L1 + 12, 3, 0, 20);
  dr.add(T_D, L1 + 13, 3, 20, 36, (t.hold & 1) ? E_UP : 0); dr.add(T_F2, L1 + 13, 3, 20, 36);
  dr.finish();
  tl.add(T_D, L1 + 11, 3, 0, 24); tl.add(T_D, L1 + 12, 3, 48, G_LATE);
  tl.add(T_U, L1 + 14, 0, 0, 24); tl.add(T_U, L1 + 13, 0, 24, 48);
  tl.add(T_D, L1 + 14, 4, 0, 48, E_HALF);
  tl.add(T_F2, L1 + 14, 4, 0, 48);
  tl.add(T_U, L1 + 15, 0, 48, G_LATE, E_HALF);
  tl.add(T_D, L1 + 15, 4, 48, G_LATE, E_HALF);
  tl.add(T_F2, L1 + 15, 4, 48, G_LATE);
  tl.finish();
}
static void launch_all(void* const* d_in, void* d_out, const Tune& t, cudaStream_t st) {
  static EncodeFn fn = nullptr;
  if (!fn) {
    void* f = nullptr;
    cudaDriverEntryPointQueryResult qr;
    cudaGetDriverEntryPoint("cuTensorMapEncodeTiled", &f, cudaEnableDefault, &qr);
    fn = (EncodeFn)f;
    cudaFuncSetAttribute(r_kernel, cudaFuncAttributeMaxDynamicSharedMemorySize, R_SMEM);
    cudaFuncSetAttribute(g_kernel, cudaFuncAttributeMaxDynamicSharedMemorySize, G_SMEM);
  }
  const CUtensorMap mq = make_map(fn, d_in[2], HD, DM, 64, 128), mk = make_map(fn, d_in[3], HD, DM, 64, 128), mv = make_map(fn, d_in[4], HD, DM, 64, 128),
                    mo = make_map(fn, d_in[5], DM, HD, 64, 64), mg = make_map(fn, d_in[8], FF, DM, 64, 64), mu = make_map(fn, d_in[9], FF, DM, 64, 64),
                    md = make_map(fn, d_in[10], DM, FF, 64, 64);
  auto launch_r = [&](int lag, int n0, int n1) {
    RParams p;
    fill_r(p, t, lag, n0, n1);
    for (int i = 0; i < 4; i++) p.w[i] = (const char*)d_in[2 + i];
    p.mem0 = (const uint4*)d_in[1]; p.x = (const uint32_t*)d_in[0]; p.pf = t.wpf;
    cudaLaunchConfig_t cfg = {};
    cfg.gridDim = dim3(3, NH); cfg.blockDim = dim3(512); cfg.dynamicSmemBytes = R_SMEM; cfg.stream = st;
    cudaLaunchAttribute at[1];
    at[0].id = cudaLaunchAttributeClusterDimension; at[0].val.clusterDim.x = 3; at[0].val.clusterDim.y = 1; at[0].val.clusterDim.z = 1;
    cfg.attrs = at; cfg.numAttrs = 1;
    cudaLaunchKernelEx(&cfg, r_kernel, mq, mk, mv, mo, p);
  };
  auto launch_g = [&](const GParams& g, bool pdl) {
    cudaLaunchConfig_t cfg = {};
    cfg.gridDim = dim3(132); cfg.blockDim = dim3(640); cfg.dynamicSmemBytes = G_SMEM; cfg.stream = st;
    cudaLaunchAttribute at[2];
    at[0].id = cudaLaunchAttributeProgrammaticStreamSerialization; at[0].val.programmaticStreamSerializationAllowed = 1;
    cfg.attrs = at; cfg.numAttrs = pdl ? 1 : 0;
    cudaLaunchKernelEx(&cfg, g_kernel, mo, mg, mu, md, g);
  };
  GParams g;
  fill_g(g, t, d_out);
  g.moff = t.moff; g.gd = t.gd; g.x = (const uint32_t*)d_in[0];
  launch_r(t.lag, 0, 2 * NSEG);
  launch_g(g, true);
}

extern "C" void kernel_launch(void* const* d_in, const int* in_sizes, int n_in, void* d_out, int out_size) {
  launch_all(d_in, d_out, Tune(), cudaStreamPerThread);
}
```

```cpp
#include <cuda_runtime.h>
#include <cuda_bf16.h>
#include <cuda.h>
#include <stdint.h>
#include <stdlib.h>

constexpr int SEQ = 2048, DM = 640, NH = 32, DH = 192, HD = NH * DH, FF = 1536;
constexpr int NSEG = 64, SEGL = 32, NMEM = 8;
constexpr int NBLK = 16;

#define DI __device__ __forceinline__

DI uint32_t smem_base() {
  extern __shared__ __align__(1024) unsigned char smem_raw[];
  uint32_t a;
  asm volatile("{.reg .u64 t; cvta.to.shared.u64 t, %1; cvt.u32.u64 %0, t;}" : "=r"(a) : "l"(smem_raw));
  return a;
}
DI uint32_t mapa(uint32_t a, uint32_t r) {
  uint32_t o;
  asm("mapa.shared::cluster.u32 %0, %1, %2;" : "=r"(o) : "r"(a), "r"(r));
  return o;
}
DI void mbar_init(uint32_t bar, uint32_t cnt) { asm volatile("mbarrier.init.shared::cta.b64 [%0], %1;" ::"r"(bar), "r"(cnt) : "memory"); }
DI void mbar_arrive(uint32_t bar) { asm volatile("mbarrier.arrive.shared::cta.b64 _, [%0];" ::"r"(bar) : "memory"); }
DI void mbar_arrive_remote(uint32_t bar) { asm volatile("mbarrier.arrive.release.cluster.shared::cluster.b64 _, [%0];" ::"r"(bar) : "memory"); }
DI void mbar_expect(uint32_t bar, uint32_t tx) { asm volatile("mbarrier.arrive.expect_tx.shared::cta.b64 _, [%0], %1;" ::"r"(bar), "r"(tx) : "memory"); }
DI void mbar_arrive_if(bool p, uint32_t bar) { asm volatile("{.reg .pred p; setp.ne.b32 p, %1, 0; @p mbarrier.arrive.shared::cta.b64 _, [%0];}" ::"r"(bar), "r"((int)p) : "memory"); }
DI void mbar_arrive_if(bool p, uint32_t bar, uint32_t cnt) {
  asm volatile("{.reg .pred p; setp.ne.b32 p, %1, 0; @p mbarrier.arrive.shared::cta.b64 _, [%0], %2;}" ::"r"(bar), "r"((int)p), "r"(cnt) : "memory");
}
DI void mbar_expect_if(bool p, uint32_t bar, uint32_t tx) {
  asm volatile("{.reg .pred p; setp.ne.b32 p, %2, 0; @p mbarrier.arrive.expect_tx.shared::cta.b64 _, [%0], %1;}" ::"r"(bar), "r"(tx), "r"((int)p) : "memory");
}
DI bool mbar_test(uint32_t bar, uint32_t par) {
  uint32_t ok;
  asm volatile("{.reg .pred p; mbarrier.test_wait.parity.shared::cta.b64 p, [%1], %2; selp.u32 %0, 1, 0, p;}" : "=r"(ok) : "r"(bar), "r"(par) : "memory");
  return ok;
}
DI void mbar_wait(uint32_t bar, uint32_t par) {
  asm volatile(
      "{.reg .pred p;\n"
      "LOOP:\n"
      "mbarrier.try_wait.parity.shared::cta.b64 p, [%0], %1;\n"
      "@!p bra LOOP;\n}" ::"r"(bar), "r"(par) : "memory");
}
DI void mbar_wait_wd(uint32_t bar, uint32_t par) {
  asm volatile(
      "{.reg .pred p; .reg .u32 c;\n"
      "mov.u32 c, 0;\n"
      "LOOP:\n"
      "mbarrier.try_wait.parity.shared::cta.b64 p, [%0], %1;\n"
      "@p bra DONE;\n"
      "add.u32 c, c, 1;\n"
      "setp.lt.u32 p, c, 4000000;\n"
      "@p bra LOOP;\n"
      "trap;\n"
      "DONE:\n}" ::"r"(bar), "r"(par) : "memory");
}
DI void fence_async_smem() { asm volatile("fence.proxy.async.shared::cta;" ::: "memory"); }
DI void fence_async_global() { asm volatile("fence.proxy.async.global;" ::: "memory"); }
DI void bar_sync(int id, int n) { asm volatile("bar.sync %0, %1;" ::"r"(id), "r"(n) : "memory"); }
DI void bar_arrive(int id, int n) { asm volatile("bar.arrive %0, %1;" ::"r"(id), "r"(n) : "memory"); }
DI void cluster_sync() { asm volatile("barrier.cluster.arrive.release.aligned; barrier.cluster.wait.acquire.aligned;" ::: "memory"); }
DI bool elect_one() {
  uint32_t p;
  asm volatile("{.reg .pred p; elect.sync _|p, 0xffffffff; selp.u32 %0, 1, 0, p;}" : "=r"(p));
  return p;
}
DI void bulk_g2s(uint32_t dst, const void* src, uint32_t bytes, uint32_t bar) {
  asm volatile("cp.async.bulk.shared::cluster.global.mbarrier::complete_tx::bytes [%0], [%1], %2, [%3];" ::"r"(dst), "l"(src), "r"(bytes), "r"(bar) : "memory");
}
DI void bulk_g2s_mc(uint32_t dst, const void* src, uint32_t bytes, uint32_t bar, uint16_t mask) {
  asm volatile("cp.async.bulk.shared::cluster.global.mbarrier::complete_tx::bytes.multicast::cluster [%0], [%1], %2, [%3], %4;" ::"r"(dst), "l"(src), "r"(bytes), "r"(bar), "h"(mask) : "memory");
}
DI void bulk_s2s(uint32_t dst, uint32_t src, uint32_t bytes, uint32_t bar) {
  asm volatile("cp.async.bulk.shared::cluster.shared::cta.mbarrier::complete_tx::bytes [%0], [%1], %2, [%3];" ::"r"(dst), "r"(src), "r"(bytes), "r"(bar) : "memory");
}
DI void tma_2d(uint32_t dst, const CUtensorMap* map, int c0, int c1, uint32_t bar) {
  asm volatile("cp.async.bulk.tensor.2d.shared::cluster.global.mbarrier::complete_tx::bytes [%0], [%1, {%3, %4}], [%2];" ::"r"(dst), "l"(map), "r"(bar), "r"(c0), "r"(c1) : "memory");
}
DI void tma_pf(const CUtensorMap* map, int c0, int c1) {
  asm volatile("cp.async.bulk.prefetch.tensor.2d.L2.global [%0, {%1, %2}];" ::"l"(map), "r"(c0), "r"(c1) : "memory");
}
DI void st_async4(uint32_t a, uint32_t x, uint32_t y, uint32_t z, uint32_t w, uint32_t bar) {
  asm volatile("st.async.shared::cluster.mbarrier::complete_tx::bytes.v4.b32 [%0], {%1,%2,%3,%4}, [%5];" ::"r"(a), "r"(x), "r"(y), "r"(z), "r"(w), "r"(bar) : "memory");
}
DI void st_async2(uint32_t a, uint32_t x, uint32_t y, uint32_t bar) {
  asm volatile("st.async.shared::cluster.mbarrier::complete_tx::bytes.v2.b32 [%0], {%1,%2}, [%3];" ::"r"(a), "r"(x), "r"(y), "r"(bar) : "memory");
}
DI void st_async1(uint32_t a, uint32_t x, uint32_t bar) {
  asm volatile("st.async.shared::cluster.mbarrier::complete_tx::bytes.b32 [%0], %1, [%2];" ::"r"(a), "r"(x), "r"(bar) : "memory");
}
DI void sts32(uint32_t a, uint32_t x) { asm volatile("st.shared.b32 [%0], %1;" ::"r"(a), "r"(x) : "memory"); }
DI void sts128(uint32_t a, uint4 v) { asm volatile("st.shared.v4.b32 [%0], {%1,%2,%3,%4};" ::"r"(a), "r"(v.x), "r"(v.y), "r"(v.z), "r"(v.w) : "memory"); }
DI uint32_t lds32(uint32_t a) { uint32_t v; asm volatile("ld.shared.b32 %0, [%1];" : "=r"(v) : "r"(a) : "memory"); return v; }
DI uint2 lds64(uint32_t a) { uint2 v; asm volatile("ld.shared.v2.b32 {%0,%1}, [%2];" : "=r"(v.x), "=r"(v.y) : "r"(a) : "memory"); return v; }
DI uint4 lds128(uint32_t a) { uint4 v; asm volatile("ld.shared.v4.b32 {%0,%1,%2,%3}, [%4];" : "=r"(v.x), "=r"(v.y), "=r"(v.z), "=r"(v.w) : "r"(a) : "memory"); return v; }
DI void stsm4(uint32_t a, uint32_t r0, uint32_t r1, uint32_t r2, uint32_t r3) {
  asm volatile("stmatrix.sync.aligned.m8n8.x4.shared.b16 [%0], {%1,%2,%3,%4};" ::"r"(a), "r"(r0), "r"(r1), "r"(r2), "r"(r3) : "memory");
}
DI void stsm2(uint32_t a, uint32_t r0, uint32_t r1) {
  asm volatile("stmatrix.sync.aligned.m8n8.x2.shared.b16 [%0], {%1,%2};" ::"r"(a), "r"(r0), "r"(r1) : "memory");
}
DI uint32_t movm(uint32_t a) { uint32_t d; asm volatile("movmatrix.sync.aligned.m8n8.trans.b16 %0, %1;" : "=r"(d) : "r"(a)); return d; }
DI uint32_t pack2(float lo, float hi) { uint32_t d; asm("cvt.rn.bf16x2.f32 %0, %1, %2;" : "=r"(d) : "f"(hi), "f"(lo)); return d; }
DI uint4 ld_rlx4(const void* p) {
  uint4 v;
  asm volatile("ld.relaxed.gpu.global.v4.u32 {%0,%1,%2,%3}, [%4];" : "=r"(v.x), "=r"(v.y), "=r"(v.z), "=r"(v.w) : "l"(p) : "memory");
  return v;
}
DI void st_rlx4(void* p, uint32_t x, uint32_t y, uint32_t z, uint32_t w) {
  asm volatile("st.relaxed.gpu.global.v4.u32 [%0], {%1,%2,%3,%4};" ::"l"(p), "r"(x), "r"(y), "r"(z), "r"(w) : "memory");
}
DI void st_rlx1(void* p, uint32_t x) { asm volatile("st.relaxed.gpu.global.u32 [%0], %1;" ::"l"(p), "r"(x) : "memory"); }
DI uint32_t ld_acq(const uint32_t* p) { uint32_t v; asm volatile("ld.acquire.gpu.global.u32 %0, [%1];" : "=r"(v) : "l"(p) : "memory"); return v; }
DI uint32_t ld_rlx(const uint32_t* p) { uint32_t v; asm volatile("ld.relaxed.gpu.global.u32 %0, [%1];" : "=r"(v) : "l"(p) : "memory"); return v; }
DI void red_rel(uint32_t* p, uint32_t v) { asm volatile("red.release.gpu.global.add.u32 [%0], %1;" ::"l"(p), "r"(v) : "memory"); }
DI void guard(uint32_t& g) { asm volatile("{.reg .pred p; add.u32 %0, %0, 1; setp.gt.u32 p, %0, 8000000; @p trap;}" : "+r"(g)); }
DI void poll_ge(const uint32_t* p, uint32_t target) {
  asm volatile(
      "{.reg .pred p; .reg .u32 v;\n"
      "LOOP:\n"
      "ld.acquire.gpu.global.u32 v, [%0];\n"
      "setp.lt.u32 p, v, %1;\n"
      "vote.sync.any.pred p, p, 0xffffffff;\n"
      "@p bra.uni LOOP;\n}" ::"l"(p), "r"(target) : "memory");
}
DI float ex2(float x) { float y; asm("ex2.approx.ftz.f32 %0, %1;" : "=f"(y) : "f"(x)); return y; }

DI void wg_fence() { asm volatile("wgmma.fence.sync.aligned;" ::: "memory"); }
DI void wg_commit() { asm volatile("wgmma.commit_group.sync.aligned;" ::: "memory"); }
template <int N> DI void wg_wait() { asm volatile("wgmma.wait_group.sync.aligned %0;" ::"n"(N) : "memory"); }
template <int N> DI void reg_fence(float* d) {
#pragma unroll
  for (int i = 0; i < N; i++) asm volatile("" : "+f"(d[i])::"memory");
}
__host__ __device__ constexpr uint64_t mkdesc(uint32_t addr, uint32_t lbo, uint32_t sbo, uint32_t sw) {
  return (uint64_t)((addr & 0x3FFFF) >> 4) | ((uint64_t)(lbo >> 4) << 16) | ((uint64_t)(sbo >> 4) << 32) | ((uint64_t)sw << 62);
}

#define ACC4(d, o) "+f"(d[o]), "+f"(d[o + 1]), "+f"(d[o + 2]), "+f"(d[o + 3])
#define ACC16(d, o) ACC4(d, o), ACC4(d, o + 4), ACC4(d, o + 8), ACC4(d, o + 12)
#define ACC20(d) ACC16(d, 0), ACC4(d, 16)

template <int TA, int TB> DI void wg_ss40(float* d, uint64_t da, uint64_t db, int sc) {
  asm volatile("{.reg .pred p; setp.ne.b32 p, %22, 0;\n"
               "wgmma.mma_async.sync.aligned.m64n40k16.f32.bf16.bf16 {%0,%1,%2,%3,%4,%5,%6,%7,%8,%9,%10,%11,%12,%13,%14,%15,%16,%17,%18,%19}, %20, %21, p, 1, 1, %23, %24;}"
               : ACC20(d) : "l"(da), "l"(db), "r"(sc), "n"(TA), "n"(TB));
}
DI void wg_rs40(float* d, uint32_t a0, uint32_t a1, uint32_t a2, uint32_t a3, uint64_t db, int sc) {
  asm volatile("{.reg .pred p; setp.ne.b32 p, %25, 0;\n"
               "wgmma.mma_async.sync.aligned.m64n40k16.f32.bf16.bf16 {%0,%1,%2,%3,%4,%5,%6,%7,%8,%9,%10,%11,%12,%13,%14,%15,%16,%17,%18,%19}, {%20,%21,%22,%23}, %24, p, 1, 1, 0;}"
               : ACC20(d) : "r"(a0), "r"(a1), "r"(a2), "r"(a3), "l"(db), "r"(sc));
}
DI void wg_rs32(float* d, uint32_t a0, uint32_t a1, uint32_t a2, uint32_t a3, uint64_t db, int sc) {
  asm volatile("{.reg .pred p; setp.ne.b32 p, %21, 0;\n"
               "wgmma.mma_async.sync.aligned.m64n32k16.f32.bf16.bf16 {%0,%1,%2,%3,%4,%5,%6,%7,%8,%9,%10,%11,%12,%13,%14,%15}, {%16,%17,%18,%19}, %20, p, 1, 1, 0;}"
               : ACC16(d, 0) : "r"(a0), "r"(a1), "r"(a2), "r"(a3), "l"(db), "r"(sc));
}
DI void wg_rs8(float* d, uint32_t a0, uint32_t a1, uint32_t a2, uint32_t a3, uint64_t db, int sc) {
  asm volatile("{.reg .pred p; setp.ne.b32 p, %9, 0;\n"
               "wgmma.mma_async.sync.aligned.m64n8k16.f32.bf16.bf16 {%0,%1,%2,%3}, {%4,%5,%6,%7}, %8, p, 1, 1, 0;}"
               : ACC4(d, 0) : "r"(a0), "r"(a1), "r"(a2), "r"(a3), "l"(db), "r"(sc));
}
DI void mma16816(float* c, const uint32_t* a, uint32_t b0, uint32_t b1) {
  asm volatile("mma.sync.aligned.m16n8k16.row.col.f32.bf16.bf16.f32 {%0,%1,%2,%3}, {%4,%5,%6,%7}, {%8,%9}, {%0,%1,%2,%3};"
               : ACC4(c, 0) : "r"(a[0]), "r"(a[1]), "r"(a[2]), "r"(a[3]), "r"(b0), "r"(b1));
}
DI void wg_ss8(float* d, uint64_t da, uint64_t db, int sc) {
  asm volatile("{.reg .pred p; setp.ne.b32 p, %6, 0;\n"
               "wgmma.mma_async.sync.aligned.m64n8k16.f32.bf16.bf16 {%0,%1,%2,%3}, %4, %5, p, 1, 1, 1, 1;}"
               : ACC4(d, 0) : "l"(da), "l"(db), "r"(sc));
}
DI void wg_rs16(float* d, uint32_t a0, uint32_t a1, uint32_t a2, uint32_t a3, uint64_t db, int sc) {
  asm volatile("{.reg .pred p; setp.ne.b32 p, %13, 0;\n"
               "wgmma.mma_async.sync.aligned.m64n16k16.f32.bf16.bf16 {%0,%1,%2,%3,%4,%5,%6,%7}, {%8,%9,%10,%11}, %12, p, 1, 1, 0;}"
               : ACC4(d, 0), ACC4(d, 4) : "r"(a0), "r"(a1), "r"(a2), "r"(a3), "l"(db), "r"(sc));
}
__device__ uint4 g_xn[2 * NSEG * 10 * 256];
__device__ uint4 g_oT[2 * NBLK * 96 * 1024];
constexpr int PART_RING = 96 * 256;
__device__ uint4 g_part[4 * PART_RING];
constexpr int MEM_OFF = 192;
#define P4 ~0u, ~0u, ~0u, ~0u
#define P16 P4, P4, P4, P4
#define P256 P16, P16, P16, P16, P16, P16, P16, P16, P16, P16, P16, P16, P16, P16, P16, P16
#define P2K P256, P256, P256, P256, P256, P256, P256, P256
#define P8K P2K, P2K, P2K, P2K
__device__ __align__(8192) uint32_t g_mem32[5 * 2 * 2 * 2048] = {P8K, P8K, P8K, P8K, P8K};
#define g_mem ((uint4*)g_mem32)
constexpr int C_XN = 0;
constexpr int C_O = C_XN + 2 * NBLK;
constexpr int C_HALF = C_O + 6 * 2 * NBLK;
constexpr int C_TOTAL = 512;
constexpr int CSTRIDE = 32;
__device__ uint32_t g_cnt[C_TOTAL * CSTRIDE];
constexpr uint32_t XN_TARGET = 128;

#define TRACE(c, n, i, v)
#define SLOG(i)
#define PROF(i)
#define PROFA(c)
#define PROFV(i, v)

constexpr uint32_t SMEM0 = 1024;
constexpr uint32_t SM_WK = 0, SM_WO = 81920, SM_H = 163840, SM_QT = 215040, QSTR = 1056  , SM_KT = SM_QT + 5 * QSTR + 1024,
                   SM_SR = SM_KT + 5120  , SM_PROF = SM_SR + 5760, R_SMEM = 232448,
                   SM_RED = SM_QT + 1024, SM_BAR = SM_RED + 768;
constexpr uint32_t SM_P = SM_KT, SM_OB = SM_QT + 3200;
constexpr uint32_t B_HFULL = SM_BAR, B_HEMPTY = SM_BAR + 40, B_MTRY = SM_BAR + 80, B_W = SM_BAR + 112, B_SR = B_W + 32,
                   B_PMEM = B_SR + 24, B_PTOK = B_SR + 32, B_OB = B_SR + 40, B_OPD = B_SR + 48, B_RFREE = B_SR + 56,
                   B_GATE = B_SR + 64, B_PSUM = B_SR + 72, B_END = B_SR + 80, B_PVI = B_SR + 88,
                   B_OPI = B_SR + 96, B_OTOK = B_SR + 112, SM_TOPI = B_SR + 128, B_PACE = SM_TOPI + 8,
                   SM_RS = SM_QT + 2 * QSTR + 1024;
static_assert(B_PACE + 32 <= SM_QT + 2 * QSTR, "barriers must fit the unused q row group");

struct RParams {
  uint64_t dH, dWK, dWO, dQT, dKT, dP, dOB[6];
  const char* w[4];
  const uint4* mem0;
  const uint32_t* x;
  int pf;
  int nslots, d3, pn, moff, ds, dh;
  int d2[10], d1[8];
  uint32_t slot[2 * NSEG];
};
static void r_fill_desc(RParams& p) {
  p.dH = mkdesc(SMEM0 + SM_H, 128, 2048, 0);
  p.dWK = mkdesc(SMEM0 + SM_WK, 1024, 1024, 1);
  p.dWO = mkdesc(SMEM0 + SM_WO, 1024, 1024, 1);
  for (int i = 0; i < 6; i++) p.dOB[i] = mkdesc(SMEM0 + SM_OB + (i < 3 ? 0 : (i - 3) * 1024), 128, 128, 0);
  p.dQT = mkdesc(SMEM0 + SM_QT, 128, QSTR, 0);
  p.dKT = mkdesc(SMEM0 + SM_KT, 128, 1024, 0);
  p.dP = mkdesc(SMEM0 + SM_P, 128, 640, 0);
}
DI uint64_t dadd(uint64_t d, int bytes) {
  uint64_t r;
  asm volatile("add.u64 %0, %1, %2;" : "=l"(r) : "l"(d), "l"((long long)(bytes / 16)));
  return r;
}
template <int BYTES> DI void dstep(uint64_t& d) { asm volatile("add.u64 %0, %0, %1;" : "+l"(d) : "n"((long long)(BYTES / 16))); }
__host__ __device__ constexpr int hoff(int ks) { return (ks >> 3) * 10240 + (ks & 7) * 256; }

DI int opaque(int v) { asm volatile("" : "+r"(v)); return v; }
DI uint32_t pin(uint32_t v, int lane) { return __shfl_sync(~0u, v + (lane >> 5), lane); }
DI char* pin(char* p, int lane) { return (char*)__shfl_sync(~0u, (unsigned long long)p, lane); }
DI float blo(uint32_t w) { return __uint_as_float(w << 16); }
DI float bhi(uint32_t w) { return __uint_as_float(w & 0xffff0000u); }
#define R_FB 1
#define PIN_DST 1
#define RG0 232
#define RG1 216
#define RG2 40
#define RG3 24
DI void ldsm4t(uint32_t* r, uint32_t a) {
  asm volatile("ldmatrix.sync.aligned.m8n8.x4.trans.shared.b16 {%0,%1,%2,%3}, [%4];" : "=r"(r[0]), "=r"(r[1]), "=r"(r[2]), "=r"(r[3]) : "r"(a) : "memory");
}
DI void st_tagged(void* p, float a, float b, uint32_t keep, uint32_t tagbit) {
  asm volatile("{.reg .b32 t; cvt.rn.bf16x2.f32 t, %2, %1; lop3.b32 t, t, %3, %4, 0xea; st.relaxed.gpu.global.b32 [%0], t;}" ::"l"(p), "f"(a), "f"(b),
               "r"(keep), "r"(tagbit) : "memory");
}
DI uint32_t lop_bad(uint32_t a, uint32_t b, uint32_t m) { uint32_t d; asm("lop3.b32 %0, %1, %2, %3, 0x7e;" : "=r"(d) : "r"(a), "r"(b), "r"(m)); return d; }
DI uint32_t lop_or3(uint32_t a, uint32_t b, uint32_t c) { uint32_t d; asm("lop3.b32 %0, %1, %2, %3, 0xfe;" : "=r"(d) : "r"(a), "r"(b), "r"(c)); return d; }
DI uint32_t clk() { uint32_t t; asm volatile("mov.u32 %0, %%clock;" : "=r"(t)); return t; }
DI void spin(uint32_t cyc) { const uint32_t t0 = clk(); while (__any_sync(~0u, clk() - t0 < cyc)) {} }
template <int NL> DI float2 poll_sum(const uint32_t* src, uint32_t tag, uint32_t even, uint32_t& g) {
  uint32_t r[NL];
  while (true) {
#pragma unroll
    for (int i = 0; i < NL; i++) r[i] = ld_rlx(src + i * 32);
    uint32_t bad = lop_or3(lop_bad(r[0], r[1], tag), lop_bad(r[2], r[3], tag), lop_bad(r[4], r[5], tag));
    if (NL == 12) bad = lop_or3(bad, lop_bad(r[6], r[7], tag), lop_bad(r[8], r[9], tag));
    asm volatile("lop3.b32 %0, %0, %1, %2, 0xa8;" : "+r"(bad) : "r"(lop_bad(r[NL - 2], r[NL - 1], tag)), "r"(even));
    if (!__any_sync(~0u, bad)) break;
    g++;
  }
  float x[NL / 2], y[NL / 2];
#pragma unroll
  for (int i = 0; i < NL / 2; i++) { x[i] = blo(r[2 * i]) + blo(r[2 * i + 1]); y[i] = bhi(r[2 * i]) + bhi(r[2 * i + 1]); }
  float2 u = make_float2((x[0] + x[1]) + (x[2] + x[3]), (y[0] + y[1]) + (y[2] + y[3]));
  if (NL == 12) { u.x += x[4] + x[5]; u.y += y[4] + y[5]; }
  return u;
}

constexpr int PLANE = 16 * 40 * 32, MAXPL = 13;
__device__ uint2 g_acc[(size_t)2 * NBLK * 2 * MAXPL * PLANE];
DI uint2* acc_planes(int lb, int d) { return g_acc + (size_t)((lb * 2 + d) * MAXPL) * PLANE; }
DI void ln_stats(const float4* v, uint32_t red, int warp, int lane, int bar, float& mean, float& rstd) {
  float s = 0.f;
#pragma unroll
  for (int i = 0; i < 5; i++) s += (v[i].x + v[i].y) + (v[i].z + v[i].w);
  s += __shfl_xor_sync(~0u, s, 1);
  s += __shfl_xor_sync(~0u, s, 2);
  s *= 1.f / 80;
  float q = 0.f;
#pragma unroll
  for (int i = 0; i < 5; i++) q += ((v[i].x - s) * (v[i].x - s) + (v[i].y - s) * (v[i].y - s)) + ((v[i].z - s) * (v[i].z - s) + (v[i].w - s) * (v[i].w - s));
  q += __shfl_xor_sync(~0u, q, 1);
  q += __shfl_xor_sync(~0u, q, 2);
  if ((lane & 3) == 0) asm volatile("st.shared.v2.f32 [%0], {%1,%2};" ::"r"(red + lane * 16 + warp * 8), "f"(s), "f"(q) : "memory");
  bar_sync(bar, 256);
  const uint4 t = lds128(red + lane * 16);
  const float m0 = __uint_as_float(t.x), m1 = __uint_as_float(t.z);
  mean = m0 + m1;
  mean += __shfl_xor_sync(~0u, mean, 1);
  mean += __shfl_xor_sync(~0u, mean, 2);
  mean *= 0.125f;
  q = __uint_as_float(t.y) + __uint_as_float(t.w) + 80.f * ((m0 - mean) * (m0 - mean) + (m1 - mean) * (m1 - mean));
  q += __shfl_xor_sync(~0u, q, 1);
  q += __shfl_xor_sync(~0u, q, 2);
  rstd = rsqrtf(q * (1.f / DM) + 1e-5f);
}
template <int SH, int STR> DI void store_img(uint32_t* dst, const float4* v, int warp, float mean, float rstd) {
#pragma unroll
  for (int i = 0; i < 5; i++) {
    const int U = 10 * warp + 2 * i;
    uint32_t* p = dst + (U >> SH) * STR + (U & ((1 << SH) - 1)) * 32;
    p[0] = pack2((v[i].x - mean) * rstd, (v[i].y - mean) * rstd);
    p[32] = pack2((v[i].z - mean) * rstd, (v[i].w - mean) * rstd);
  }
}
DI uint32_t* xn_row_group(int layer, int rg) { return (uint32_t*)(g_xn + (size_t)((layer * NSEG + (rg >> 2)) * 2560 + (rg & 3) * 128)); }

DI void first_ln(const uint32_t* a, int rg, uint32_t red, int warp, int lane, int bar) {
  float4 v[5];
#pragma unroll
  for (int i = 0; i < 5; i++) {
    v[i] = make_float4(blo(a[2 * i]), bhi(a[2 * i]), blo(a[2 * i + 1]), bhi(a[2 * i + 1]));
    acc_planes(rg >> 4, 0)[((rg & 15) * 40 + warp * 5 + i) * 32 + lane] = make_uint2(a[2 * i], a[2 * i + 1]);
  }
  float mean, rstd;
  ln_stats(v, red, warp, lane, bar, mean, rstd);
  store_img<4, 2048>(xn_row_group(0, rg) + lane, v, warp, mean, rstd);
}
#define QK_P0 32
#define QK_KB 0
struct QKOrder { int op[76]; };
__host__ __device__ constexpr QKOrder qk_order() {
  QKOrder o = {};
  int n = 0, k = 0, q = 0;
  for (; k < QK_P0; k++, q++) { o.op[n++] = 64 | k; o.op[n++] = q; }
  for (int i = 0; i < QK_KB; i++) o.op[n++] = 64 | k++;
  for (int i = 0; i < -QK_KB; i++) o.op[n++] = q++;
  const int nk = 40 - k, nq = 36 - q;
  for (int i = 0, dk = 0, dq = 0; i < nk + nq; i++) {
    if (dq * nk <= dk * nq + (QK_KB ? 0 : -nq) && dq < nq) { o.op[n++] = q++; dq++; } else if (dk < nk) { o.op[n++] = 64 | k++; dk++; } else { o.op[n++] = q++; dq++; }
  }
  return o;
}
__global__ void __launch_bounds__(512, 1)
r_kernel(const __grid_constant__ CUtensorMap mapWq, const __grid_constant__ CUtensorMap mapWk, const __grid_constant__ CUtensorMap mapWv,
         const __grid_constant__ CUtensorMap mapWo, const __grid_constant__ RParams prm) {
  const uint32_t sb = smem_base();
  const int wid = __shfl_sync(~0u, threadIdx.x >> 5, 0);
  const int lane0 = __shfl_sync(~0u, threadIdx.x & 31, threadIdx.x & 31);
  const int lane = lane0;
  const int warp = wid & 3, wg = wid >> 2;
  const uint32_t rank = blockIdx.x, head = blockIdx.y, cta = head * 3 + rank;
  const uint32_t peer1 = mapa(sb, rank == 2 ? 0 : rank + 1), peer2 = mapa(sb, rank == 0 ? 2 : rank - 1);
  const int nslots = prm.nslots;

  SLOG(0);
  if (threadIdx.x == 384) {
    if ((sb & 0x3FFFF) != SMEM0) __trap();
    for (int c = 0; c < 5; c++) { mbar_init(sb + B_HFULL + 8 * c, 2); mbar_init(sb + B_HEMPTY + 8 * c, c == 4 ? 8 : 4); }
    for (int c = 0; c < 11; c++) mbar_init(sb + B_MTRY + 8 * c, 1);
    mbar_init(sb + B_PTOK, rank == 0 ? 3 : 2); mbar_init(sb + B_OB, 5); mbar_init(sb + B_OPD, 4);
    mbar_init(sb + B_OPI, 1); mbar_init(sb + B_OPI + 8, 1); mbar_init(sb + B_RFREE, 1); mbar_init(sb + B_GATE, 1); mbar_init(sb + B_PMEM, 2); mbar_init(sb + B_PSUM, 2); mbar_init(sb + B_PVI, 1); mbar_init(sb + B_OTOK, 4); mbar_init(sb + B_OTOK + 8, 4); mbar_init(sb + B_END, 15);
    for (int c = 0; c < 4; c++) mbar_init(sb + B_PACE + 8 * c, 1);
    asm volatile("fence.mbarrier_init.release.cluster;" ::: "memory");
    fence_async_smem();
  }
  asm volatile("griddepcontrol.launch_dependents;");
  asm volatile("barrier.cluster.arrive.release.aligned;" ::: "memory");

  if (wg < 2) {
  {
    uint32_t xa[10];
    const uint32_t* src = prm.x + (size_t)(cta * 8 + (lane >> 2)) * (DM / 2) + wid * 40 + (lane & 3);
#pragma unroll
    for (int i = 0; i < 10; i++) xa[i] = __ldg(src + i * 4);
    asm volatile("barrier.cluster.wait.acquire.aligned;" ::: "memory");
    first_ln(xa, cta, sb + SM_SR, wid, lane, 8);
    bar_arrive(10, 288);
  }
  if (wg == 0) {
    asm volatile("setmaxnreg.inc.sync.aligned.u32 %0;" ::"n"(RG0));
    uint32_t wq[160];
    SLOG(1);
    mbar_wait(sb + B_W, 0);
    SLOG(2);
    {
      const uint32_t ld_off = ((lane >> 4) * 8 + (lane & 7)) * 128 + (((2 * warp + ((lane >> 3) & 1)) ^ (lane & 7)) << 4);
#pragma unroll
      for (int ks = 0; ks < 40; ks++) ldsm4t(wq + 4 * ks, sb + SM_WO + ks * 2048 + ld_off);
    }
    fence_async_smem();
    bar_arrive(5, 160);
    mbar_wait(sb + B_W + 16, 0);
    SLOG(3);
    const uint32_t st_addr = pin(sb + SM_QT + (lane >> 4) * 1024 + (2 * warp + ((lane >> 3) & 1)) * 128 + (lane & 7) * 16, lane);
    const uint32_t sq_addr = pin(sb + SM_QT + (2 + (lane & 3)) * QSTR + warp * 256 + (lane >> 2) * 16, lane);
    const uint32_t to_lo = warp == 0 ? peer1 : mapa(sb, warp == 2 ? 2 : 0), to_hi = warp == 0 ? peer2 : mapa(sb, warp == 1 ? 1 : 0);
    const uint32_t sr_off = SM_SR + warp * 1920 + rank * 640, sr_bar = B_SR + warp * 8;
    const uint32_t sa0 = pin(to_lo + sr_off + lane * 16, lane), sb0 = pin(to_lo + sr_bar, lane), sa1 = pin(to_lo + sr_off + 512 + lane * 4, lane), sb1 = pin(sb0, lane);
    const uint32_t sa2 = pin(to_hi + sr_off + lane * 16, lane), sb2 = pin(to_hi + sr_bar, lane), sa3 = pin(to_hi + sr_off + 512 + lane * 4, lane), sb3 = pin(sb2, lane);
#pragma unroll 1
    for (int n = 0; n < nslots; n++) {
      const uint32_t par = n & 1;
      PROFA(warp == PW);
      float qa[20], ka[20];
      uint64_t rk = prm.dWK, rh = prm.dH, rq;
      auto K = [&](int ks) { wg_ss40<1, 0>(ka, rk, rh, ks != 0); };
      auto Q = [&](int ks, uint64_t db) { wg_rs40(qa, wq[4 * ks], wq[4 * ks + 1], wq[4 * ks + 2], wq[4 * ks + 3], db, ks != 0); };
      auto next = [&](uint64_t& d, int ks) { if ((ks & 7) == 7) dstep<10240 - 7 * 256>(d); else dstep<256>(d); };
      constexpr QKOrder ord = qk_order();
      auto first = [&](int g, int c) { for (int i = 0; i < 76; i++) if ((ord.op[i] & 63) >> 3 == c) return i >> 2 == g; return false; };
      bool ok = true;
      mbar_wait(sb + B_HFULL, par);
#pragma unroll
      for (int g = 0; g < 19; g++) {
        if (!ok) {
#pragma unroll
          for (int c = 1; c < 5; c++) if (first(g, c)) mbar_wait(sb + B_HFULL + 8 * c, par);
          mbar_wait(sb + B_GATE, 1);
        }
        if (g == 0) PROF(0);
        if (g < 18) ok = mbar_test(sb + B_GATE, 1);
#pragma unroll
        for (int c = 1; c < 5; c++) if (first(g + 1, c)) ok &= mbar_test(sb + B_HFULL + 8 * c, par);
        wg_fence();
#pragma unroll
        for (int i = 4 * g; i < 4 * g + 4; i++) {
          const int ks = ord.op[i] & 63;
          if (i < 2 * QK_P0) {
            if (ord.op[i] & 64) K(ks);
            else { Q(ks, rh); dstep<2048>(rk); next(rh, ks); if (i == 2 * QK_P0 - 1) rq = rh; }
          } else if (ord.op[i] & 64) { K(ks); if (ks < 39) { dstep<2048>(rk); next(rh, ks); } }
          else { Q(ks, rq); next(rq, ks); }
        }
        if (g == 17) wg_commit();
      }
      wg_commit();
#pragma unroll
      for (int ks = 36; ks < 40; ks++) { Q(ks, rq); if (ks < 39) dstep<256>(rq); }
      wg_commit();
      wg_wait<2>();
      bar_arrive(2, 256);
      mbar_wait(sb + B_OPD, par ^ 1);
      wg_wait<1>();
      reg_fence<20>(ka);
      stsm2(st_addr + (SM_KT - SM_QT), pack2(ka[0], ka[1]), pack2(ka[2], ka[3]));
      stsm4(st_addr + (SM_KT - SM_QT) + 1024, pack2(ka[4], ka[5]), pack2(ka[6], ka[7]), pack2(ka[8], ka[9]), pack2(ka[10], ka[11]));
      stsm4(st_addr + (SM_KT - SM_QT) + 3072, pack2(ka[12], ka[13]), pack2(ka[14], ka[15]), pack2(ka[16], ka[17]), pack2(ka[18], ka[19]));
      wg_wait<0>();
      reg_fence<20>(qa);
      PROF(9);
      stsm2(st_addr, pack2(qa[0], qa[1]), pack2(qa[2], qa[3]));
      sts128(sq_addr, make_uint4(pack2(qa[4], qa[5]), pack2(qa[8], qa[9]), pack2(qa[12], qa[13]), pack2(qa[16], qa[17])));
      sts128(sq_addr + 128, make_uint4(pack2(qa[6], qa[7]), pack2(qa[10], qa[11]), pack2(qa[14], qa[15]), pack2(qa[18], qa[19])));
      mbar_arrive_if(lane == 0, sb + B_HEMPTY + 32);
      fence_async_smem();
      bar_sync(1, 128);
      PROF(1);
      wg_fence();
#pragma unroll
      for (int k = 0; k < 4; k++) wg_ss40<1, 1>(qa, dadd(prm.dQT, k * 256), dadd(prm.dKT, k * 256), k != 0);
      wg_commit();
      bar_arrive(7, 256);
      wg_wait<0>();
      reg_fence<20>(qa);
      PROF(3);
      if (warp < 3) {
        uint32_t p[5];
#pragma unroll
        for (int j = 0; j < 5; j++) p[j] = pack2(qa[4 * j], qa[4 * j + 1]);
        if (warp == 0) {
          st_async4(sa0, p[0], p[1], p[2], p[3], sb0);
          st_async4(sa2, p[0], p[1], p[2], p[3], sb2);
          st_async1(sa1, p[4], sb1);
          st_async1(sa3, p[4], sb3);
          sts128(sb + sr_off + lane * 16, make_uint4(p[0], p[1], p[2], p[3]));
          sts32(sb + sr_off + 512 + lane * 4, p[4]);
          __syncwarp();
          mbar_expect_if(lane == 0, sb + B_SR, 1280);
        } else {
          uint32_t h[5];
#pragma unroll
          for (int j = 0; j < 5; j++) h[j] = pack2(qa[4 * j + 2], qa[4 * j + 3]);
          spin(prm.d3);
          st_async4(sa0, p[0], p[1], p[2], p[3], sb0);
          st_async4(sa2, h[0], h[1], h[2], h[3], sb2);
          st_async1(sa1, p[4], sb1);
          st_async1(sa3, h[4], sb3);
        }
      }
    }
  } else {
    asm volatile("setmaxnreg.inc.sync.aligned.u32 %0;" ::"n"(RG1));
    uint32_t wv[160];
    mbar_wait(sb + B_W + 8, 0);
    SLOG(4);
    {
      const uint32_t ld_off = ((lane >> 4) * 8 + (lane & 7)) * 128 + (((2 * warp + ((lane >> 3) & 1)) ^ (lane & 7)) << 4);
#pragma unroll
      for (int ks = 0; ks < 40; ks++) ldsm4t(wv + 4 * ks, sb + SM_WO + ks * 2048 + ld_off);
    }
    fence_async_smem();
    bar_arrive(6, 160);
    const uint64_t dH = prm.dH;
    uint32_t op[8];
    const uint32_t ob_off = SM_OB + (4 * rank + warp) * 256 + lane * 4;
    const uint32_t oa0 = pin(peer1 + ob_off, lane), ob0 = pin(peer1 + B_OB, lane), oa1 = pin(peer2 + ob_off, lane), ob1 = pin(peer2 + B_OB, lane);
    const uint32_t oa2 = pin(oa0 + 128, lane), ob2 = pin(ob0, lane), oa3 = pin(oa1 + 128, lane), ob3 = pin(ob1, lane);
    const uint32_t o_loc = pin(sb + ob_off, lane), rs_addr = pin(sb + SM_RS + (lane & 3) * 8, lane);
    const uint32_t tok_off = pin((cta * 1024 + 64 * warp + (lane ^ (lane >> 3))) * 16, lane), keep = pin((lane & 1) ? ~0u : ~1u, lane);
    const uint32_t pb_off = pin((8 * rank + 2 * warp) * 4096 + head * 128 + lane * 4, lane);
    const uint32_t ph_off = pin(72 * 4096 + 2 * warp * 12288 + cta * 64 + (lane & 2) * 3072 + (lane >> 2) * 8 + (lane & 1) * 4, lane);
    auto store_tok = [&](int m, int lane) {
      const uint32_t ls = prm.slot[m] & 127, sig = prm.slot[m] >> 16;
      uint4* dst = (uint4*)((char*)(g_oT + (size_t)((ls >> 2) * (96 * 1024) + (ls & 3) * 256)) + tok_off);
      dst[0] = make_uint4(op[0], op[1], op[2], op[3]);
      dst[32] = make_uint4(op[4], op[5], op[6], op[7]);
      __syncwarp();
      mbar_arrive_if(sig && lane == 0, sb + B_OTOK + (ls >> 6) * 8);
    };
#pragma unroll 1
    for (int n = 0; n < nslots; n++) {
      const uint32_t par = n & 1;
      const int lane = opaque(lane0);
      PROFA(warp == PW);
      float va[20];
      mbar_expect_if(warp == 0 && lane == 0, sb + B_PTOK, rank == 0 ? 1280 : 1920);
      bar_sync(2, 256);
#pragma unroll
      for (int g = 0; g < 10; g++) {
        wg_fence();
#pragma unroll
        for (int ks = 4 * g; ks < 4 * g + 4; ks++) { wg_rs40(va, wv[4 * ks], wv[4 * ks + 1], wv[4 * ks + 2], wv[4 * ks + 3], dadd(dH, hoff(ks)), ks != 0); }
        wg_commit();
        if (g >= 2 && !(g & 1)) {
          wg_wait<1>();
          if (lane == 0) mbar_arrive(sb + B_HEMPTY + 8 * (g / 2 - 1));
        }
        if (g == 2) bar_sync(7, 256);
      }
      wg_wait<0>();
      reg_fence<20>(va);
      if (lane == 0) mbar_arrive(sb + B_HEMPTY + 32);
      PROF(10);
      uint32_t vf[10];
#pragma unroll
      for (int j = 0; j < 10; j++) {
        const int i = (j + 4) % 10;
        asm volatile("cvt.rn.bf16x2.f32 %0, %1, %2;" : "=r"(vf[i]) : "f"(va[2 * i + 1]), "f"(va[2 * i]));
        if (j == 5) mbar_wait(sb + B_W + 8, 0);
      }
      uint32_t z0, z1;
      asm volatile("shr.u32 %0, %2, 5; shr.u32 %1, %2, 6;" : "=r"(z0), "=r"(z1) : "r"(lane));
      const uint32_t info = prm.slot[n];
      const uint32_t tagbit = ~(info >> 1) & ~keep;
      char* const ring = (char*)(g_part + (size_t)((((info >> 5) & 2) + (info & 1)) * PART_RING));
      char* const pb = pin(ring + pb_off, lane);
      char* const ph = ring + ph_off;
      mbar_wait(sb + B_PMEM, par);
      float om[4];
      wg_fence();
      wg_rs8(om, vf[0], vf[1], vf[2], vf[3], prm.dP, 0);
      wg_rs8(om, vf[4], vf[5], vf[6], vf[7], dadd(prm.dP, 256), 1);
      wg_rs8(om, vf[8], vf[9], z0, z1, dadd(prm.dP, 512 - (128 << 16)), 1);
      wg_commit();
      {
        wg_wait<0>();
        reg_fence<4>(om);
        const uint32_t b0 = pack2(om[0], om[1]), b1 = pack2(om[2], om[3]);
        st_async1(oa0, b0, ob0);
        st_async1(oa1, b0, ob1);
        st_async1(oa2, b1, ob2);
        st_async1(oa3, b1, ob3);
        sts32(o_loc, b0);
        sts32(o_loc + 128, b1);
        fence_async_smem();
        __syncwarp();
        mbar_arrive_if(lane == 0, sb + B_OB);
      }
      PROF(11);
      {
        float c[8];
        mbar_wait(sb + B_PSUM, par);
        const uint2 rs = lds64(rs_addr);
        const float r0 = __uint_as_float(rs.x), r1 = __uint_as_float(rs.y);
        if (n == 0) { SLOG(5); mbar_wait(sb + B_W + 24, 0); SLOG(6); }
        mbar_wait(sb + B_OB, par);
        asm volatile("fence.proxy.async::generic.acquire.sync_restrict::shared::cluster.cluster;" ::: "memory");
        PROF(16);
        if ((info & 63) == NSEG - 1) {
          mbar_wait(sb + B_OPI + par * 8, (n >> 1) & 1);
          mbar_arrive_if(warp == 3 && lane == 0, sb + B_GATE);
#pragma unroll
          for (int p = 0; p < 6; p++) st_rlx1(pb + (p >> 1) * 98304 + (p & 1) * 4096, tagbit);
          st_rlx1(ph, tagbit);
          st_rlx1(ph + 12288, tagbit);
        } else {
#pragma unroll
        for (int p = 0; p < 4; p++) {
          float* const cur = c + 4 * (p & 1);
          float* const prv = c + 4 * (~p & 1);
          if (p == 2) mbar_wait(sb + B_OPI + par * 8, (n >> 1) & 1);
          wg_fence();
#pragma unroll
          for (int ks = 0; ks < (p < 3 ? 12 : 4); ks++) {
            wg_ss8(cur, dadd(prm.dWO, p * 24576 + ks * 2048), dadd(prm.dOB[p < 3 ? p : 3 + rank], ks * 256), ks != 0);
            if (p == 3 && ks == 3) mbar_arrive_if(warp == 3 && lane == 0, sb + B_GATE);
            if (p > 0 && ks == 3) {
              wg_commit();
              wg_wait<1>();
              reg_fence<4>(prv);
              st_tagged(pb + (p - 1) * 98304, prv[0] * r0, prv[1] * r1, keep, tagbit);
              st_tagged(pb + (p - 1) * 98304 + 4096, prv[2] * r0, prv[3] * r1, keep, tagbit);
            }
          }
          if (p < 3) wg_commit();
        }
        wg_wait<0>();
        reg_fence<4>(c + 4);
        st_tagged(ph, c[4] * r0, c[5] * r1, keep, tagbit);
        st_tagged(ph + 12288, c[6] * r0, c[7] * r1, keep, tagbit);
        }
        PROF(17);
      }
      mbar_wait(sb + B_PTOK, par);
      PROF(12);
      {
        float ot[16];
        wg_fence();
        wg_rs32(ot, vf[0], vf[1], vf[2], vf[3], dadd(prm.dP, 640), 0);
        wg_rs32(ot, vf[4], vf[5], vf[6], vf[7], dadd(prm.dP, 640 + 256), 1);
        wg_rs32(ot, vf[8], vf[9], z0, z1, dadd(prm.dP, 640 + 512 - (128 << 16)), 1);
        wg_commit();
        wg_wait<0>();
        reg_fence<16>(ot);
#pragma unroll
        for (int i = 0; i < 8; i++) op[(i & 1) * 4 + (i >> 1)] = pack2(ot[2 * i], ot[2 * i + 1]);
      }
      if (lane == 0) mbar_arrive(sb + B_OPD);
      PROF(13);
      if (info & 128) spin(prm.ds);
      store_tok(n, lane);
    }
  }
  } else if (wg == 2) {
    asm volatile("setmaxnreg.dec.sync.aligned.u32 %0;" ::"n"(RG2));
    asm volatile("barrier.cluster.wait.acquire.aligned;" ::: "memory");
    if (warp == 1) {
      const uint32_t depth = prm.pf & 7;
#pragma unroll 1
      for (uint32_t i = 0; i < 20 + depth; i++) {
        if (i >= depth) {
          const uint32_t j = i - depth;
          mbar_wait_wd(sb + B_PACE + 8 * (j & 3), (j >> 2) & 1);
          if (j % 5 == 4) mbar_arrive_if(lane == 0 && (j != 14 || depth == 1), sb + B_W + (j == 4 ? 0 : j == 9 ? 16 : j == 14 ? 8 : 24));
        }
        if (i >= 20) continue;
        const uint32_t m = i / 5, k = i % 5, bar = sb + B_PACE + 8 * (i & 3);
        if (i == 10) bar_sync(5, 160);
        if (i == 15) {
          if ((prm.pf & 8) && elect_one())
            for (int q = 0; q < 4; q++) tma_pf(&mapWo, (q / 3 * 3 + rank) * 64, head * DH + q % 3 * 64);
#pragma unroll 1
          for (uint32_t j = 16 - depth; j < 15; j++) mbar_wait_wd(sb + B_PACE + 8 * (j & 3), (j >> 2) & 1);
          mbar_arrive_if(lane == 0 && depth > 1, sb + B_W + 8);
          bar_sync(6, 160);
        }
        if (elect_one()) {
          mbar_expect(bar, 16384);
          if (m < 3) tma_2d(sb + (m == 1 ? SM_WK : SM_WO) + k * 16384, m == 0 ? &mapWq : m == 1 ? &mapWk : &mapWv, cta * 64, k * 128, bar);
          else
            for (uint32_t q = 2 * k; q < 2 * k + 2; q++)
              tma_2d(sb + SM_WO + q * 8192, &mapWo, q < 9 ? (q / 3 * 3 + rank) * 64 : 576, head * DH + (q < 9 ? q % 3 : rank) * 64, bar);
        }
      }
    }
    if (warp == 2 && cta < 80 && lane < 16)
      g_mem[(cta >> 4) * 2048 + (lane >> 3) * 1024 + prm.moff + (cta & 15) * 8 + (lane & 7)] = prm.mem0[(lane & 7) * 80 + cta];
    if (warp == 3) {
      bar_sync(10, 288);
      if (lane == 0) red_rel(&g_cnt[(C_XN + (cta >> 4)) * CSTRIDE], 8);
    }
    const uint32_t grp = warp == 1 ? 1 + rank : 4 - (rank >> 1);
    constexpr float SC = 0.07216878364870322f * 1.4426950408889634f;
    const bool split = cta >= 72;
    const uint32_t wd = split ? 72 * 16 + cta * 16 : cta * 32;
    const uint32_t src_off = pin(split ? 72 * 4096 + (cta - 72) * 6144 + warp * 1536 + (lane & 2) * 32 + (lane >> 2) * 8 + (lane & 1) * 4 : cta * 4096 + warp * 1024 + lane * 4, lane);
    const uint32_t dst_off = pin(((wd >> 9) * 8192 + prm.moff * 4 + (wd & 511) + lane) * 4, lane);
    const uint32_t red = pin(sb + SM_RED + (warp < 2 ? 0 : (warp - 1) * 256) + lane * 8, lane);
    const uint32_t fl = (warp & 2) * 8 + (lane >> 3) * 4 + (lane & 3), hf = lane & 4;
    const uint32_t s0 = pin(sb + SM_SR + fl * 16 + hf * 2, lane), s1 = pin(sb + fl * 4, lane), pd = pin(s1 + hf * 64, lane);
    const uint32_t even = pin(~lane & 1, lane);
    uint32_t nred = 0;
    const uint32_t arm = pin(warp == 0 && (lane == 5 || ((lane == 1 || lane == 2) && lane + rank != 3)) ? sb + B_SR + lane * 8 : 0, lane);
#pragma unroll 1
    for (int n = 0; n < nslots; n++) {
      const uint32_t par = n & 1;
      const int lane = opaque(lane0);
      PROFA(warp == PW2);
      const uint32_t info = prm.slot[n], s = info & 63, l = (info >> 6) & 1;
      {
        mbar_expect_if(arm, arm, lane == 5 ? 2048 : 1920);
        if (warp == 0 || warp == 3) {
          mbar_wait(sb + B_SR, par);
          PROF(4);
          const uint2 a0 = lds64(s0), a1 = lds64(s0 + 640), a2 = lds64(s0 + 1280);
          const uint32_t b0 = lds32(s1 + SM_SR + 512), b1 = lds32(s1 + SM_SR + 1152), b2 = lds32(s1 + SM_SR + 1792);
          float v[6];
          v[0] = blo(a0.x) + blo(a1.x) + blo(a2.x); v[1] = bhi(a0.x) + bhi(a1.x) + bhi(a2.x);
          v[2] = blo(a0.y) + blo(a1.y) + blo(a2.y); v[3] = bhi(a0.y) + bhi(a1.y) + bhi(a2.y);
          v[4] = blo(b0) + blo(b1) + blo(b2); v[5] = bhi(b0) + bhi(b1) + bhi(b2);
          float m = fmaxf(fmaxf(v[0], v[1]), fmaxf(v[2], v[3]));
          m = fmaxf(fmaxf(m, __shfl_xor_sync(~0u, m, 4)), fmaxf(v[4], v[5]));
          {
            const float m1 = __shfl_xor_sync(~0u, m, 1), m2 = __shfl_xor_sync(~0u, m, 2), m3 = __shfl_xor_sync(~0u, m, 3);
            m = fmaxf(fmaxf(m, m1), fmaxf(m2, m3));
          }
          const float ms = -m * SC;
#pragma unroll
          for (int i = 0; i < 6; i++) v[i] = ex2(fmaf(v[i], SC, ms));
          float sum = (v[0] + v[1]) + (v[2] + v[3]);
          const float so = __shfl_xor_sync(~0u, sum, 4);
          sts32(pd + SM_P, pack2(v[0], v[1]));
          sts32(pd + SM_P + 128, pack2(v[2], v[3]));
          sts32(s1 + SM_P + 512, pack2(v[4], v[5]));
          fence_async_smem();
          __syncwarp();
          mbar_arrive_if(lane == 0, sb + B_PMEM);
          PROF(5);
          sum += so + (v[4] + v[5]);
          {
            const float t1 = __shfl_xor_sync(~0u, sum, 1), t2 = __shfl_xor_sync(~0u, sum, 2), t3 = __shfl_xor_sync(~0u, sum, 3);
            sum = (sum + t1) + (t2 + t3);
          }
          float r;
          asm("rcp.approx.ftz.f32 %0, %1;" : "=f"(r) : "f"(sum));
          sts32(sb + SM_RS + (warp & 2) * 8 + (lane >> 3) * 4, __float_as_uint(r));
          __syncwarp();
          mbar_arrive_if(lane == 0, sb + B_PSUM);
        } else {
          if (warp + rank != 3) {
            const uint32_t src = sb + SM_SR + warp * 1920;
            mbar_wait(sb + B_SR + warp * 8, par);
            const uint4 a0 = lds128(src + lane * 16), a1 = lds128(src + 640 + lane * 16), a2 = lds128(src + 1280 + lane * 16);
            const uint32_t b0 = lds32(src + 512 + lane * 4), b1 = lds32(src + 1152 + lane * 4), b2 = lds32(src + 1792 + lane * 4);
            float v[10];
            v[0] = blo(a0.x) + blo(a1.x) + blo(a2.x); v[1] = bhi(a0.x) + bhi(a1.x) + bhi(a2.x);
            v[2] = blo(a0.y) + blo(a1.y) + blo(a2.y); v[3] = bhi(a0.y) + bhi(a1.y) + bhi(a2.y);
            v[4] = blo(a0.z) + blo(a1.z) + blo(a2.z); v[5] = bhi(a0.z) + bhi(a1.z) + bhi(a2.z);
            v[6] = blo(a0.w) + blo(a1.w) + blo(a2.w); v[7] = bhi(a0.w) + bhi(a1.w) + bhi(a2.w);
            v[8] = blo(b0) + blo(b1) + blo(b2); v[9] = bhi(b0) + bhi(b1) + bhi(b2);
            {
              const int lim = 6 + 2 * grp + (lane & 24) + ((lane >> 2) & 1) - 2 * (lane & 3);
#pragma unroll
              for (int i = 2; i < 10; i++) if ((i >> 1) * 8 + (i & 1) > lim) v[i] = -INFINITY;
            }
            float m = fmaxf(fmaxf(fmaxf(v[0], v[1]), fmaxf(v[2], v[3])), fmaxf(fmaxf(v[4], v[5]), fmaxf(v[6], v[7])));
            m = fmaxf(m, fmaxf(v[8], v[9]));
            {
              const float m1 = __shfl_xor_sync(~0u, m, 1), m2 = __shfl_xor_sync(~0u, m, 2), m3 = __shfl_xor_sync(~0u, m, 3);
              m = fmaxf(fmaxf(m, m1), fmaxf(m2, m3));
            }
            const float ms = -m * SC;
#pragma unroll
            for (int i = 0; i < 10; i++) v[i] = ex2(fmaf(v[i], SC, ms));
            float sum = ((v[0] + v[1]) + (v[2] + v[3])) + ((v[4] + v[5]) + (v[6] + v[7])) + (v[8] + v[9]);
            {
              const float s1 = __shfl_xor_sync(~0u, sum, 1), s2 = __shfl_xor_sync(~0u, sum, 2), s3 = __shfl_xor_sync(~0u, sum, 3);
              sum = (sum + s1) + (s2 + s3);
            }
            float r;
            asm("rcp.approx.ftz.f32 %0, %1;" : "=f"(r) : "f"(sum));
            {
              const uint32_t row = SM_P + grp * 640;
#pragma unroll
              for (int j = 0; j < 5; j++) sts32(sb + row + j * 128 + lane * 4, pack2(v[2 * j] * r, v[2 * j + 1] * r));
              fence_async_smem();
              __syncwarp();
              mbar_arrive_if(lane == 0, sb + B_PTOK);
              if (elect_one()) {
                bulk_s2s(peer1 + row, sb + row, 640, peer1 + B_PTOK);
                bulk_s2s(peer2 + row, sb + row, 640, peer2 + B_PTOK);
              }
            }
          }
        }
      }
      const uint32_t* const src = (const uint32_t*)((char*)(g_part + (size_t)((l * 2 + (s & 1)) * PART_RING)) + src_off);
      uint32_t* const dst = (uint32_t*)pin((char*)(g_mem + l * 1024 + (~s & 1) * 512) + dst_off, lane);
      {
        const uint32_t d1 = prm.d1[cta / 24 + ((info >> 5) & 4)];
        if (warp == 3) {
          mbar_wait(sb + B_OB, par);
          mbar_arrive_if(lane == 0, sb + B_GATE);
          sts32(sb + SM_TOPI + par * 4, clk());
          __syncwarp();
          mbar_arrive_if(lane == 0, sb + B_OPI + par * 8);
          TRACE(true, n, 0, gtl());
        }
        const bool reduce = cta < 88 && s != NSEG - 1;
        if (reduce || warp == 0) mbar_wait(sb + B_OPI + par * 8, (n >> 1) & 1);
        if (!reduce) continue;
        mbar_wait(sb + B_RFREE, (nred++ & 1) ^ 1);
        mbar_wait(sb + B_GATE, 1);
        if (d1) spin(d1);
      }
      {
        uint32_t g = 0;
        float2 u;
        PROF(14);
        if (!split) {
          u = poll_sum<8>(src, ~(s >> 1), even, g);
        } else {
          u = poll_sum<12>(src, ~(s >> 1), even, g);
          u.x += __shfl_xor_sync(~0u, u.x, 2);
          u.y += __shfl_xor_sync(~0u, u.y, 2);
        }
        PROF(18);
        if (warp != 1) {
          asm volatile("st.shared.v2.f32 [%0], {%1,%2};" ::"r"(red), "f"(u.x), "f"(u.y) : "memory");
          bar_arrive(3, 128);
        } else {
          bar_sync(3, 128);
          const uint2 o0 = lds64(red), o1 = lds64(red + 256), o2 = lds64(red + 512);
          const uint32_t w = movm(pack2((u.x + __uint_as_float(o0.x)) + (__uint_as_float(o1.x) + __uint_as_float(o2.x)),
                                        (u.y + __uint_as_float(o0.y)) + (__uint_as_float(o1.y) + __uint_as_float(o2.y))));
          if (!split || lane < 16) {
            st_rlx1(dst, w);
            st_rlx1(dst + ((s & 1) ? 2048 : -2048), ~0u);
          }
          mbar_arrive_if(lane == 0, sb + B_RFREE);
        }
        PROF(19);
        PROFV(2, g);
        TRACE(warp == 1, n, 1, gtl());
        TRACE(g, n, 2, g);
      }
    }
  } else {
    asm volatile("setmaxnreg.dec.sync.aligned.u32 %0;" ::"n"(RG3));
    asm volatile("barrier.cluster.wait.acquire.aligned;" ::: "memory");
    const uint32_t chk = lane * 32 + ((lane >> 2) << 2);
    const uint32_t bar = sb + B_MTRY + 8 * warp;
    uint32_t mph = 0, waited = 0, pub = 0, pph = 0;
    auto publish = [&](uint32_t upto) {
#pragma unroll 1
      for (; pub < upto; pub++) {
        const uint32_t e = prm.slot[pub], l = (e >> 6) & 1;
        if (warp == 3 && (e >> 16)) {
          mbar_wait_wd(sb + B_OTOK + l * 8, (pph >> l) & 1);
          pph ^= 1 << l;
          if (elect_one()) red_rel(&g_cnt[(e >> 16) * CSTRIDE], 1);
        }
      }
    };
#pragma unroll 1
    for (int m = 0; m < nslots; m++) {
      const uint32_t info = prm.slot[m], prod = (info >> 8) & 255, ls = info & 127;
      uint32_t g = 0;
#pragma unroll 1
      for (; waited < prod && waited + 1 < m; waited++) mbar_wait_wd(sb + B_OPI + (waited & 1) * 8, (waited >> 1) & 1);
      uint32_t t0 = lds32(sb + SM_TOPI + (~waited & 1) * 4);
      publish(waited);
      if ((ls & 3) == 0) {
        while (__any_sync(~0u, ld_acq(&g_cnt[(C_XN + (ls >> 2)) * CSTRIDE]) < XN_TARGET)) guard(g);
        fence_async_global();
      }
#pragma unroll 1
      for (uint32_t c = warp; c < 5; c += 4) {
        const uint32_t dst = sb + SM_H + c * 10240, full = sb + B_HFULL + 8 * c;
        const uint4* src = g_mem + (c * 2048 + (ls >> 6) * 1024 + (ls & 1) * 512 + prm.moff);
        const uint32_t d = prod ? prm.d2[(m - prod) * 5 + c] : 0;
        const uint4* tok = g_xn + (size_t)(ls * 2560 + c * 512);
        const uint32_t pp = (m & 1) ^ 1;
        const bool single = waited < prod;
        mbar_wait_wd(full, pp);
        mbar_expect_if(lane < 2, lane ? bar : full, lane ? 2048 : 8192);
        if (!single) while (__any_sync(~0u, clk() - t0 < d)) {}
        if (c >= 2) mbar_wait_wd(sb + B_HEMPTY + 8 * c, pp);
        mbar_wait_wd(sb + (c < 2 ? B_HEMPTY + 8 * c : c == 2 && !single ? B_PMEM : B_OB), pp);
        if (c != 2 || single) { if (elect_one()) bulk_g2s(dst + 2048, tok, 8192, full); }
        if (single) {
          mbar_wait_wd(sb + B_OPI + (waited & 1) * 8, (waited >> 1) & 1);
          waited++;
          t0 = lds32(sb + SM_TOPI + (~waited & 1) * 4);
          publish(waited);
          while (__any_sync(~0u, clk() - t0 < d)) {}
        }
        else if (c < 2) spin(prm.dh);
        if (elect_one()) bulk_g2s(dst, src, 2048, bar);
        if (c == 2 && !single) {
          mbar_wait_wd(sb + B_OB, pp);
          if (elect_one()) bulk_g2s(dst + 2048, tok, 8192, full);
        }
        g = 0;
        while (true) {
          mbar_wait_wd(bar, mph);
          mph ^= 1;
          const uint32_t v0 = lds32(dst + chk), v1 = lds32(dst + chk + 1024);
          if (__all_sync(~0u, v0 != ~0u && v1 != ~0u)) break;
          if (elect_one()) {
            mbar_expect(bar, 2048);
            bulk_g2s(dst, src, 2048, bar);
          }
          guard(g);
        }
        mbar_arrive_if(lane == 0, full);
        TRACE(c < 2, m, 3 + 2 * c, gtl());
        TRACE(c < 2, m, 4 + 2 * c, g);
      }
    }
    publish(nslots);
    if (warp == 0) mbar_wait_wd(sb + B_END, 0);
  }
  __syncwarp();
  if (wid != 12 && lane0 == 0) mbar_arrive(sb + B_END);
  cluster_sync();
}
__device__ uint32_t g_xa[NBLK * 10 * 4096];
__device__ uint32_t g_h[NBLK * 24 * 4096];

enum { T_A = 0, T_F1 = 1, T_U = 2, T_D = 3, T_F2 = 4, T_NONE = 7 };
__host__ __device__ constexpr int c_phase(int type, int lb) { return C_O + type * 32 + lb; }
constexpr int C_TICKET = c_phase(5, 0), C_EXIT = C_TICKET + 1, C_USED = C_HALF + 2 * NBLK;
constexpr int G_NST = 7;
constexpr uint32_t GS_RED = G_NST * 32768, GS_BAR = GS_RED + 1088, G_SMEM = GS_BAR + 224;
constexpr uint32_t GB_FULL = GS_BAR, GB_EMPTY = GS_BAR + 64, GB_ORD = GS_BAR + 128, GB_READY = GS_BAR + 144, GB_ACK = GS_BAR + 152, GB_GATE = GS_BAR + 160, GB_SIG = GS_BAR + 176, GB_SACK = GS_BAR + 192,
                   GS_SIG = GS_BAR + 208, GS_COL = GS_BAR + 216;
#define FPL 6
constexpr int NF = 16;
constexpr int G_EARLY = 36;
constexpr int G_LATE = 96, PL = 6, ML = 8, DL = 24, TL = 10;
constexpr int GRC = 112, GRP = 32;
constexpr uint32_t E_UP = 1u << 8, E_HALF = 1u << 28, E_GRP = 1u << 29, E_HAND = 1u << 30, E_EXCL = 1u << 31;

struct GParams {
  __nv_bfloat16* out;
  const uint32_t* x;
  int moff, gd;
  int pend;
  uint8_t perm[G_EARLY], first[9];
  uint8_t need[5][2 * NBLK];
  uint32_t tab[G_EARLY * (PL + ML + DL) + G_LATE * TL];
};
constexpr int EL = PL + ML + DL, TAB_TAIL = G_EARLY * EL;
struct GIter {
  int p, left, period;
  uint32_t e, type, lb, n0, kb0, nkb;
  bool gemm, valid;
  DI GIter(const GParams& prm, int col) {
    if (col < G_EARLY) { p = col * EL; left = PL; period = 0; }
    else { p = TAB_TAIL + (col - G_EARLY) * TL; left = TL; period = prm.pend; }
  }
  DI bool next(const GParams& prm, int col) {
    do {
      if (left == 0) {
        if (++period > prm.pend) return false;
        left = period < prm.pend ? ML : DL;
        if (period > 1 && period < prm.pend) p -= ML;
      }
      e = prm.tab[p++]; left--;
    } while ((e & 7) == T_NONE);
    const int b = (e >> 4) & 15, blk = period < prm.pend ? period - b : b;
    type = e & 7; valid = blk >= 0; lb = (e & 8) * 2 + (blk & 15); n0 = (e >> 9) & 127; kb0 = (e >> 16) & 127;
    gemm = type != T_F1 && type != T_F2;
    nkb = valid ? (e >> 23) & 31 : 0;
    return true;
  }
  DI int id_(int pend) const { return period < pend ? period * 10 + ML - left : 160 + DL - left; }
};

#define GLOG(nt, i, v)
template <int TA> DI void wg_ss128(float* d, uint64_t da, uint64_t db, int sc) {
  asm volatile("{.reg .pred p; setp.ne.b32 p, %66, 0;\n"
               "wgmma.mma_async.sync.aligned.m64n128k16.f32.bf16.bf16 "
               "{%0,%1,%2,%3,%4,%5,%6,%7,%8,%9,%10,%11,%12,%13,%14,%15,%16,%17,%18,%19,%20,%21,%22,%23,%24,%25,%26,%27,%28,%29,%30,%31,"
               "%32,%33,%34,%35,%36,%37,%38,%39,%40,%41,%42,%43,%44,%45,%46,%47,%48,%49,%50,%51,%52,%53,%54,%55,%56,%57,%58,%59,%60,%61,%62,%63}, "
               "%64, %65, p, 1, 1, %67, 1;}"
               : ACC16(d, 0), ACC16(d, 16), ACC16(d, 32), ACC16(d, 48) : "l"(da), "l"(db), "r"(sc), "n"(TA));
}

template <int TA> DI void g_mainloop(float* acc, uint32_t sb, uint32_t hand, uint32_t gate, int nkb, int cw, int lane, uint32_t st, uint32_t ph) {
  const uint64_t da0 = (TA ? mkdesc(SMEM0, 4096, 512, 2) : mkdesc(SMEM0, 128, 1024, 0)) + (cw >> 2) * 512;
  const uint64_t db0 = mkdesc(SMEM0 + 16384, 8192, 1024, 1);
  uint32_t prev = 0;
#pragma unroll 1
  for (int kb = 0; kb < nkb; kb++) {
    mbar_wait(sb + GB_FULL + 8 * st, ph);
    mbar_wait(gate, 1);
    const uint64_t da = da0 + st * 2048, db = db0 + st * 2048;
    wg_fence();
#pragma unroll
    for (int k = 0; k < 4; k++) wg_ss128<TA>(acc, da + k * (TA ? 64 : 16), db + k * 128, 1);
    wg_commit();
    mbar_arrive_if(hand && kb == nkb - 1 && lane == 0, hand);
    wg_wait<1>();
    mbar_arrive_if(kb > 0 && lane == 0, sb + GB_EMPTY + 8 * prev);
    prev = st;
    if (++st == G_NST) { st = 0; ph ^= 1; }
  }
  wg_wait<0>();
  reg_fence<64>(acc);
  mbar_arrive_if(lane == 0, sb + GB_EMPTY + 8 * prev);
}

__global__ void __launch_bounds__(640, 1)
g_kernel(const __grid_constant__ CUtensorMap mapWo, const __grid_constant__ CUtensorMap mapWg, const __grid_constant__ CUtensorMap mapWu,
         const __grid_constant__ CUtensorMap mapWd, const __grid_constant__ GParams prm) {
  const uint32_t sb = smem_base();
  const int wid = __shfl_sync(~0u, threadIdx.x >> 5, 0), lane = threadIdx.x & 31;
  if (threadIdx.x == 0) {
    if ((sb & 0x3FFFF) != SMEM0) __trap();
    {
      uint32_t sm; asm volatile("mov.u32 %0, %%smid;" : "=r"(sm));
      uint32_t* const tk = &g_cnt[C_TICKET * CSTRIDE];
      uint32_t c = atomicAdd(tk, 1);
      if (c < G_EARLY) {
        const uint32_t k = sm < 64 ? (sm >> 1) & 7 : sm < 120 ? 1 + ((sm - 64) >> 1) % 7 : sm < 124 ? 1 + ((sm >> 1) & 1) : 0;
        const uint32_t t = atomicAdd(tk + 1 + k, 1);
        atomicAdd(tk + 9, 1);
        if (t < prm.first[k + 1] - prm.first[k]) c = prm.perm[prm.first[k] + t];
        else {
          uint32_t o = atomicAdd(tk + 10, 1), g = 0;
          while (ld_acq(tk + 9) < G_EARLY) guard(g);
          for (int j = 0; j < 8; j++)
            for (uint32_t i = prm.first[j] + ld_acq(tk + 1 + j); i < prm.first[j + 1]; i++) if (o-- == 0) c = prm.perm[i];
        }
      }
      sts32(sb + GS_COL, c);
    }
    for (int i = 0; i < G_NST; i++) { mbar_init(sb + GB_FULL + 8 * i, 1); mbar_init(sb + GB_EMPTY + 8 * i, 8); }
    mbar_init(sb + GB_ORD, 8); mbar_init(sb + GB_ORD + 8, 8); mbar_init(sb + GB_READY, 1); mbar_init(sb + GB_ACK, 1);
    mbar_init(sb + GB_GATE, 1); mbar_init(sb + GB_GATE + 8, 1);
    mbar_init(sb + GB_SIG, 8); mbar_init(sb + GB_SIG + 8, 8); mbar_init(sb + GB_SACK, 1); mbar_init(sb + GB_SACK + 8, 1);
    fence_async_smem();
  }
  __syncthreads();
  const int col = __shfl_sync(~0u, lds32(sb + GS_COL), 0);

  if (wid >= 16) {
    GIter t(prm, col);
    asm volatile("setmaxnreg.dec.sync.aligned.u32 %0;" ::"n"(GRP));
    uint32_t st = 0, ph = 1, k = 0;
    if (wid == 16) {
      while (t.next(prm, col)) {
        const CUtensorMap* m0 = t.type == T_A ? &mapWo : t.type == T_U ? &mapWg : &mapWd;
        const CUtensorMap* m1 = t.type == T_U ? &mapWu : m0;
        const int c0 = t.type == T_U ? t.n0 * 64 : (t.n0 & 7) * 128, c1 = t.type == T_U ? c0 : c0 + 64;
        if ((t.e & (E_HALF | E_UP)) == E_UP) poll_ge(&g_cnt[c_phase(t.type, t.lb) * CSTRIDE], prm.need[t.type][t.lb]);
#pragma unroll 1
        for (uint32_t kb = t.kb0; kb < t.kb0 + t.nkb; kb++) {
          mbar_wait(sb + GB_EMPTY + 8 * st, ph);
          if (elect_one()) {
            const uint32_t full = sb + GB_FULL + 8 * st, dst = sb + st * 32768;
            mbar_expect(full, (t.e & E_HALF) ? 24576 : 32768);
            tma_2d(dst + 16384, m0, c0, kb * 64, full);
            tma_2d(dst + 24576, m1, c1, kb * 64, full);
          }
          if (++st == G_NST) { st = 0; ph ^= 1; }
        }
      }
    } else if (wid == 17) {
      while (t.next(prm, col)) {
        if (!t.nkb) continue;
        const char* asrc = t.type == T_A ? (const char*)g_oT + (size_t)t.lb * (96 * 16384)
                         : t.type == T_U ? (const char*)g_xa + (size_t)(t.lb & 15) * (10 * 16384) : (const char*)g_h + (size_t)(t.lb & 15) * (24 * 16384);
        const uint32_t up = (t.e & E_HALF) ? (t.e & E_UP) * 32 : 0;
        GLOG(t.id_(prm.pend), 1, gtime());
        mbar_wait(sb + GB_READY, k & 1);
        mbar_arrive_if(lane == 0, sb + GB_ACK);
        k++;
#pragma unroll 1
        for (uint32_t kb = t.kb0; kb < t.kb0 + t.nkb; kb++) {
          mbar_wait(sb + GB_EMPTY + 8 * st, ph);
          if (elect_one()) bulk_g2s(sb + st * 32768 + up, asrc + (size_t)kb * 16384 + up, (t.e & E_HALF) ? 8192 : 16384, sb + GB_FULL + 8 * st);
          if (++st == G_NST) { st = 0; ph ^= 1; }
        }
      }
    } else if (wid == 18) {
      while (t.next(prm, col)) {
        if (!t.nkb) continue;
        const bool lower = t.type == T_A && (t.e & (E_HALF | E_UP)) == E_HALF;
        poll_ge(&g_cnt[(lower ? C_HALF + t.lb : c_phase(t.type, t.lb)) * CSTRIDE], prm.need[t.type][t.lb]);
        fence_async_global();
        GLOG(t.id_(prm.pend), 2, gtime());
        mbar_wait(sb + GB_ACK, (k & 1) ^ 1);
        mbar_arrive_if(lane == 0, sb + GB_READY);
        k++;
      }
    } else {
      uint32_t live = 3, par = 0, g = 0;
      while (live) {
        const bool ev = lane < 2 && ((live >> lane) & 1) && mbar_test(sb + GB_SIG + 8 * lane, (par >> lane) & 1);
        const uint32_t evs = __ballot_sync(~0u, ev);
        if (!evs) { guard(g); __nanosleep(20); continue; }
        const uint32_t msg = ev ? lds32(sb + GS_SIG + 4 * lane) : 0;
        mbar_arrive_if(ev, sb + GB_SACK + 8 * lane);
        mbar_arrive_if(msg >> 31, sb + GB_GATE + 8 * lane);
        if (msg) red_rel(&g_cnt[(msg & 0xffff) * CSTRIDE], (msg >> 16) & 255);
        par ^= evs;
        live &= ~__ballot_sync(~0u, ev && !msg);
        g = 0;
      }
      asm volatile("griddepcontrol.wait;" ::: "memory");
      if (col < 80 && lane < 16) g_mem[(col >> 4) * 2048 + (lane >> 3) * 1024 + 512 + prm.moff + (col & 15) * 8 + (lane & 7)] = make_uint4(~0u, ~0u, ~0u, ~0u);
      uint32_t last = 0;
      if (lane == 0) last = atomicAdd(&g_cnt[C_EXIT * CSTRIDE], 1) == gridDim.x - 1;
      if (__shfl_sync(~0u, last, 0)) {
        g_cnt[C_TICKET * CSTRIDE + lane] = 0;
        for (int i = lane; i < C_USED; i += 32) g_cnt[i * CSTRIDE] = 0;
      }
    }
  } else {
    asm volatile("setmaxnreg.inc.sync.aligned.u32 %0;" ::"n"(GRC));
    const int cw = wid & 7, wk = wid >> 3;
    GIter t(prm, col);
    uint32_t pos = 0, seen = 0, waited = 0;
    uint32_t nsig = 0;
    auto signal = [&](uint32_t msg) {
      mbar_wait(sb + GB_SACK + 8 * wk, (nsig++ & 1) ^ 1);
      if (cw == 0) sts32(sb + GS_SIG + 4 * wk, msg);
      __syncwarp();
      mbar_arrive_if(lane == 0, sb + GB_SIG + 8 * wk);
    };
    if (col < G_EARLY) {
      spin(prm.gd);
#pragma unroll 1
      for (int rg = 96 + col * 2 + wk; rg < 256; rg += 2 * G_EARLY) {
        uint32_t a[10];
        const uint32_t* src = prm.x + (size_t)(rg * 8 + (lane >> 2)) * (DM / 2) + cw * 40 + (lane & 3);
#pragma unroll
        for (int i = 0; i < 10; i++) a[i] = __ldg(src + i * 4);
        first_ln(a, rg, sb + GS_RED + wk * 512, cw, lane, 1 + wk);
        signal((C_XN + (rg >> 4)) | ((XN_TARGET / NF) << 16));
        bar_sync(1 + wk, 256);
      }
    }
    while (t.next(prm, col)) {
      const uint32_t pos0 = pos;
      pos = (pos + t.nkb) % (2 * G_NST);
      if (((t.e >> 29) & 1) != wk) { seen += (t.e >> 30) & 1; continue; }
      const uint32_t type = t.type, blk = t.lb & 15, layer = t.lb >> 4, n0 = t.n0;
      if (cw == 0 && t.valid) GLOG(t.id_(prm.pend), 0, 0x80000000u | type | (t.lb << 3) | (n0 << 8) | (t.nkb << 16));
      if (!t.gemm) {
        if (!t.valid) continue;
        const int rg = blk * 16 + n0;
        float4 v[5];
        const int off = (n0 * 40 + cw * 5) * 32 + lane, npl = t.kb0;
        const uint2* src = acc_planes(t.lb, type == T_F2) + off;
        if (cw == 0) {
          poll_ge(&g_cnt[c_phase(type, t.lb) * CSTRIDE], prm.need[type][t.lb]);
          mbar_arrive_if((t.e & E_EXCL) && lane == 0, sb + GB_GATE + 8 * wk);
          GLOG(t.id_(prm.pend), 2, gtime()); GLOG(t.id_(prm.pend), 3, gtime());
        }
        bar_sync(1 + wk, 256);
        {
          const uint32_t eye = (lane >> 3) == (lane & 3) ? ((lane & 4) ? 0x3f800000u : 0x00003f80u) : 0u;
#pragma unroll
          for (int i = 0; i < 5; i++) v[i] = make_float4(0.f, 0.f, 0.f, 0.f);
#pragma unroll 1
          for (int p0 = 0; p0 < npl; p0 += FPL) {
            uint32_t r[FPL / 2][5][4];
#pragma unroll
            for (int p = 0; p < FPL; p++)
#pragma unroll
              for (int i = 0; i < 5; i++) {
                const uint2 w = p0 + p < npl ? __ldcg(src + (size_t)(p0 + p) * PLANE + i * 32) : make_uint2(0, 0);
                r[p >> 1][i][(p & 1) * 2] = w.x; r[p >> 1][i][(p & 1) * 2 + 1] = w.y;
              }
#pragma unroll
            for (int p = 0; p < FPL / 2; p++) {
              if (p0 + 2 * p >= npl) break;
              if (t.e & E_EXCL) {
#pragma unroll
                for (int i = 0; i < 5; i++) mma16816(&v[i].x, r[p][i], eye, eye);
              } else {
#pragma unroll
                for (int i = 0; i < 5; i++) {
                  const uint32_t* w = r[p][i];
                  v[i].x += blo(w[0]) + blo(w[2]); v[i].y += bhi(w[0]) + bhi(w[2]); v[i].z += blo(w[1]) + blo(w[3]); v[i].w += bhi(w[1]) + bhi(w[3]);
                }
              }
            }
          }
        }
        if (type == T_F2 && layer == 1) {
          uint2* dst = (uint2*)prm.out + (size_t)(rg * 8 + (lane >> 2)) * (DM / 4) + cw * 20 + (lane & 1) * 2 + ((lane >> 1) & 1);
#pragma unroll
          for (int i = 0; i < 5; i++) {
            const uint32_t a = pack2(v[i].x, v[i].y), b = pack2(v[i].z, v[i].w);
            const uint32_t o = __shfl_xor_sync(~0u, (lane & 1) ? a : b, 1);
            dst[i * 4] = (lane & 1) ? make_uint2(o, b) : make_uint2(a, o);
          }
        } else {
          uint2* nx = (type == T_F1 ? acc_planes(t.lb, 1) : acc_planes(NBLK + blk, 0)) + off;
#pragma unroll
          for (int i = 0; i < 5; i++) {
            const uint2 w = make_uint2(pack2(v[i].x, v[i].y), pack2(v[i].z, v[i].w));
            nx[i * 32] = w;
            v[i] = make_float4(blo(w.x), bhi(w.x), blo(w.y), bhi(w.y));
          }
          float mean, rstd;
          ln_stats(v, sb + GS_RED + wk * 512, cw, lane, 1 + wk, mean, rstd);
          if (type == T_F2) store_img<4, 2048>(xn_row_group(1, rg) + lane, v, cw, mean, rstd);
          else store_img<3, 4096>(g_xa + (size_t)(blk * 10 * 4096 + n0 * 256) + lane, v, cw, mean, rstd);
        }
      } else {
        float acc[64];
#pragma unroll
        for (int j = 0; j < 64; j++) acc[j] = 0.f;
        if (waited != seen) { mbar_wait(sb + GB_ORD + 8 * (wk ^ 1), waited & 1); waited++; }
        const uint32_t hand = (t.e & E_HAND) ? sb + GB_ORD + 8 * wk : 0;
        if (!t.valid) { mbar_arrive_if(hand && lane == 0, hand); continue; }
        if (cw == 0) GLOG(t.id_(prm.pend), 3, gtime());
        const uint32_t ph = pos0 >= G_NST, st = pos0 - ph * G_NST, early = (t.e & E_EXCL) ? 0 : hand;
        const bool idle = (t.e & E_HALF) && ((t.e >> 8) & 1) != (cw >> 2);
        if (idle) {
          uint32_t s2 = st, p2 = ph;
#pragma unroll 1
          for (uint32_t kb = 0; kb < t.nkb; kb++) {
            mbar_wait(sb + GB_FULL + 8 * s2, p2);
            mbar_arrive_if(lane == 0, sb + GB_EMPTY + 8 * s2);
            if (++s2 == G_NST) { s2 = 0; p2 ^= 1; }
          }
          mbar_arrive_if(early && lane == 0, early);
        } else if (type == T_A) g_mainloop<1>(acc, sb, early, sb + GB_GATE + 8 * (wk ^ 1), t.nkb, cw, lane, st, ph);
        else g_mainloop<0>(acc, sb, early, sb + GB_GATE + 8 * (wk ^ 1), t.nkb, cw, lane, st, ph);
        if (cw == 0) GLOG(t.id_(prm.pend), 4, gtime());
        if (idle) {
        } else if (type == T_U) {
          uint32_t* dst = g_h + (size_t)((blk * 24 + n0) * 4096 + cw * 512) + lane;
#pragma unroll
          for (int j = 0; j < 8; j++) {
            float h[4];
#pragma unroll
            for (int e = 0; e < 4; e++) {
              float th;
              asm("tanh.approx.f32 %0, %1;" : "=f"(th) : "f"(0.5f * acc[4 * j + e]));
              h[e] = acc[32 + 4 * j + e] * fmaf(th, 0.5f, 0.5f);
            }
            dst[j * 32] = pack2(h[0], h[1]);
            dst[j * 32 + 256] = pack2(h[2], h[3]);
          }
        } else {
          uint2* dst = acc_planes(t.lb, type == T_D) + (size_t)((1 + (n0 >> 3)) * PLANE + (2 * cw * 40 + (n0 & 7) * 8) * 32) + lane;
#pragma unroll
          for (int j = 0; j < 16; j++) {
            const float* a = acc + (j >> 1) * 8 + (j & 1) * 2;
            dst[(j >> 1) * 32 + (j & 1) * 1280] = make_uint2(pack2(a[0], a[1]), pack2(a[4], a[5]));
          }
        }
        mbar_arrive_if(hand != early && lane == 0, hand);
      }
      if (cw == 0) GLOG(t.id_(prm.pend), 5, gtime());
      if (cw == 0) GLOG(t.id_(prm.pend), 6, gtime());
      if (type == T_F2 && layer == 1) mbar_arrive_if((t.e & E_EXCL) && cw == 0 && lane == 0, sb + GB_GATE + 8 * wk);
      else
        signal((type != T_F2 ? c_phase(type + 1, t.lb) | (1 << 16) : (C_XN + NBLK + blk) | ((XN_TARGET / NF) << 16)) | (t.gemm ? 0 : t.e & E_EXCL));
    }
    signal(0);
  }
}

typedef CUresult (*EncodeFn)(CUtensorMap*, CUtensorMapDataType, cuuint32_t, void*, const cuuint64_t*, const cuuint64_t*, const cuuint32_t*,
                             const cuuint32_t*, CUtensorMapInterleave, CUtensorMapSwizzle, CUtensorMapL2promotion, CUtensorMapFloatOOBfill);
static CUtensorMap make_map(EncodeFn fn, const void* p, uint64_t inner, uint64_t outer, uint32_t bi, uint32_t bo) {
  CUtensorMap m;
  cuuint64_t dims[2] = {inner, outer}, str[1] = {inner * 2};
  cuuint32_t box[2] = {bi, bo}, es[2] = {1, 1};
  fn(&m, CU_TENSOR_MAP_DATA_TYPE_BFLOAT16, 2, (void*)p, dims, str, box, es, CU_TENSOR_MAP_INTERLEAVE_NONE, CU_TENSOR_MAP_SWIZZLE_128B,
     CU_TENSOR_MAP_L2_PROMOTION_L2_256B, CU_TENSOR_MAP_FLOAT_OOB_FILL_NONE);
  return m;
}
struct Tune {
  int lag = 11, excl = 7, gonly = 0, xl = 1, ronly = 0, pn = 30;
  int da = 100, db = 350, dc = 650, dd = 650, d2 = 2000, p1 = 400, p2 = 800;
  int ea = 60, eb = 310, ec = 550, ed = 550, e2 = 2200, q1 = 200, q2 = 400, d3 = 60, moff = 192, ds = 400, dh = 60, pa = 0, pb = 0, pc = 0, pd = 0, pe = 0, pf = 0, pg = 0, ph = 0, hold = 1, wpf = 4, gd = 22000;
};
static void fill_r(RParams& p, const Tune& t, int lag, int n0, int n1) {
  r_fill_desc(p);
  p.nslots = 0; p.d3 = t.d3; p.pn = t.pn; p.moff = t.moff; p.ds = t.ds; p.dh = t.dh;
  for (int c = 0; c < 5; c++) { p.d2[c] = t.d2 + (c == 0 ? 0 : c < 3 ? t.p1 : t.p2); p.d2[5 + c] = t.e2 + (c == 0 ? 0 : c < 3 ? t.q1 : t.q2); }
  const int d1[8] = {t.da, t.db, t.dc, t.dd, t.ea, t.eb, t.ec, t.ed};
  for (int i = 0; i < 8; i++) p.d1[i] = d1[i];
  int last[2] = {0, 0}, n = 0;
  for (int s0 = 0; s0 < NSEG + lag; s0++)
    for (int l = 0; l < 2; l++) {
      const int s = l ? s0 - lag : s0;
      if (s < 0 || s >= NSEG) continue;
      if (n >= n0 && n < n1) { p.slot[p.nslots] = s | (l << 6) | (last[l] << 8) | (((s & 3) == 3 ? C_O + l * NBLK + s / 4 : s == (l ? 61 : 1) ? C_HALF + l * NBLK + s / 4 : 0) << 16); last[l] = ++p.nslots; }
      n++;
    }
  for (int i = 0; i + 1 < p.nslots; i++) if (((p.slot[i] ^ p.slot[i + 1]) >> 6) & 1) p.slot[i] |= 128;
}
static uint32_t g_entry(int grp, int type, int layer, int blk, int i, int ks) {
  int n0 = i, kb0 = 0, kb1 = type == T_U ? 10 : 0;
  if (type == T_F1 || type == T_F2) kb0 = kb1 = ks + 1;
  if (type == T_A || type == T_D) {
    const int KB = type == T_A ? 96 : 24, sp = i / 5;
    n0 = i % 5 | (sp << 3); kb0 = sp * KB / ks; kb1 = (sp + 1) * KB / ks;
  }
  return type | (layer << 3) | (blk << 4) | (n0 << 9) | (kb0 << 16) | ((kb1 - kb0) << 23) | (grp ? E_GRP : 0);
}
static bool g_is_gemm(uint32_t e) { return (e & 7) == T_A || (e & 7) == T_U || (e & 7) == T_D; }
static void g_handover(uint32_t* e, int len) {
  uint32_t next = 0;
  for (int i = len - 1; i >= 0; i--)
    if (g_is_gemm(e[i])) { if ((e[i] & E_GRP) != next) e[i] |= E_HAND; next = e[i] & E_GRP; }
}
struct GList {
  GParams& g; uint32_t* tab; int ncol, stride, len, n[G_LATE], load[G_LATE], grp[G_LATE];
  GList(GParams& g_, uint32_t* t, int nc, int st, int l) : g(g_), tab(t), ncol(nc), stride(st), len(l) { for (int c = 0; c < nc; c++) { n[c] = load[c] = 0; grp[c] = 1; } }
  void add(int type, int lb, int ks, int c0, int c1, uint32_t flags = 0, int i0 = 0, int i1 = 999, int step = 1) {
    const int half = (flags & E_HALF) != 0, ln = type == T_F1 || type == T_F2;
    const int cnt = (type == T_U ? 24 : ln ? NF : 5 * ks) << half;
    if (type < T_F2) g.need[type + 1][lb] = cnt;
    int used[G_LATE] = {0};
    for (int i = i0; i < cnt && i < i1; i += step) {
      int best = c0;
      for (int c = c0; c < c1; c++) if (used[c] < used[best] || (used[c] == used[best] && load[c] < load[best])) best = c;
      used[best]++;
      if (!ln) grp[best] ^= 1;
      const uint32_t e = g_entry(grp[best], type, lb >> 4, lb & 15, i >> half, ks) | flags | (ln ? E_EXCL : 0) | ((i & half) ? E_UP : 0);
      if (n[best] >= len) abort();
      tab[best * stride + n[best]++] = e;
      load[best] += (((e >> 23) & 31) >> half) + 2;
    }
  }
  void finish() { for (int c = 0; c < ncol; c++) g_handover(tab + c * stride, len); }
};
static void fill_g(GParams& g, const Tune& t, void* out) {
  g.out = (__nv_bfloat16*)out;  g.pend = NBLK - 1;
  for (int b = 0; b < 2 * NBLK; b++) {
    g.need[T_A][b] = 96; g.need[T_F1][b] = 20; g.need[T_U][b] = NF; g.need[T_D][b] = 32; g.need[T_F2][b] = 15;
  }
  {
    const uint8_t perm[G_EARLY] = {0, 1, 2, 3, 16, 17, 18, 19, 34, 35, 4, 20, 21, 15, 22, 23, 5, 6, 7, 8, 9, 24, 25, 26, 10, 11, 12, 13, 14, 27, 28, 29, 30, 31, 32, 33};
    const uint8_t first[9] = {0, 10, 13, 16, 20, 24, 28, 32, 36};
    const int* pk = &t.pa;
    for (int i = 0; i < G_EARLY; i++) g.perm[i] = t.pa ? (pk[i / 5] >> (6 * (i % 5))) & 63 : perm[i];
    for (int i = 0; i < 9; i++) g.first[i] = first[i];
  }
  for (uint32_t& e : g.tab) e = T_NONE;
  GList pr(g, g.tab, G_EARLY, EL, PL);
  pr.add(T_A, 0, 7, 1, 36, E_HALF, 0, 999, 2); pr.add(T_A, 0, 7, 1, 36, E_HALF, 1, 999, 2); pr.add(T_F1, 0, 7, 20, 36); pr.add(T_U, 0, 0, 12, 36);
  pr.add(T_D, 0, 3, 20, 36); pr.add(T_F2, 0, 3, 20, 36);
  pr.finish();
  const int d = 3;
  const uint32_t xa = (t.excl & 1) ? E_EXCL : 0, xu = (t.excl & 2) ? E_EXCL : 0, xd = (t.excl & 4) ? E_EXCL : 0;
  for (int c = 0; c < G_EARLY; c++) {
    uint32_t* e = g.tab + c * EL + PL;
    if (c < 20) {
      *e++ = g_entry(0, T_A, 0, 0, c, 4) | xa;
      if (c < NF) *e++ = g_entry(0, T_F1, 0, 0, c, 4) | ((t.xl & 1) ? E_EXCL : 0);
      *e++ = g_entry(1, T_A, 1, d, c, 4);
      if (c >= 20 - NF) *e++ = g_entry(1, T_F1, 1, d, c - (20 - NF), 4);
    } else {
      const int j = c - 20;
      const uint32_t hf = E_HALF | ((j & 1) ? E_UP : 0);
      *e++ = g_entry(0, T_U, 0, 0, j, 0);
      *e++ = g_entry(1, T_U, 0, 0, 16 + j / 2, 0) | hf | xu;
      *e++ = g_entry(0, T_U, 1, d + 1, 16 + j / 2, 0) | hf;
      if (j < 15) *e++ = g_entry(1, T_D, 0, 0, j, 3) | xd;
      *e++ = g_entry(1, T_F2, 0, 0, j, 3) | ((t.xl & 2) ? E_EXCL : 0);
      if (j < 15) *e++ = g_entry(0, T_D, 1, d + 2, j, 3);
      *e++ = g_entry(0, T_U, 1, d + 1, j, 0);
      *e++ = g_entry(1, T_F2, 1, d + 2, j, 3);
    }
    g_handover(g.tab + c * EL + PL, ML);
  }
  GList dr(g, g.tab + PL + ML, G_EARLY, EL, DL);
  GList tl(g, g.tab + TAB_TAIL, G_LATE, TL, TL);
  const int L1 = NBLK;
  auto ufull = [&](int lb) { dr.add(T_U, lb, 0, 20, 36, 0, 0, 16); g.need[T_D][lb] = 32; };
  auto uhalf = [&](int lb) { dr.add(T_U, lb, 0, 20, 36, E_HALF, 32); g.need[T_D][lb] = 32; };
  dr.add(T_A, 15, 4, 0, 20, E_EXCL);
  dr.add(T_F1, 15, 4, 0, 16);
  dr.add(T_U, 15, 0, 12, 36, E_EXCL);
  dr.add(T_A, L1 + 12, 4, 0, 20); dr.add(T_F1, L1 + 12, 4, 0, 16);
  uhalf(L1 + 11);
  dr.add(T_D, 15, 3, 20, 36, E_EXCL); dr.add(T_F2, 15, 3, 20, 36);
  dr.add(T_A, L1 + 13, 4, 0, 20); dr.add(T_F1, L1 + 13, 4, 0, 20);
  ufull(L1 + 11);
  dr.add(T_D, L1 + 10, 3, 20, 36);
  ufull(L1 + 12); uhalf(L1 + 12);
  dr.add(T_A, L1 + 14, 4, 0, 20);
  dr.add(T_A, L1 + 15, 7, 0, 35, E_HALF, 0, 999, 2); dr.add(T_A, L1 + 15, 7, 0, 35, E_HALF | E_EXCL, 1, 999, 2);
  dr.add(T_F1, L1 + 14, 4, 0, 16);
  dr.add(T_F1, L1 + 15, 7, 20, 36);
  dr.add(T_F2, L1 + 10, 3, 0, 16); dr.add(T_F2, L1 + 11, 3, 4, 20); dr.add(T_F2, L1 + 12, 3, 0, 20);
  dr.add(T_D, L1 + 13, 3, 20, 36, (t.hold & 1) ? E_UP : 0); dr.add(T_F2, L1 + 13, 3, 20, 36);
  dr.finish();
  tl.add(T_D, L1 + 11, 3, 0, 24); tl.add(T_D, L1 + 12, 3, 48, G_LATE);
  tl.add(T_U, L1 + 14, 0, 0, 24); tl.add(T_U, L1 + 13, 0, 24, 48);
  tl.add(T_D, L1 + 14, 4, 0, 48, E_HALF);
  tl.add(T_F2, L1 + 14, 4, 0, 48);
  tl.add(T_U, L1 + 15, 0, 48, G_LATE, E_HALF);
  tl.add(T_D, L1 + 15, 4, 48, G_LATE, E_HALF);
  tl.add(T_F2, L1 + 15, 4, 48, G_LATE);
  tl.finish();
}
static void launch_all(void* const* d_in, void* d_out, const Tune& t, cudaStream_t st) {
  static EncodeFn fn = nullptr;
  if (!fn) {
    void* f = nullptr;
    cudaDriverEntryPointQueryResult qr;
    cudaGetDriverEntryPoint("cuTensorMapEncodeTiled", &f, cudaEnableDefault, &qr);
    fn = (EncodeFn)f;
    cudaFuncSetAttribute(r_kernel, cudaFuncAttributeMaxDynamicSharedMemorySize, R_SMEM);
    cudaFuncSetAttribute(g_kernel, cudaFuncAttributeMaxDynamicSharedMemorySize, G_SMEM);
  }
  const CUtensorMap mq = make_map(fn, d_in[2], HD, DM, 64, 128), mk = make_map(fn, d_in[3], HD, DM, 64, 128), mv = make_map(fn, d_in[4], HD, DM, 64, 128),
                    mo = make_map(fn, d_in[5], DM, HD, 64, 64), mg = make_map(fn, d_in[8], FF, DM, 64, 64), mu = make_map(fn, d_in[9], FF, DM, 64, 64),
                    md = make_map(fn, d_in[10], DM, FF, 64, 64);
  auto launch_r = [&](int lag, int n0, int n1) {
    RParams p;
    fill_r(p, t, lag, n0, n1);
    for (int i = 0; i < 4; i++) p.w[i] = (const char*)d_in[2 + i];
    p.mem0 = (const uint4*)d_in[1]; p.x = (const uint32_t*)d_in[0]; p.pf = t.wpf;
    cudaLaunchConfig_t cfg = {};
    cfg.gridDim = dim3(3, NH); cfg.blockDim = dim3(512); cfg.dynamicSmemBytes = R_SMEM; cfg.stream = st;
    cudaLaunchAttribute at[1];
    at[0].id = cudaLaunchAttributeClusterDimension; at[0].val.clusterDim.x = 3; at[0].val.clusterDim.y = 1; at[0].val.clusterDim.z = 1;
    cfg.attrs = at; cfg.numAttrs = 1;
    cudaLaunchKernelEx(&cfg, r_kernel, mq, mk, mv, mo, p);
  };
  auto launch_g = [&](const GParams& g, bool pdl) {
    cudaLaunchConfig_t cfg = {};
    cfg.gridDim = dim3(132); cfg.blockDim = dim3(640); cfg.dynamicSmemBytes = G_SMEM; cfg.stream = st;
    cudaLaunchAttribute at[2];
    at[0].id = cudaLaunchAttributeProgrammaticStreamSerialization; at[0].val.programmaticStreamSerializationAllowed = 1;
    cfg.attrs = at; cfg.numAttrs = pdl ? 1 : 0;
    cudaLaunchKernelEx(&cfg, g_kernel, mo, mg, mu, md, g);
  };
  GParams g;
  fill_g(g, t, d_out);
  g.moff = t.moff; g.gd = t.gd; g.x = (const uint32_t*)d_in[0];
  launch_r(t.lag, 0, 2 * NSEG);
  launch_g(g, true);
}

extern "C" void kernel_launch(void* const* d_in, const int* in_sizes, int n_in, void* d_out, int out_size) {
  launch_all(d_in, d_out, Tune(), cudaStreamPerThread);
}
```

```cpp
#include <cuda_runtime.h>
#include <cuda_bf16.h>
#include <cuda.h>
#include <stdint.h>
#include <stdlib.h>

constexpr int SEQ = 2048, DM = 640, NH = 32, DH = 192, HD = NH * DH, FF = 1536;
constexpr int NSEG = 64, SEGL = 32, NMEM = 8;
constexpr int NBLK = 16;

#define DI __device__ __forceinline__

DI uint32_t smem_base() {
  extern __shared__ __align__(1024) unsigned char smem_raw[];
  uint32_t a;
  asm volatile("{.reg .u64 t; cvta.to.shared.u64 t, %1; cvt.u32.u64 %0, t;}" : "=r"(a) : "l"(smem_raw));
  return a;
}
DI uint32_t mapa(uint32_t a, uint32_t r) {
  uint32_t o;
  asm("mapa.shared::cluster.u32 %0, %1, %2;" : "=r"(o) : "r"(a), "r"(r));
  return o;
}
DI void mbar_init(uint32_t bar, uint32_t cnt) { asm volatile("mbarrier.init.shared::cta.b64 [%0], %1;" ::"r"(bar), "r"(cnt) : "memory"); }
DI void mbar_arrive(uint32_t bar) { asm volatile("mbarrier.arrive.shared::cta.b64 _, [%0];" ::"r"(bar) : "memory"); }
DI void mbar_arrive_remote(uint32_t bar) { asm volatile("mbarrier.arrive.release.cluster.shared::cluster.b64 _, [%0];" ::"r"(bar) : "memory"); }
DI void mbar_expect(uint32_t bar, uint32_t tx) { asm volatile("mbarrier.arrive.expect_tx.shared::cta.b64 _, [%0], %1;" ::"r"(bar), "r"(tx) : "memory"); }
DI void mbar_arrive_if(bool p, uint32_t bar) { asm volatile("{.reg .pred p; setp.ne.b32 p, %1, 0; @p mbarrier.arrive.shared::cta.b64 _, [%0];}" ::"r"(bar), "r"((int)p) : "memory"); }
DI void mbar_arrive_if(bool p, uint32_t bar, uint32_t cnt) {
  asm volatile("{.reg .pred p; setp.ne.b32 p, %1, 0; @p mbarrier.arrive.shared::cta.b64 _, [%0], %2;}" ::"r"(bar), "r"((int)p), "r"(cnt) : "memory");
}
DI void mbar_expect_if(bool p, uint32_t bar, uint32_t tx) {
  asm volatile("{.reg .pred p; setp.ne.b32 p, %2, 0; @p mbarrier.arrive.expect_tx.shared::cta.b64 _, [%0], %1;}" ::"r"(bar), "r"(tx), "r"((int)p) : "memory");
}
DI bool mbar_test(uint32_t bar, uint32_t par) {
  uint32_t ok;
  asm volatile("{.reg .pred p; mbarrier.test_wait.parity.shared::cta.b64 p, [%1], %2; selp.u32 %0, 1, 0, p;}" : "=r"(ok) : "r"(bar), "r"(par) : "memory");
  return ok;
}
DI void mbar_wait(uint32_t bar, uint32_t par) {
  asm volatile(
      "{.reg .pred p;\n"
      "LOOP:\n"
      "mbarrier.try_wait.parity.shared::cta.b64 p, [%0], %1;\n"
      "@!p bra LOOP;\n}" ::"r"(bar), "r"(par) : "memory");
}
DI void mbar_wait_wd(uint32_t bar, uint32_t par) {
  asm volatile(
      "{.reg .pred p; .reg .u32 c;\n"
      "mov.u32 c, 0;\n"
      "LOOP:\n"
      "mbarrier.try_wait.parity.shared::cta.b64 p, [%0], %1;\n"
      "@p bra DONE;\n"
      "add.u32 c, c, 1;\n"
      "setp.lt.u32 p, c, 4000000;\n"
      "@p bra LOOP;\n"
      "trap;\n"
      "DONE:\n}" ::"r"(bar), "r"(par) : "memory");
}
DI void fence_async_smem() { asm volatile("fence.proxy.async.shared::cta;" ::: "memory"); }
DI void fence_async_global() { asm volatile("fence.proxy.async.global;" ::: "memory"); }
DI void bar_sync(int id, int n) { asm volatile("bar.sync %0, %1;" ::"r"(id), "r"(n) : "memory"); }
DI void bar_arrive(int id, int n) { asm volatile("bar.arrive %0, %1;" ::"r"(id), "r"(n) : "memory"); }
DI void cluster_sync() { asm volatile("barrier.cluster.arrive.release.aligned; barrier.cluster.wait.acquire.aligned;" ::: "memory"); }
DI bool elect_one() {
  uint32_t p;
  asm volatile("{.reg .pred p; elect.sync _|p, 0xffffffff; selp.u32 %0, 1, 0, p;}" : "=r"(p));
  return p;
}
DI void bulk_g2s(uint32_t dst, const void* src, uint32_t bytes, uint32_t bar) {
  asm volatile("cp.async.bulk.shared::cluster.global.mbarrier::complete_tx::bytes [%0], [%1], %2, [%3];" ::"r"(dst), "l"(src), "r"(bytes), "r"(bar) : "memory");
}
DI void bulk_g2s_mc(uint32_t dst, const void* src, uint32_t bytes, uint32_t bar, uint16_t mask) {
  asm volatile("cp.async.bulk.shared::cluster.global.mbarrier::complete_tx::bytes.multicast::cluster [%0], [%1], %2, [%3], %4;" ::"r"(dst), "l"(src), "r"(bytes), "r"(bar), "h"(mask) : "memory");
}
DI void bulk_s2s(uint32_t dst, uint32_t src, uint32_t bytes, uint32_t bar) {
  asm volatile("cp.async.bulk.shared::cluster.shared::cta.mbarrier::complete_tx::bytes [%0], [%1], %2, [%3];" ::"r"(dst), "r"(src), "r"(bytes), "r"(bar) : "memory");
}
DI void tma_2d(uint32_t dst, const CUtensorMap* map, int c0, int c1, uint32_t bar) {
  asm volatile("cp.async.bulk.tensor.2d.shared::cluster.global.mbarrier::complete_tx::bytes [%0], [%1, {%3, %4}], [%2];" ::"r"(dst), "l"(map), "r"(bar), "r"(c0), "r"(c1) : "memory");
}
DI void tma_pf(const CUtensorMap* map, int c0, int c1) {
  asm volatile("cp.async.bulk.prefetch.tensor.2d.L2.global [%0, {%1, %2}];" ::"l"(map), "r"(c0), "r"(c1) : "memory");
}
DI void st_async4(uint32_t a, uint32_t x, uint32_t y, uint32_t z, uint32_t w, uint32_t bar) {
  asm volatile("st.async.shared::cluster.mbarrier::complete_tx::bytes.v4.b32 [%0], {%1,%2,%3,%4}, [%5];" ::"r"(a), "r"(x), "r"(y), "r"(z), "r"(w), "r"(bar) : "memory");
}
DI void st_async2(uint32_t a, uint32_t x, uint32_t y, uint32_t bar) {
  asm volatile("st.async.shared::cluster.mbarrier::complete_tx::bytes.v2.b32 [%0], {%1,%2}, [%3];" ::"r"(a), "r"(x), "r"(y), "r"(bar) : "memory");
}
DI void st_async1(uint32_t a, uint32_t x, uint32_t bar) {
  asm volatile("st.async.shared::cluster.mbarrier::complete_tx::bytes.b32 [%0], %1, [%2];" ::"r"(a), "r"(x), "r"(bar) : "memory");
}
DI void sts32(uint32_t a, uint32_t x) { asm volatile("st.shared.b32 [%0], %1;" ::"r"(a), "r"(x) : "memory"); }
DI void sts128(uint32_t a, uint4 v) { asm volatile("st.shared.v4.b32 [%0], {%1,%2,%3,%4};" ::"r"(a), "r"(v.x), "r"(v.y), "r"(v.z), "r"(v.w) : "memory"); }
DI uint32_t lds32(uint32_t a) { uint32_t v; asm volatile("ld.shared.b32 %0, [%1];" : "=r"(v) : "r"(a) : "memory"); return v; }
DI uint2 lds64(uint32_t a) { uint2 v; asm volatile("ld.shared.v2.b32 {%0,%1}, [%2];" : "=r"(v.x), "=r"(v.y) : "r"(a) : "memory"); return v; }
DI uint4 lds128(uint32_t a) { uint4 v; asm volatile("ld.shared.v4.b32 {%0,%1,%2,%3}, [%4];" : "=r"(v.x), "=r"(v.y), "=r"(v.z), "=r"(v.w) : "r"(a) : "memory"); return v; }
DI void stsm4(uint32_t a, uint32_t r0, uint32_t r1, uint32_t r2, uint32_t r3) {
  asm volatile("stmatrix.sync.aligned.m8n8.x4.shared.b16 [%0], {%1,%2,%3,%4};" ::"r"(a), "r"(r0), "r"(r1), "r"(r2), "r"(r3) : "memory");
}
DI void stsm2(uint32_t a, uint32_t r0, uint32_t r1) {
  asm volatile("stmatrix.sync.aligned.m8n8.x2.shared.b16 [%0], {%1,%2};" ::"r"(a), "r"(r0), "r"(r1) : "memory");
}
DI uint32_t movm(uint32_t a) { uint32_t d; asm volatile("movmatrix.sync.aligned.m8n8.trans.b16 %0, %1;" : "=r"(d) : "r"(a)); return d; }
DI uint32_t pack2(float lo, float hi) { uint32_t d; asm("cvt.rn.bf16x2.f32 %0, %1, %2;" : "=r"(d) : "f"(hi), "f"(lo)); return d; }
DI uint4 ld_rlx4(const void* p) {
  uint4 v;
  asm volatile("ld.relaxed.gpu.global.v4.u32 {%0,%1,%2,%3}, [%4];" : "=r"(v.x), "=r"(v.y), "=r"(v.z), "=r"(v.w) : "l"(p) : "memory");
  return v;
}
DI void st_rlx4(void* p, uint32_t x, uint32_t y, uint32_t z, uint32_t w) {
  asm volatile("st.relaxed.gpu.global.v4.u32 [%0], {%1,%2,%3,%4};" ::"l"(p), "r"(x), "r"(y), "r"(z), "r"(w) : "memory");
}
DI void st_rlx1(void* p, uint32_t x) { asm volatile("st.relaxed.gpu.global.u32 [%0], %1;" ::"l"(p), "r"(x) : "memory"); }
DI uint32_t ld_acq(const uint32_t* p) { uint32_t v; asm volatile("ld.acquire.gpu.global.u32 %0, [%1];" : "=r"(v) : "l"(p) : "memory"); return v; }
DI uint32_t ld_rlx(const uint32_t* p) { uint32_t v; asm volatile("ld.relaxed.gpu.global.u32 %0, [%1];" : "=r"(v) : "l"(p) : "memory"); return v; }
DI void red_rel(uint32_t* p, uint32_t v) { asm volatile("red.release.gpu.global.add.u32 [%0], %1;" ::"l"(p), "r"(v) : "memory"); }
DI void guard(uint32_t& g) { asm volatile("{.reg .pred p; add.u32 %0, %0, 1; setp.gt.u32 p, %0, 8000000; @p trap;}" : "+r"(g)); }
DI void poll_ge(const uint32_t* p, uint32_t target) {
  asm volatile(
      "{.reg .pred p; .reg .u32 v;\n"
      "LOOP:\n"
      "ld.acquire.gpu.global.u32 v, [%0];\n"
      "setp.lt.u32 p, v, %1;\n"
      "vote.sync.any.pred p, p, 0xffffffff;\n"
      "@p bra.uni LOOP;\n}" ::"l"(p), "r"(target) : "memory");
}
DI float ex2(float x) { float y; asm("ex2.approx.ftz.f32 %0, %1;" : "=f"(y) : "f"(x)); return y; }

DI void wg_fence() { asm volatile("wgmma.fence.sync.aligned;" ::: "memory"); }
DI void wg_commit() { asm volatile("wgmma.commit_group.sync.aligned;" ::: "memory"); }
template <int N> DI void wg_wait() { asm volatile("wgmma.wait_group.sync.aligned %0;" ::"n"(N) : "memory"); }
template <int N> DI void reg_fence(float* d) {
#pragma unroll
  for (int i = 0; i < N; i++) asm volatile("" : "+f"(d[i])::"memory");
}
__host__ __device__ constexpr uint64_t mkdesc(uint32_t addr, uint32_t lbo, uint32_t sbo, uint32_t sw) {
  return (uint64_t)((addr & 0x3FFFF) >> 4) | ((uint64_t)(lbo >> 4) << 16) | ((uint64_t)(sbo >> 4) << 32) | ((uint64_t)sw << 62);
}

#define ACC4(d, o) "+f"(d[o]), "+f"(d[o + 1]), "+f"(d[o + 2]), "+f"(d[o + 3])
#define ACC16(d, o) ACC4(d, o), ACC4(d, o + 4), ACC4(d, o + 8), ACC4(d, o + 12)
#define ACC20(d) ACC16(d, 0), ACC4(d, 16)

template <int TA, int TB> DI void wg_ss40(float* d, uint64_t da, uint64_t db, int sc) {
  asm volatile("{.reg .pred p; setp.ne.b32 p, %22, 0;\n"
               "wgmma.mma_async.sync.aligned.m64n40k16.f32.bf16.bf16 {%0,%1,%2,%3,%4,%5,%6,%7,%8,%9,%10,%11,%12,%13,%14,%15,%16,%17,%18,%19}, %20, %21, p, 1, 1, %23, %24;}"
               : ACC20(d) : "l"(da), "l"(db), "r"(sc), "n"(TA), "n"(TB));
}
DI void wg_rs40(float* d, uint32_t a0, uint32_t a1, uint32_t a2, uint32_t a3, uint64_t db, int sc) {
  asm volatile("{.reg .pred p; setp.ne.b32 p, %25, 0;\n"
               "wgmma.mma_async.sync.aligned.m64n40k16.f32.bf16.bf16 {%0,%1,%2,%3,%4,%5,%6,%7,%8,%9,%10,%11,%12,%13,%14,%15,%16,%17,%18,%19}, {%20,%21,%22,%23}, %24, p, 1, 1, 0;}"
               : ACC20(d) : "r"(a0), "r"(a1), "r"(a2), "r"(a3), "l"(db), "r"(sc));
}
DI void wg_rs32(float* d, uint32_t a0, uint32_t a1, uint32_t a2, uint32_t a3, uint64_t db, int sc) {
  asm volatile("{.reg .pred p; setp.ne.b32 p, %21, 0;\n"
               "wgmma.mma_async.sync.aligned.m64n32k16.f32.bf16.bf16 {%0,%1,%2,%3,%4,%5,%6,%7,%8,%9,%10,%11,%12,%13,%14,%15}, {%16,%17,%18,%19}, %20, p, 1, 1, 0;}"
               : ACC16(d, 0) : "r"(a0), "r"(a1), "r"(a2), "r"(a3), "l"(db), "r"(sc));
}
DI void wg_rs8(float* d, uint32_t a0, uint32_t a1, uint32_t a2, uint32_t a3, uint64_t db, int sc) {
  asm volatile("{.reg .pred p; setp.ne.b32 p, %9, 0;\n"
               "wgmma.mma_async.sync.aligned.m64n8k16.f32.bf16.bf16 {%0,%1,%2,%3}, {%4,%5,%6,%7}, %8, p, 1, 1, 0;}"
               : ACC4(d, 0) : "r"(a0), "r"(a1), "r"(a2), "r"(a3), "l"(db), "r"(sc));
}
DI void mma16816(float* c, const uint32_t* a, uint32_t b0, uint32_t b1) {
  asm volatile("mma.sync.aligned.m16n8k16.row.col.f32.bf16.bf16.f32 {%0,%1,%2,%3}, {%4,%5,%6,%7}, {%8,%9}, {%0,%1,%2,%3};"
               : ACC4(c, 0) : "r"(a[0]), "r"(a[1]), "r"(a[2]), "r"(a[3]), "r"(b0), "r"(b1));
}
DI void wg_ss8(float* d, uint64_t da, uint64_t db, int sc) {
  asm volatile("{.reg .pred p; setp.ne.b32 p, %6, 0;\n"
               "wgmma.mma_async.sync.aligned.m64n8k16.f32.bf16.bf16 {%0,%1,%2,%3}, %4, %5, p, 1, 1, 1, 1;}"
               : ACC4(d, 0) : "l"(da), "l"(db), "r"(sc));
}
DI void wg_rs16(float* d, uint32_t a0, uint32_t a1, uint32_t a2, uint32_t a3, uint64_t db, int sc) {
  asm volatile("{.reg .pred p; setp.ne.b32 p, %13, 0;\n"
               "wgmma.mma_async.sync.aligned.m64n16k16.f32.bf16.bf16 {%0,%1,%2,%3,%4,%5,%6,%7}, {%8,%9,%10,%11}, %12, p, 1, 1, 0;}"
               : ACC4(d, 0), ACC4(d, 4) : "r"(a0), "r"(a1), "r"(a2), "r"(a3), "l"(db), "r"(sc));
}
__device__ uint4 g_xn[2 * NSEG * 10 * 256];
__device__ uint4 g_oT[2 * NBLK * 96 * 1024];
constexpr int PART_RING = 96 * 256;
__device__ uint4 g_part[4 * PART_RING];
constexpr int MEM_OFF = 192;
#define P4 ~0u, ~0u, ~0u, ~0u
#define P16 P4, P4, P4, P4
#define P256 P16, P16, P16, P16, P16, P16, P16, P16, P16, P16, P16, P16, P16, P16, P16, P16
#define P2K P256, P256, P256, P256, P256, P256, P256, P256
#define P8K P2K, P2K, P2K, P2K
__device__ __align__(8192) uint32_t g_mem32[5 * 2 * 2 * 2048] = {P8K, P8K, P8K, P8K, P8K};
#define g_mem ((uint4*)g_mem32)
constexpr int C_XN = 0;
constexpr int C_O = C_XN + 2 * NBLK;
constexpr int C_HALF = C_O + 6 * 2 * NBLK;
constexpr int C_TOTAL = 512;
constexpr int CSTRIDE = 32;
__device__ uint32_t g_cnt[C_TOTAL * CSTRIDE];
constexpr uint32_t XN_TARGET = 128;

#define TRACE(c, n, i, v)
#define SLOG(i)
#define PROF(i)
#define PROFA(c)
#define PROFV(i, v)

constexpr uint32_t SMEM0 = 1024;
constexpr uint32_t SM_WK = 0, SM_WO = 81920, SM_H = 163840, SM_QT = 215040, QSTR = 1056  , SM_KT = SM_QT + 5 * QSTR + 1024,
                   SM_SR = SM_KT + 5120  , SM_PROF = SM_SR + 5760, R_SMEM = 232448,
                   SM_RED = SM_QT + 1024, SM_BAR = SM_RED + 768;
constexpr uint32_t SM_P = SM_KT, SM_OB = SM_QT + 3200;
constexpr uint32_t B_HFULL = SM_BAR, B_HEMPTY = SM_BAR + 40, B_MTRY = SM_BAR + 80, B_W = SM_BAR + 112, B_SR = B_W + 32,
                   B_PMEM = B_SR + 24, B_PTOK = B_SR + 32, B_OB = B_SR + 40, B_OPD = B_SR + 48, B_RFREE = B_SR + 56,
                   B_GATE = B_SR + 64, B_PSUM = B_SR + 72, B_END = B_SR + 80, B_PVI = B_SR + 88,
                   B_OPI = B_SR + 96, B_OTOK = B_SR + 112, SM_TOPI = B_SR + 128, B_PACE = SM_TOPI + 8,
                   SM_RS = SM_QT + 2 * QSTR + 1024;
static_assert(B_PACE + 32 <= SM_QT + 2 * QSTR, "barriers must fit the unused q row group");

struct RParams {
  uint64_t dH, dWK, dWO, dQT, dKT, dP, dOB[6];
  const char* w[4];
  const uint4* mem0;
  const uint32_t* x;
  int pf;
  int nslots, d3, pn, moff, ds, dh;
  int d2[10], d1[8];
  uint32_t slot[2 * NSEG];
};
static void r_fill_desc(RParams& p) {
  p.dH = mkdesc(SMEM0 + SM_H, 128, 2048, 0);
  p.dWK = mkdesc(SMEM0 + SM_WK, 1024, 1024, 1);
  p.dWO = mkdesc(SMEM0 + SM_WO, 1024, 1024, 1);
  for (int i = 0; i < 6; i++) p.dOB[i] = mkdesc(SMEM0 + SM_OB + (i < 3 ? 0 : (i - 3) * 1024), 128, 128, 0);
  p.dQT = mkdesc(SMEM0 + SM_QT, 128, QSTR, 0);
  p.dKT = mkdesc(SMEM0 + SM_KT, 128, 1024, 0);
  p.dP = mkdesc(SMEM0 + SM_P, 128, 640, 0);
}
DI uint64_t dadd(uint64_t d, int bytes) {
  uint64_t r;
  asm volatile("add.u64 %0, %1, %2;" : "=l"(r) : "l"(d), "l"((long long)(bytes / 16)));
  return r;
}
template <int BYTES> DI void dstep(uint64_t& d) { asm volatile("add.u64 %0, %0, %1;" : "+l"(d) : "n"((long long)(BYTES / 16))); }
__host__ __device__ constexpr int hoff(int ks) { return (ks >> 3) * 10240 + (ks & 7) * 256; }

DI int opaque(int v) { asm volatile("" : "+r"(v)); return v; }
DI uint32_t pin(uint32_t v, int lane) { return __shfl_sync(~0u, v + (lane >> 5), lane); }
DI char* pin(char* p, int lane) { return (char*)__shfl_sync(~0u, (unsigned long long)p, lane); }
DI float blo(uint32_t w) { return __uint_as_float(w << 16); }
DI float bhi(uint32_t w) { return __uint_as_float(w & 0xffff0000u); }
#define R_FB 1
#define PIN_DST 1
#define RG0 232
#define RG1 216
#define RG2 40
#define RG3 24
DI void ldsm4t(uint32_t* r, uint32_t a) {
  asm volatile("ldmatrix.sync.aligned.m8n8.x4.trans.shared.b16 {%0,%1,%2,%3}, [%4];" : "=r"(r[0]), "=r"(r[1]), "=r"(r[2]), "=r"(r[3]) : "r"(a) : "memory");
}
DI void st_tagged(void* p, float a, float b, uint32_t keep, uint32_t tagbit) {
  asm volatile("{.reg .b32 t; cvt.rn.bf16x2.f32 t, %2, %1; lop3.b32 t, t, %3, %4, 0xea; st.relaxed.gpu.global.b32 [%0], t;}" ::"l"(p), "f"(a), "f"(b),
               "r"(keep), "r"(tagbit) : "memory");
}
DI uint32_t lop_bad(uint32_t a, uint32_t b, uint32_t m) { uint32_t d; asm("lop3.b32 %0, %1, %2, %3, 0x7e;" : "=r"(d) : "r"(a), "r"(b), "r"(m)); return d; }
DI uint32_t lop_or3(uint32_t a, uint32_t b, uint32_t c) { uint32_t d; asm("lop3.b32 %0, %1, %2, %3, 0xfe;" : "=r"(d) : "r"(a), "r"(b), "r"(c)); return d; }
DI uint32_t clk() { uint32_t t; asm volatile("mov.u32 %0, %%clock;" : "=r"(t)); return t; }
DI void spin(uint32_t cyc) { const uint32_t t0 = clk(); while (__any_sync(~0u, clk() - t0 < cyc)) {} }
template <int NL> DI float2 poll_sum(const uint32_t* src, uint32_t tag, uint32_t even, uint32_t& g) {
  uint32_t r[NL];
  while (true) {
#pragma unroll
    for (int i = 0; i < NL; i++) r[i] = ld_rlx(src + i * 32);
    uint32_t bad = lop_or3(lop_bad(r[0], r[1], tag), lop_bad(r[2], r[3], tag), lop_bad(r[4], r[5], tag));
    if (NL == 12) bad = lop_or3(bad, lop_bad(r[6], r[7], tag), lop_bad(r[8], r[9], tag));
    asm volatile("lop3.b32 %0, %0, %1, %2, 0xa8;" : "+r"(bad) : "r"(lop_bad(r[NL - 2], r[NL - 1], tag)), "r"(even));
    if (!__any_sync(~0u, bad)) break;
    g++;
  }
  float x[NL / 2], y[NL / 2];
#pragma unroll
  for (int i = 0; i < NL / 2; i++) { x[i] = blo(r[2 * i]) + blo(r[2 * i + 1]); y[i] = bhi(r[2 * i]) + bhi(r[2 * i + 1]); }
  float2 u = make_float2((x[0] + x[1]) + (x[2] + x[3]), (y[0] + y[1]) + (y[2] + y[3]));
  if (NL == 12) { u.x += x[4] + x[5]; u.y += y[4] + y[5]; }
  return u;
}

constexpr int PLANE = 16 * 40 * 32, MAXPL = 13;
__device__ uint2 g_acc[(size_t)2 * NBLK * 2 * MAXPL * PLANE];
DI uint2* acc_planes(int lb, int d) { return g_acc + (size_t)((lb * 2 + d) * MAXPL) * PLANE; }
DI void ln_stats(const float4* v, uint32_t red, int warp, int lane, int bar, float& mean, float& rstd) {
  float s = 0.f;
#pragma unroll
  for (int i = 0; i < 5; i++) s += (v[i].x + v[i].y) + (v[i].z + v[i].w);
  s += __shfl_xor_sync(~0u, s, 1);
  s += __shfl_xor_sync(~0u, s, 2);
  s *= 1.f / 80;
  float q = 0.f;
#pragma unroll
  for (int i = 0; i < 5; i++) q += ((v[i].x - s) * (v[i].x - s) + (v[i].y - s) * (v[i].y - s)) + ((v[i].z - s) * (v[i].z - s) + (v[i].w - s) * (v[i].w - s));
  q += __shfl_xor_sync(~0u, q, 1);
  q += __shfl_xor_sync(~0u, q, 2);
  if ((lane & 3) == 0) asm volatile("st.shared.v2.f32 [%0], {%1,%2};" ::"r"(red + lane * 16 + warp * 8), "f"(s), "f"(q) : "memory");
  bar_sync(bar, 256);
  const uint4 t = lds128(red + lane * 16);
  const float m0 = __uint_as_float(t.x), m1 = __uint_as_float(t.z);
  mean = m0 + m1;
  mean += __shfl_xor_sync(~0u, mean, 1);
  mean += __shfl_xor_sync(~0u, mean, 2);
  mean *= 0.125f;
  q = __uint_as_float(t.y) + __uint_as_float(t.w) + 80.f * ((m0 - mean) * (m0 - mean) + (m1 - mean) * (m1 - mean));
  q += __shfl_xor_sync(~0u, q, 1);
  q += __shfl_xor_sync(~0u, q, 2);
  rstd = rsqrtf(q * (1.f / DM) + 1e-5f);
}
template <int SH, int STR> DI void store_img(uint32_t* dst, const float4* v, int warp, float mean, float rstd) {
#pragma unroll
  for (int i = 0; i < 5; i++) {
    const int U = 10 * warp + 2 * i;
    uint32_t* p = dst + (U >> SH) * STR + (U & ((1 << SH) - 1)) * 32;
    p[0] = pack2((v[i].x - mean) * rstd, (v[i].y - mean) * rstd);
    p[32] = pack2((v[i].z - mean) * rstd, (v[i].w - mean) * rstd);
  }
}
DI uint32_t* xn_row_group(int layer, int rg) { return (uint32_t*)(g_xn + (size_t)((layer * NSEG + (rg >> 2)) * 2560 + (rg & 3) * 128)); }

DI void first_ln(const uint32_t* a, int rg, uint32_t red, int warp, int lane, int bar) {
  float4 v[5];
#pragma unroll
  for (int i = 0; i < 5; i++) {
    v[i] = make_float4(blo(a[2 * i]), bhi(a[2 * i]), blo(a[2 * i + 1]), bhi(a[2 * i + 1]));
    acc_planes(rg >> 4, 0)[((rg & 15) * 40 + warp * 5 + i) * 32 + lane] = make_uint2(a[2 * i], a[2 * i + 1]);
  }
  float mean, rstd;
  ln_stats(v, red, warp, lane, bar, mean, rstd);
  store_img<4, 2048>(xn_row_group(0, rg) + lane, v, warp, mean, rstd);
}
#define QK_P0 32
#define QK_KB 0
struct QKOrder { int op[76]; };
__host__ __device__ constexpr QKOrder qk_order() {
  QKOrder o = {};
  int n = 0, k = 0, q = 0;
  for (; k < QK_P0; k++, q++) { o.op[n++] = 64 | k; o.op[n++] = q; }
  for (int i = 0; i < QK_KB; i++) o.op[n++] = 64 | k++;
  for (int i = 0; i < -QK_KB; i++) o.op[n++] = q++;
  const int nk = 40 - k, nq = 36 - q;
  for (int i = 0, dk = 0, dq = 0; i < nk + nq; i++) {
    if (dq * nk <= dk * nq + (QK_KB ? 0 : -nq) && dq < nq) { o.op[n++] = q++; dq++; } else if (dk < nk) { o.op[n++] = 64 | k++; dk++; } else { o.op[n++] = q++; dq++; }
  }
  return o;
}
__global__ void __launch_bounds__(512, 1)
r_kernel(const __grid_constant__ CUtensorMap mapWq, const __grid_constant__ CUtensorMap mapWk, const __grid_constant__ CUtensorMap mapWv,
         const __grid_constant__ CUtensorMap mapWo, const __grid_constant__ RParams prm) {
  const uint32_t sb = smem_base();
  const int wid = __shfl_sync(~0u, threadIdx.x >> 5, 0);
  const int lane0 = __shfl_sync(~0u, threadIdx.x & 31, threadIdx.x & 31);
  const int lane = lane0;
  const int warp = wid & 3, wg = wid >> 2;
  const uint32_t rank = blockIdx.x, head = blockIdx.y, cta = head * 3 + rank;
  const uint32_t peer1 = mapa(sb, rank == 2 ? 0 : rank + 1), peer2 = mapa(sb, rank == 0 ? 2 : rank - 1);
  const int nslots = prm.nslots;

  SLOG(0);
  if (threadIdx.x == 384) {
    if ((sb & 0x3FFFF) != SMEM0) __trap();
    for (int c = 0; c < 5; c++) { mbar_init(sb + B_HFULL + 8 * c, 2); mbar_init(sb + B_HEMPTY + 8 * c, c == 4 ? 8 : 4); }
    for (int c = 0; c < 11; c++) mbar_init(sb + B_MTRY + 8 * c, 1);
    mbar_init(sb + B_PTOK, rank == 0 ? 3 : 2); mbar_init(sb + B_OB, 5); mbar_init(sb + B_OPD, 4);
    mbar_init(sb + B_OPI, 1); mbar_init(sb + B_OPI + 8, 1); mbar_init(sb + B_RFREE, 1); mbar_init(sb + B_GATE, 1); mbar_init(sb + B_PMEM, 2); mbar_init(sb + B_PSUM, 2); mbar_init(sb + B_PVI, 1); mbar_init(sb + B_OTOK, 4); mbar_init(sb + B_OTOK + 8, 4); mbar_init(sb + B_END, 15);
    for (int c = 0; c < 4; c++) mbar_init(sb + B_PACE + 8 * c, 1);
    asm volatile("fence.mbarrier_init.release.cluster;" ::: "memory");
    fence_async_smem();
  }
  asm volatile("griddepcontrol.launch_dependents;");
  asm volatile("barrier.cluster.arrive.release.aligned;" ::: "memory");

  if (wg < 2) {
  {
    uint32_t xa[10];
    const uint32_t* src = prm.x + (size_t)(cta * 8 + (lane >> 2)) * (DM / 2) + wid * 40 + (lane & 3);
#pragma unroll
    for (int i = 0; i < 10; i++) xa[i] = __ldg(src + i * 4);
    asm volatile("barrier.cluster.wait.acquire.aligned;" ::: "memory");
    first_ln(xa, cta, sb + SM_SR, wid, lane, 8);
    bar_arrive(10, 288);
  }
  if (wg == 0) {
    asm volatile("setmaxnreg.inc.sync.aligned.u32 %0;" ::"n"(RG0));
    uint32_t wq[160];
    SLOG(1);
    mbar_wait(sb + B_W, 0);
    SLOG(2);
    {
      const uint32_t ld_off = ((lane >> 4) * 8 + (lane & 7)) * 128 + (((2 * warp + ((lane >> 3) & 1)) ^ (lane & 7)) << 4);
#pragma unroll
      for (int ks = 0; ks < 40; ks++) ldsm4t(wq + 4 * ks, sb + SM_WO + ks * 2048 + ld_off);
    }
    fence_async_smem();
    bar_arrive(5, 160);
    mbar_wait(sb + B_W + 16, 0);
    SLOG(3);
    const uint32_t st_addr = pin(sb + SM_QT + (lane >> 4) * 1024 + (2 * warp + ((lane >> 3) & 1)) * 128 + (lane & 7) * 16, lane);
    const uint32_t sq_addr = pin(sb + SM_QT + (2 + (lane & 3)) * QSTR + warp * 256 + (lane >> 2) * 16, lane);
    const uint32_t to_lo = warp == 0 ? peer1 : mapa(sb, warp == 2 ? 2 : 0), to_hi = warp == 0 ? peer2 : mapa(sb, warp == 1 ? 1 : 0);
    const uint32_t sr_off = SM_SR + warp * 1920 + rank * 640, sr_bar = B_SR + warp * 8;
    const uint32_t sa0 = pin(to_lo + sr_off + lane * 16, lane), sb0 = pin(to_lo + sr_bar, lane), sa1 = pin(to_lo + sr_off + 512 + lane * 4, lane), sb1 = pin(sb0, lane);
    const uint32_t sa2 = pin(to_hi + sr_off + lane * 16, lane), sb2 = pin(to_hi + sr_bar, lane), sa3 = pin(to_hi + sr_off + 512 + lane * 4, lane), sb3 = pin(sb2, lane);
#pragma unroll 1
    for (int n = 0; n < nslots; n++) {
      const uint32_t par = n & 1;
      PROFA(warp == PW);
      float qa[20], ka[20];
      uint64_t rk = prm.dWK, rh = prm.dH, rq;
      auto K = [&](int ks) { wg_ss40<1, 0>(ka, rk, rh, ks != 0); };
      auto Q = [&](int ks, uint64_t db) { wg_rs40(qa, wq[4 * ks], wq[4 * ks + 1], wq[4 * ks + 2], wq[4 * ks + 3], db, ks != 0); };
      auto next = [&](uint64_t& d, int ks) { if ((ks & 7) == 7) dstep<10240 - 7 * 256>(d); else dstep<256>(d); };
      constexpr QKOrder ord = qk_order();
      auto first = [&](int g, int c) { for (int i = 0; i < 76; i++) if ((ord.op[i] & 63) >> 3 == c) return i >> 2 == g; return false; };
      bool ok = true;
      mbar_wait(sb + B_HFULL, par);
#pragma unroll
      for (int g = 0; g < 19; g++) {
        if (!ok) {
#pragma unroll
          for (int c = 1; c < 5; c++) if (first(g, c)) mbar_wait(sb + B_HFULL + 8 * c, par);
          mbar_wait(sb + B_GATE, 1);
        }
        if (g == 0) PROF(0);
        if (g < 18) ok = mbar_test(sb + B_GATE, 1);
#pragma unroll
        for (int c = 1; c < 5; c++) if (first(g + 1, c)) ok &= mbar_test(sb + B_HFULL + 8 * c, par);
        wg_fence();
#pragma unroll
        for (int i = 4 * g; i < 4 * g + 4; i++) {
          const int ks = ord.op[i] & 63;
          if (i < 2 * QK_P0) {
            if (ord.op[i] & 64) K(ks);
            else { Q(ks, rh); dstep<2048>(rk); next(rh, ks); if (i == 2 * QK_P0 - 1) rq = rh; }
          } else if (ord.op[i] & 64) { K(ks); if (ks < 39) { dstep<2048>(rk); next(rh, ks); } }
          else { Q(ks, rq); next(rq, ks); }
        }
        if (g == 17) wg_commit();
      }
      wg_commit();
#pragma unroll
      for (int ks = 36; ks < 40; ks++) { Q(ks, rq); if (ks < 39) dstep<256>(rq); }
      wg_commit();
      wg_wait<2>();
      const bool alt = prm.slot[n] & 128;
      if (alt) bar_arrive(2, 256);
      mbar_wait(sb + B_OPD, par ^ 1);
      wg_wait<1>();
      if (!alt) bar_arrive(2, 256);
      reg_fence<20>(ka);
      stsm2(st_addr + (SM_KT - SM_QT), pack2(ka[0], ka[1]), pack2(ka[2], ka[3]));
      stsm4(st_addr + (SM_KT - SM_QT) + 1024, pack2(ka[4], ka[5]), pack2(ka[6], ka[7]), pack2(ka[8], ka[9]), pack2(ka[10], ka[11]));
      stsm4(st_addr + (SM_KT - SM_QT) + 3072, pack2(ka[12], ka[13]), pack2(ka[14], ka[15]), pack2(ka[16], ka[17]), pack2(ka[18], ka[19]));
      wg_wait<0>();
      reg_fence<20>(qa);
      PROF(9);
      stsm2(st_addr, pack2(qa[0], qa[1]), pack2(qa[2], qa[3]));
      sts128(sq_addr, make_uint4(pack2(qa[4], qa[5]), pack2(qa[8], qa[9]), pack2(qa[12], qa[13]), pack2(qa[16], qa[17])));
      sts128(sq_addr + 128, make_uint4(pack2(qa[6], qa[7]), pack2(qa[10], qa[11]), pack2(qa[14], qa[15]), pack2(qa[18], qa[19])));
      mbar_arrive_if(lane == 0, sb + B_HEMPTY + 32);
      fence_async_smem();
      bar_sync(1, 128);
      PROF(1);
      wg_fence();
#pragma unroll
      for (int k = 0; k < 4; k++) wg_ss40<1, 1>(qa, dadd(prm.dQT, k * 256), dadd(prm.dKT, k * 256), k != 0);
      wg_commit();
      bar_arrive(7, 256);
      wg_wait<0>();
      reg_fence<20>(qa);
      PROF(3);
      if (warp < 3) {
        uint32_t p[5];
#pragma unroll
        for (int j = 0; j < 5; j++) p[j] = pack2(qa[4 * j], qa[4 * j + 1]);
        if (warp == 0) {
          st_async4(sa0, p[0], p[1], p[2], p[3], sb0);
          st_async4(sa2, p[0], p[1], p[2], p[3], sb2);
          st_async1(sa1, p[4], sb1);
          st_async1(sa3, p[4], sb3);
          sts128(sb + sr_off + lane * 16, make_uint4(p[0], p[1], p[2], p[3]));
          sts32(sb + sr_off + 512 + lane * 4, p[4]);
          __syncwarp();
          mbar_expect_if(lane == 0, sb + B_SR, 1280);
        } else {
          uint32_t h[5];
#pragma unroll
          for (int j = 0; j < 5; j++) h[j] = pack2(qa[4 * j + 2], qa[4 * j + 3]);
          spin(prm.d3);
          st_async4(sa0, p[0], p[1], p[2], p[3], sb0);
          st_async4(sa2, h[0], h[1], h[2], h[3], sb2);
          st_async1(sa1, p[4], sb1);
          st_async1(sa3, h[4], sb3);
        }
      }
    }
  } else {
    asm volatile("setmaxnreg.inc.sync.aligned.u32 %0;" ::"n"(RG1));
    uint32_t wv[160];
    mbar_wait(sb + B_W + 8, 0);
    SLOG(4);
    {
      const uint32_t ld_off = ((lane >> 4) * 8 + (lane & 7)) * 128 + (((2 * warp + ((lane >> 3) & 1)) ^ (lane & 7)) << 4);
#pragma unroll
      for (int ks = 0; ks < 40; ks++) ldsm4t(wv + 4 * ks, sb + SM_WO + ks * 2048 + ld_off);
    }
    fence_async_smem();
    bar_arrive(6, 160);
    const uint64_t dH = prm.dH;
    uint32_t op[8];
    const uint32_t ob_off = SM_OB + (4 * rank + warp) * 256 + lane * 4;
    const uint32_t oa0 = pin(peer1 + ob_off, lane), ob0 = pin(peer1 + B_OB, lane), oa1 = pin(peer2 + ob_off, lane), ob1 = pin(peer2 + B_OB, lane);
    const uint32_t oa2 = pin(oa0 + 128, lane), ob2 = pin(ob0, lane), oa3 = pin(oa1 + 128, lane), ob3 = pin(ob1, lane);
    const uint32_t o_loc = pin(sb + ob_off, lane), rs_addr = pin(sb + SM_RS + (lane & 3) * 8, lane);
    const uint32_t tok_off = pin((cta * 1024 + 64 * warp + (lane ^ (lane >> 3))) * 16, lane), keep = pin((lane & 1) ? ~0u : ~1u, lane);
    const uint32_t pb_off = pin((8 * rank + 2 * warp) * 4096 + head * 128 + lane * 4, lane);
    const uint32_t ph_off = pin(72 * 4096 + 2 * warp * 12288 + cta * 64 + (lane & 2) * 3072 + (lane >> 2) * 8 + (lane & 1) * 4, lane);
    auto store_tok = [&](int m, int lane) {
      const uint32_t ls = prm.slot[m] & 127, sig = prm.slot[m] >> 16;
      uint4* dst = (uint4*)((char*)(g_oT + (size_t)((ls >> 2) * (96 * 1024) + (ls & 3) * 256)) + tok_off);
      dst[0] = make_uint4(op[0], op[1], op[2], op[3]);
      dst[32] = make_uint4(op[4], op[5], op[6], op[7]);
      __syncwarp();
      mbar_arrive_if(sig && lane == 0, sb + B_OTOK + (ls >> 6) * 8);
    };
#pragma unroll 1
    for (int n = 0; n < nslots; n++) {
      const uint32_t par = n & 1;
      const int lane = opaque(lane0);
      PROFA(warp == PW);
      float va[20];
      const bool alt = prm.slot[n] & 128;
      mbar_expect_if(warp == 0 && lane == 0, sb + B_PTOK, rank == 0 ? 1280 : 1920);
      bar_sync(2, 256);
#pragma unroll
      for (int g = 0; g < 10; g++) {
        wg_fence();
#pragma unroll
        for (int ks = 4 * g; ks < 4 * g + 4; ks++) { wg_rs40(va, wv[4 * ks], wv[4 * ks + 1], wv[4 * ks + 2], wv[4 * ks + 3], dadd(dH, hoff(ks)), ks != 0); }
        wg_commit();
        if (g >= 2 && !(g & 1)) {
          wg_wait<1>();
          if (lane == 0) mbar_arrive(sb + B_HEMPTY + 8 * (g / 2 - 1));
        }
        if (g == 1 ? !alt : g == 2 && alt) bar_sync(7, 256);
      }
      wg_wait<0>();
      reg_fence<20>(va);
      if (lane == 0) mbar_arrive(sb + B_HEMPTY + 32);
      PROF(10);
      uint32_t vf[10];
#pragma unroll
      for (int j = 0; j < 10; j++) {
        const int i = (j + 4) % 10;
        asm volatile("cvt.rn.bf16x2.f32 %0, %1, %2;" : "=r"(vf[i]) : "f"(va[2 * i + 1]), "f"(va[2 * i]));
        if (j == 5) mbar_wait(sb + B_W + 8, 0);
      }
      uint32_t z0, z1;
      asm volatile("shr.u32 %0, %2, 5; shr.u32 %1, %2, 6;" : "=r"(z0), "=r"(z1) : "r"(lane));
      const uint32_t info = prm.slot[n];
      const uint32_t tagbit = ~(info >> 1) & ~keep;
      char* const ring = (char*)(g_part + (size_t)((((info >> 5) & 2) + (info & 1)) * PART_RING));
      char* const pb = pin(ring + pb_off, lane);
      char* const ph = ring + ph_off;
      mbar_wait(sb + B_PMEM, par);
      float om[4];
      wg_fence();
      wg_rs8(om, vf[0], vf[1], vf[2], vf[3], prm.dP, 0);
      wg_rs8(om, vf[4], vf[5], vf[6], vf[7], dadd(prm.dP, 256), 1);
      wg_rs8(om, vf[8], vf[9], z0, z1, dadd(prm.dP, 512 - (128 << 16)), 1);
      wg_commit();
      {
        wg_wait<0>();
        reg_fence<4>(om);
        const uint32_t b0 = pack2(om[0], om[1]), b1 = pack2(om[2], om[3]);
        st_async1(oa0, b0, ob0);
        st_async1(oa1, b0, ob1);
        st_async1(oa2, b1, ob2);
        st_async1(oa3, b1, ob3);
        sts32(o_loc, b0);
        sts32(o_loc + 128, b1);
        fence_async_smem();
        __syncwarp();
        mbar_arrive_if(lane == 0, sb + B_OB);
      }
      PROF(11);
      {
        float c[8];
        mbar_wait(sb + B_PSUM, par);
        const uint2 rs = lds64(rs_addr);
        const float r0 = __uint_as_float(rs.x), r1 = __uint_as_float(rs.y);
        if (n == 0) { SLOG(5); mbar_wait(sb + B_W + 24, 0); SLOG(6); }
        mbar_wait(sb + B_OB, par);
        asm volatile("fence.proxy.async::generic.acquire.sync_restrict::shared::cluster.cluster;" ::: "memory");
        PROF(16);
        if ((info & 63) == NSEG - 1) {
          mbar_wait(sb + B_OPI + par * 8, (n >> 1) & 1);
          mbar_arrive_if(warp == 3 && lane == 0, sb + B_GATE);
#pragma unroll
          for (int p = 0; p < 6; p++) st_rlx1(pb + (p >> 1) * 98304 + (p & 1) * 4096, tagbit);
          st_rlx1(ph, tagbit);
          st_rlx1(ph + 12288, tagbit);
        } else {
#pragma unroll
        for (int p = 0; p < 4; p++) {
          float* const cur = c + 4 * (p & 1);
          float* const prv = c + 4 * (~p & 1);
          if (p == 2) mbar_wait(sb + B_OPI + par * 8, (n >> 1) & 1);
          wg_fence();
#pragma unroll
          for (int ks = 0; ks < (p < 3 ? 12 : 4); ks++) {
            wg_ss8(cur, dadd(prm.dWO, p * 24576 + ks * 2048), dadd(prm.dOB[p < 3 ? p : 3 + rank], ks * 256), ks != 0);
            if (p == 3 && ks == 3) mbar_arrive_if(warp == 3 && lane == 0, sb + B_GATE);
            if (p > 0 && ks == 3) {
              wg_commit();
              wg_wait<1>();
              reg_fence<4>(prv);
              st_tagged(pb + (p - 1) * 98304, prv[0] * r0, prv[1] * r1, keep, tagbit);
              st_tagged(pb + (p - 1) * 98304 + 4096, prv[2] * r0, prv[3] * r1, keep, tagbit);
            }
          }
          if (p < 3) wg_commit();
        }
        wg_wait<0>();
        reg_fence<4>(c + 4);
        st_tagged(ph, c[4] * r0, c[5] * r1, keep, tagbit);
        st_tagged(ph + 12288, c[6] * r0, c[7] * r1, keep, tagbit);
        }
        PROF(17);
      }
      mbar_wait(sb + B_PTOK, par);
      PROF(12);
      {
        float ot[16];
        wg_fence();
        wg_rs32(ot, vf[0], vf[1], vf[2], vf[3], dadd(prm.dP, 640), 0);
        wg_rs32(ot, vf[4], vf[5], vf[6], vf[7], dadd(prm.dP, 640 + 256), 1);
        wg_rs32(ot, vf[8], vf[9], z0, z1, dadd(prm.dP, 640 + 512 - (128 << 16)), 1);
        wg_commit();
        wg_wait<0>();
        reg_fence<16>(ot);
#pragma unroll
        for (int i = 0; i < 8; i++) op[(i & 1) * 4 + (i >> 1)] = pack2(ot[2 * i], ot[2 * i + 1]);
      }
      if (lane == 0) mbar_arrive(sb + B_OPD);
      PROF(13);
      if (info & 128) spin(prm.ds);
      store_tok(n, lane);
    }
  }
  } else if (wg == 2) {
    asm volatile("setmaxnreg.dec.sync.aligned.u32 %0;" ::"n"(RG2));
    asm volatile("barrier.cluster.wait.acquire.aligned;" ::: "memory");
    if (warp == 1) {
      const uint32_t depth = prm.pf & 7;
#pragma unroll 1
      for (uint32_t i = 0; i < 20 + depth; i++) {
        if (i >= depth) {
          const uint32_t j = i - depth;
          mbar_wait_wd(sb + B_PACE + 8 * (j & 3), (j >> 2) & 1);
          if (j % 5 == 4) mbar_arrive_if(lane == 0 && (j != 14 || depth == 1), sb + B_W + (j == 4 ? 0 : j == 9 ? 16 : j == 14 ? 8 : 24));
        }
        if (i >= 20) continue;
        const uint32_t m = i / 5, k = i % 5, bar = sb + B_PACE + 8 * (i & 3);
        if (i == 10) bar_sync(5, 160);
        if (i == 15) {
          if ((prm.pf & 8) && elect_one())
            for (int q = 0; q < 4; q++) tma_pf(&mapWo, (q / 3 * 3 + rank) * 64, head * DH + q % 3 * 64);
#pragma unroll 1
          for (uint32_t j = 16 - depth; j < 15; j++) mbar_wait_wd(sb + B_PACE + 8 * (j & 3), (j >> 2) & 1);
          mbar_arrive_if(lane == 0 && depth > 1, sb + B_W + 8);
          bar_sync(6, 160);
        }
        if (elect_one()) {
          mbar_expect(bar, 16384);
          if (m < 3) tma_2d(sb + (m == 1 ? SM_WK : SM_WO) + k * 16384, m == 0 ? &mapWq : m == 1 ? &mapWk : &mapWv, cta * 64, k * 128, bar);
          else
            for (uint32_t q = 2 * k; q < 2 * k + 2; q++)
              tma_2d(sb + SM_WO + q * 8192, &mapWo, q < 9 ? (q / 3 * 3 + rank) * 64 : 576, head * DH + (q < 9 ? q % 3 : rank) * 64, bar);
        }
      }
    }
    if (warp == 2 && cta < 80 && lane < 16)
      g_mem[(cta >> 4) * 2048 + (lane >> 3) * 1024 + prm.moff + (cta & 15) * 8 + (lane & 7)] = prm.mem0[(lane & 7) * 80 + cta];
    if (warp == 3) {
      bar_sync(10, 288);
      if (lane == 0) red_rel(&g_cnt[(C_XN + (cta >> 4)) * CSTRIDE], 8);
    }
    const uint32_t grp = warp == 1 ? 1 + rank : 4 - (rank >> 1);
    constexpr float SC = 0.07216878364870322f * 1.4426950408889634f;
    const bool split = cta >= 72;
    const uint32_t wd = split ? 72 * 16 + cta * 16 : cta * 32;
    const uint32_t src_off = pin(split ? 72 * 4096 + (cta - 72) * 6144 + warp * 1536 + (lane & 2) * 32 + (lane >> 2) * 8 + (lane & 1) * 4 : cta * 4096 + warp * 1024 + lane * 4, lane);
    const uint32_t dst_off = pin(((wd >> 9) * 8192 + prm.moff * 4 + (wd & 511) + lane) * 4, lane);
    const uint32_t red = pin(sb + SM_RED + (warp < 2 ? 0 : (warp - 1) * 256) + lane * 8, lane);
    const uint32_t fl = (warp & 2) * 8 + (lane >> 3) * 4 + (lane & 3), hf = lane & 4;
    const uint32_t s0 = pin(sb + SM_SR + fl * 16 + hf * 2, lane), s1 = pin(sb + fl * 4, lane), pd = pin(s1 + hf * 64, lane);
    const uint32_t even = pin(~lane & 1, lane);
    uint32_t nred = 0;
    const uint32_t arm = pin(warp == 0 && (lane == 5 || ((lane == 1 || lane == 2) && lane + rank != 3)) ? sb + B_SR + lane * 8 : 0, lane);
#pragma unroll 1
    for (int n = 0; n < nslots; n++) {
      const uint32_t par = n & 1;
      const int lane = opaque(lane0);
      PROFA(warp == PW2);
      const uint32_t info = prm.slot[n], s = info & 63, l = (info >> 6) & 1;
      {
        mbar_expect_if(arm, arm, lane == 5 ? 2048 : 1920);
        if (warp == 0 || warp == 3) {
          mbar_wait(sb + B_SR, par);
          PROF(4);
          const uint2 a0 = lds64(s0), a1 = lds64(s0 + 640), a2 = lds64(s0 + 1280);
          const uint32_t b0 = lds32(s1 + SM_SR + 512), b1 = lds32(s1 + SM_SR + 1152), b2 = lds32(s1 + SM_SR + 1792);
          float v[6];
          v[0] = blo(a0.x) + blo(a1.x) + blo(a2.x); v[1] = bhi(a0.x) + bhi(a1.x) + bhi(a2.x);
          v[2] = blo(a0.y) + blo(a1.y) + blo(a2.y); v[3] = bhi(a0.y) + bhi(a1.y) + bhi(a2.y);
          v[4] = blo(b0) + blo(b1) + blo(b2); v[5] = bhi(b0) + bhi(b1) + bhi(b2);
          float m = fmaxf(fmaxf(v[0], v[1]), fmaxf(v[2], v[3]));
          m = fmaxf(fmaxf(m, __shfl_xor_sync(~0u, m, 4)), fmaxf(v[4], v[5]));
          {
            const float m1 = __shfl_xor_sync(~0u, m, 1), m2 = __shfl_xor_sync(~0u, m, 2), m3 = __shfl_xor_sync(~0u, m, 3);
            m = fmaxf(fmaxf(m, m1), fmaxf(m2, m3));
          }
          const float ms = -m * SC;
#pragma unroll
          for (int i = 0; i < 6; i++) v[i] = ex2(fmaf(v[i], SC, ms));
          float sum = (v[0] + v[1]) + (v[2] + v[3]);
          const float so = __shfl_xor_sync(~0u, sum, 4);
          sts32(pd + SM_P, pack2(v[0], v[1]));
          sts32(pd + SM_P + 128, pack2(v[2], v[3]));
          sts32(s1 + SM_P + 512, pack2(v[4], v[5]));
          fence_async_smem();
          __syncwarp();
          mbar_arrive_if(lane == 0, sb + B_PMEM);
          PROF(5);
          sum += so + (v[4] + v[5]);
          {
            const float t1 = __shfl_xor_sync(~0u, sum, 1), t2 = __shfl_xor_sync(~0u, sum, 2), t3 = __shfl_xor_sync(~0u, sum, 3);
            sum = (sum + t1) + (t2 + t3);
          }
          float r;
          asm("rcp.approx.ftz.f32 %0, %1;" : "=f"(r) : "f"(sum));
          sts32(sb + SM_RS + (warp & 2) * 8 + (lane >> 3) * 4, __float_as_uint(r));
          __syncwarp();
          mbar_arrive_if(lane == 0, sb + B_PSUM);
        } else {
          if (warp + rank != 3) {
            const uint32_t src = sb + SM_SR + warp * 1920;
            mbar_wait(sb + B_SR + warp * 8, par);
            const uint4 a0 = lds128(src + lane * 16), a1 = lds128(src + 640 + lane * 16), a2 = lds128(src + 1280 + lane * 16);
            const uint32_t b0 = lds32(src + 512 + lane * 4), b1 = lds32(src + 1152 + lane * 4), b2 = lds32(src + 1792 + lane * 4);
            float v[10];
            v[0] = blo(a0.x) + blo(a1.x) + blo(a2.x); v[1] = bhi(a0.x) + bhi(a1.x) + bhi(a2.x);
            v[2] = blo(a0.y) + blo(a1.y) + blo(a2.y); v[3] = bhi(a0.y) + bhi(a1.y) + bhi(a2.y);
            v[4] = blo(a0.z) + blo(a1.z) + blo(a2.z); v[5] = bhi(a0.z) + bhi(a1.z) + bhi(a2.z);
            v[6] = blo(a0.w) + blo(a1.w) + blo(a2.w); v[7] = bhi(a0.w) + bhi(a1.w) + bhi(a2.w);
            v[8] = blo(b0) + blo(b1) + blo(b2); v[9] = bhi(b0) + bhi(b1) + bhi(b2);
            {
              const int lim = 6 + 2 * grp + (lane & 24) + ((lane >> 2) & 1) - 2 * (lane & 3);
#pragma unroll
              for (int i = 2; i < 10; i++) if ((i >> 1) * 8 + (i & 1) > lim) v[i] = -INFINITY;
            }
            float m = fmaxf(fmaxf(fmaxf(v[0], v[1]), fmaxf(v[2], v[3])), fmaxf(fmaxf(v[4], v[5]), fmaxf(v[6], v[7])));
            m = fmaxf(m, fmaxf(v[8], v[9]));
            {
              const float m1 = __shfl_xor_sync(~0u, m, 1), m2 = __shfl_xor_sync(~0u, m, 2), m3 = __shfl_xor_sync(~0u, m, 3);
              m = fmaxf(fmaxf(m, m1), fmaxf(m2, m3));
            }
            const float ms = -m * SC;
#pragma unroll
            for (int i = 0; i < 10; i++) v[i] = ex2(fmaf(v[i], SC, ms));
            float sum = ((v[0] + v[1]) + (v[2] + v[3])) + ((v[4] + v[5]) + (v[6] + v[7])) + (v[8] + v[9]);
            {
              const float s1 = __shfl_xor_sync(~0u, sum, 1), s2 = __shfl_xor_sync(~0u, sum, 2), s3 = __shfl_xor_sync(~0u, sum, 3);
              sum = (sum + s1) + (s2 + s3);
            }
            float r;
            asm("rcp.approx.ftz.f32 %0, %1;" : "=f"(r) : "f"(sum));
            {
              const uint32_t row = SM_P + grp * 640;
#pragma unroll
              for (int j = 0; j < 5; j++) sts32(sb + row + j * 128 + lane * 4, pack2(v[2 * j] * r, v[2 * j + 1] * r));
              fence_async_smem();
              __syncwarp();
              mbar_arrive_if(lane == 0, sb + B_PTOK);
              if (elect_one()) {
                bulk_s2s(peer1 + row, sb + row, 640, peer1 + B_PTOK);
                bulk_s2s(peer2 + row, sb + row, 640, peer2 + B_PTOK);
              }
            }
          }
        }
      }
      const uint32_t* const src = (const uint32_t*)((char*)(g_part + (size_t)((l * 2 + (s & 1)) * PART_RING)) + src_off);
      uint32_t* const dst = (uint32_t*)pin((char*)(g_mem + l * 1024 + (~s & 1) * 512) + dst_off, lane);
      {
        const uint32_t d1 = prm.d1[cta / 24 + ((info >> 5) & 4)];
        if (warp == 3) {
          mbar_wait(sb + B_OB, par);
          mbar_arrive_if(lane == 0, sb + B_GATE);
          sts32(sb + SM_TOPI + par * 4, clk());
          __syncwarp();
          mbar_arrive_if(lane == 0, sb + B_OPI + par * 8);
          TRACE(true, n, 0, gtl());
        }
        const bool reduce = cta < 88 && s != NSEG - 1;
        if (reduce || warp == 0) mbar_wait(sb + B_OPI + par * 8, (n >> 1) & 1);
        if (!reduce) continue;
        mbar_wait(sb + B_RFREE, (nred++ & 1) ^ 1);
        mbar_wait(sb + B_GATE, 1);
        if (d1) spin(d1);
      }
      {
        uint32_t g = 0;
        float2 u;
        PROF(14);
        if (!split) {
          u = poll_sum<8>(src, ~(s >> 1), even, g);
        } else {
          u = poll_sum<12>(src, ~(s >> 1), even, g);
          u.x += __shfl_xor_sync(~0u, u.x, 2);
          u.y += __shfl_xor_sync(~0u, u.y, 2);
        }
        PROF(18);
        if (warp != 1) {
          asm volatile("st.shared.v2.f32 [%0], {%1,%2};" ::"r"(red), "f"(u.x), "f"(u.y) : "memory");
          bar_arrive(3, 128);
        } else {
          bar_sync(3, 128);
          const uint2 o0 = lds64(red), o1 = lds64(red + 256), o2 = lds64(red + 512);
          const uint32_t w = movm(pack2((u.x + __uint_as_float(o0.x)) + (__uint_as_float(o1.x) + __uint_as_float(o2.x)),
                                        (u.y + __uint_as_float(o0.y)) + (__uint_as_float(o1.y) + __uint_as_float(o2.y))));
          if (!split || lane < 16) {
            st_rlx1(dst, w);
            st_rlx1(dst + ((s & 1) ? 2048 : -2048), ~0u);
          }
          mbar_arrive_if(lane == 0, sb + B_RFREE);
        }
        PROF(19);
        PROFV(2, g);
        TRACE(warp == 1, n, 1, gtl());
        TRACE(g, n, 2, g);
      }
    }
  } else {
    asm volatile("setmaxnreg.dec.sync.aligned.u32 %0;" ::"n"(RG3));
    asm volatile("barrier.cluster.wait.acquire.aligned;" ::: "memory");
    const uint32_t chk = lane * 32 + ((lane >> 2) << 2);
    const uint32_t bar = sb + B_MTRY + 8 * warp;
    uint32_t mph = 0, waited = 0, pub = 0, pph = 0;
    auto publish = [&](uint32_t upto) {
#pragma unroll 1
      for (; pub < upto; pub++) {
        const uint32_t e = prm.slot[pub], l = (e >> 6) & 1;
        if (warp == 3 && (e >> 16)) {
          mbar_wait_wd(sb + B_OTOK + l * 8, (pph >> l) & 1);
          pph ^= 1 << l;
          if (elect_one()) red_rel(&g_cnt[(e >> 16) * CSTRIDE], 1);
        }
      }
    };
#pragma unroll 1
    for (int m = 0; m < nslots; m++) {
      const uint32_t info = prm.slot[m], prod = (info >> 8) & 255, ls = info & 127;
      uint32_t g = 0;
#pragma unroll 1
      for (; waited < prod && waited + 1 < m; waited++) mbar_wait_wd(sb + B_OPI + (waited & 1) * 8, (waited >> 1) & 1);
      uint32_t t0 = lds32(sb + SM_TOPI + (~waited & 1) * 4);
      publish(waited);
      if ((ls & 3) == 0) {
        while (__any_sync(~0u, ld_acq(&g_cnt[(C_XN + (ls >> 2)) * CSTRIDE]) < XN_TARGET)) guard(g);
        fence_async_global();
      }
#pragma unroll 1
      for (uint32_t c = warp; c < 5; c += 4) {
        const uint32_t dst = sb + SM_H + c * 10240, full = sb + B_HFULL + 8 * c;
        const uint4* src = g_mem + (c * 2048 + (ls >> 6) * 1024 + (ls & 1) * 512 + prm.moff);
        const uint32_t d = prod ? prm.d2[(m - prod) * 5 + c] : 0;
        const uint4* tok = g_xn + (size_t)(ls * 2560 + c * 512);
        const uint32_t pp = (m & 1) ^ 1;
        const bool single = waited < prod;
        mbar_wait_wd(full, pp);
        mbar_expect_if(lane < 2, lane ? bar : full, lane ? 2048 : 8192);
        if (!single) while (__any_sync(~0u, clk() - t0 < d)) {}
        if (c >= 2) mbar_wait_wd(sb + B_HEMPTY + 8 * c, pp);
        mbar_wait_wd(sb + (c < 2 ? B_HEMPTY + 8 * c : c == 2 && !single ? B_PMEM : B_OB), pp);
        if (c != 2 || single) { if (elect_one()) bulk_g2s(dst + 2048, tok, 8192, full); }
        if (single) {
          mbar_wait_wd(sb + B_OPI + (waited & 1) * 8, (waited >> 1) & 1);
          waited++;
          t0 = lds32(sb + SM_TOPI + (~waited & 1) * 4);
          publish(waited);
          while (__any_sync(~0u, clk() - t0 < d)) {}
        }
        else if (c < 2) spin(prm.dh);
        if (elect_one()) bulk_g2s(dst, src, 2048, bar);
        if (c == 2 && !single) {
          mbar_wait_wd(sb + B_OB, pp);
          if (elect_one()) bulk_g2s(dst + 2048, tok, 8192, full);
        }
        g = 0;
        while (true) {
          mbar_wait_wd(bar, mph);
          mph ^= 1;
          const uint32_t v0 = lds32(dst + chk), v1 = lds32(dst + chk + 1024);
          if (__all_sync(~0u, v0 != ~0u && v1 != ~0u)) break;
          if (elect_one()) {
            mbar_expect(bar, 2048);
            bulk_g2s(dst, src, 2048, bar);
          }
          guard(g);
        }
        mbar_arrive_if(lane == 0, full);
        TRACE(c < 2, m, 3 + 2 * c, gtl());
        TRACE(c < 2, m, 4 + 2 * c, g);
      }
    }
    publish(nslots);
    if (warp == 0) mbar_wait_wd(sb + B_END, 0);
  }
  __syncwarp();
  if (wid != 12 && lane0 == 0) mbar_arrive(sb + B_END);
  cluster_sync();
}
__device__ uint32_t g_xa[NBLK * 10 * 4096];
__device__ uint32_t g_h[NBLK * 24 * 4096];

enum { T_A = 0, T_F1 = 1, T_U = 2, T_D = 3, T_F2 = 4, T_NONE = 7 };
__host__ __device__ constexpr int c_phase(int type, int lb) { return C_O + type * 32 + lb; }
constexpr int C_TICKET = c_phase(5, 0), C_EXIT = C_TICKET + 1, C_USED = C_HALF + 2 * NBLK;
constexpr int G_NST = 7;
constexpr uint32_t GS_RED = G_NST * 32768, GS_BAR = GS_RED + 1088, G_SMEM = GS_BAR + 224;
constexpr uint32_t GB_FULL = GS_BAR, GB_EMPTY = GS_BAR + 64, GB_ORD = GS_BAR + 128, GB_READY = GS_BAR + 144, GB_ACK = GS_BAR + 152, GB_GATE = GS_BAR + 160, GB_SIG = GS_BAR + 176, GB_SACK = GS_BAR + 192,
                   GS_SIG = GS_BAR + 208, GS_COL = GS_BAR + 216;
#define FPL 6
constexpr int NF = 16;
constexpr int G_EARLY = 36;
constexpr int G_LATE = 96, PL = 6, ML = 8, DL = 24, TL = 10;
constexpr int GRC = 112, GRP = 32;
constexpr uint32_t E_UP = 1u << 8, E_HALF = 1u << 28, E_GRP = 1u << 29, E_HAND = 1u << 30, E_EXCL = 1u << 31;

struct GParams {
  __nv_bfloat16* out;
  const uint32_t* x;
  int moff, gd;
  int pend;
  uint8_t perm[G_EARLY], first[9];
  uint8_t need[5][2 * NBLK];
  uint32_t tab[G_EARLY * (PL + ML + DL) + G_LATE * TL];
};
constexpr int EL = PL + ML + DL, TAB_TAIL = G_EARLY * EL;
struct GIter {
  int p, left, period;
  uint32_t e, type, lb, n0, kb0, nkb;
  bool gemm, valid;
  DI GIter(const GParams& prm, int col) {
    if (col < G_EARLY) { p = col * EL; left = PL; period = 0; }
    else { p = TAB_TAIL + (col - G_EARLY) * TL; left = TL; period = prm.pend; }
  }
  DI bool next(const GParams& prm, int col) {
    do {
      if (left == 0) {
        if (++period > prm.pend) return false;
        left = period < prm.pend ? ML : DL;
        if (period > 1 && period < prm.pend) p -= ML;
      }
      e = prm.tab[p++]; left--;
    } while ((e & 7) == T_NONE);
    const int b = (e >> 4) & 15, blk = period < prm.pend ? period - b : b;
    type = e & 7; valid = blk >= 0; lb = (e & 8) * 2 + (blk & 15); n0 = (e >> 9) & 127; kb0 = (e >> 16) & 127;
    gemm = type != T_F1 && type != T_F2;
    nkb = valid ? (e >> 23) & 31 : 0;
    return true;
  }
  DI int id_(int pend) const { return period < pend ? period * 10 + ML - left : 160 + DL - left; }
};

#define GLOG(nt, i, v)
template <int TA> DI void wg_ss128(float* d, uint64_t da, uint64_t db, int sc) {
  asm volatile("{.reg .pred p; setp.ne.b32 p, %66, 0;\n"
               "wgmma.mma_async.sync.aligned.m64n128k16.f32.bf16.bf16 "
               "{%0,%1,%2,%3,%4,%5,%6,%7,%8,%9,%10,%11,%12,%13,%14,%15,%16,%17,%18,%19,%20,%21,%22,%23,%24,%25,%26,%27,%28,%29,%30,%31,"
               "%32,%33,%34,%35,%36,%37,%38,%39,%40,%41,%42,%43,%44,%45,%46,%47,%48,%49,%50,%51,%52,%53,%54,%55,%56,%57,%58,%59,%60,%61,%62,%63}, "
               "%64, %65, p, 1, 1, %67, 1;}"
               : ACC16(d, 0), ACC16(d, 16), ACC16(d, 32), ACC16(d, 48) : "l"(da), "l"(db), "r"(sc), "n"(TA));
}

template <int TA> DI void g_mainloop(float* acc, uint32_t sb, uint32_t hand, uint32_t gate, int nkb, int cw, int lane, uint32_t st, uint32_t ph) {
  const uint64_t da0 = (TA ? mkdesc(SMEM0, 4096, 512, 2) : mkdesc(SMEM0, 128, 1024, 0)) + (cw >> 2) * 512;
  const uint64_t db0 = mkdesc(SMEM0 + 16384, 8192, 1024, 1);
  uint32_t prev = 0;
#pragma unroll 1
  for (int kb = 0; kb < nkb; kb++) {
    mbar_wait(sb + GB_FULL + 8 * st, ph);
    mbar_wait(gate, 1);
    const uint64_t da = da0 + st * 2048, db = db0 + st * 2048;
    wg_fence();
#pragma unroll
    for (int k = 0; k < 4; k++) wg_ss128<TA>(acc, da + k * (TA ? 64 : 16), db + k * 128, 1);
    wg_commit();
    mbar_arrive_if(hand && kb == nkb - 1 && lane == 0, hand);
    wg_wait<1>();
    mbar_arrive_if(kb > 0 && lane == 0, sb + GB_EMPTY + 8 * prev);
    prev = st;
    if (++st == G_NST) { st = 0; ph ^= 1; }
  }
  wg_wait<0>();
  reg_fence<64>(acc);
  mbar_arrive_if(lane == 0, sb + GB_EMPTY + 8 * prev);
}

__global__ void __launch_bounds__(640, 1)
g_kernel(const __grid_constant__ CUtensorMap mapWo, const __grid_constant__ CUtensorMap mapWg, const __grid_constant__ CUtensorMap mapWu,
         const __grid_constant__ CUtensorMap mapWd, const __grid_constant__ GParams prm) {
  const uint32_t sb = smem_base();
  const int wid = __shfl_sync(~0u, threadIdx.x >> 5, 0), lane = threadIdx.x & 31;
  if (threadIdx.x == 0) {
    if ((sb & 0x3FFFF) != SMEM0) __trap();
    {
      uint32_t sm; asm volatile("mov.u32 %0, %%smid;" : "=r"(sm));
      uint32_t* const tk = &g_cnt[C_TICKET * CSTRIDE];
      uint32_t c = atomicAdd(tk, 1);
      if (c < G_EARLY) {
        const uint32_t k = sm < 64 ? (sm >> 1) & 7 : sm < 120 ? 1 + ((sm - 64) >> 1) % 7 : sm < 124 ? 1 + ((sm >> 1) & 1) : 0;
        const uint32_t t = atomicAdd(tk + 1 + k, 1);
        atomicAdd(tk + 9, 1);
        if (t < prm.first[k + 1] - prm.first[k]) c = prm.perm[prm.first[k] + t];
        else {
          uint32_t o = atomicAdd(tk + 10, 1), g = 0;
          while (ld_acq(tk + 9) < G_EARLY) guard(g);
          for (int j = 0; j < 8; j++)
            for (uint32_t i = prm.first[j] + ld_acq(tk + 1 + j); i < prm.first[j + 1]; i++) if (o-- == 0) c = prm.perm[i];
        }
      }
      sts32(sb + GS_COL, c);
    }
    for (int i = 0; i < G_NST; i++) { mbar_init(sb + GB_FULL + 8 * i, 1); mbar_init(sb + GB_EMPTY + 8 * i, 8); }
    mbar_init(sb + GB_ORD, 8); mbar_init(sb + GB_ORD + 8, 8); mbar_init(sb + GB_READY, 1); mbar_init(sb + GB_ACK, 1);
    mbar_init(sb + GB_GATE, 1); mbar_init(sb + GB_GATE + 8, 1);
    mbar_init(sb + GB_SIG, 8); mbar_init(sb + GB_SIG + 8, 8); mbar_init(sb + GB_SACK, 1); mbar_init(sb + GB_SACK + 8, 1);
    fence_async_smem();
  }
  __syncthreads();
  const int col = __shfl_sync(~0u, lds32(sb + GS_COL), 0);

  if (wid >= 16) {
    GIter t(prm, col);
    asm volatile("setmaxnreg.dec.sync.aligned.u32 %0;" ::"n"(GRP));
    uint32_t st = 0, ph = 1, k = 0;
    if (wid == 16) {
      while (t.next(prm, col)) {
        const CUtensorMap* m0 = t.type == T_A ? &mapWo : t.type == T_U ? &mapWg : &mapWd;
        const CUtensorMap* m1 = t.type == T_U ? &mapWu : m0;
        const int c0 = t.type == T_U ? t.n0 * 64 : (t.n0 & 7) * 128, c1 = t.type == T_U ? c0 : c0 + 64;
        if ((t.e & (E_HALF | E_UP)) == E_UP) poll_ge(&g_cnt[c_phase(t.type, t.lb) * CSTRIDE], prm.need[t.type][t.lb]);
#pragma unroll 1
        for (uint32_t kb = t.kb0; kb < t.kb0 + t.nkb; kb++) {
          mbar_wait(sb + GB_EMPTY + 8 * st, ph);
          if (elect_one()) {
            const uint32_t full = sb + GB_FULL + 8 * st, dst = sb + st * 32768;
            mbar_expect(full, (t.e & E_HALF) ? 24576 : 32768);
            tma_2d(dst + 16384, m0, c0, kb * 64, full);
            tma_2d(dst + 24576, m1, c1, kb * 64, full);
          }
          if (++st == G_NST) { st = 0; ph ^= 1; }
        }
      }
    } else if (wid == 17) {
      while (t.next(prm, col)) {
        if (!t.nkb) continue;
        const char* asrc = t.type == T_A ? (const char*)g_oT + (size_t)t.lb * (96 * 16384)
                         : t.type == T_U ? (const char*)g_xa + (size_t)(t.lb & 15) * (10 * 16384) : (const char*)g_h + (size_t)(t.lb & 15) * (24 * 16384);
        const uint32_t up = (t.e & E_HALF) ? (t.e & E_UP) * 32 : 0;
        GLOG(t.id_(prm.pend), 1, gtime());
        mbar_wait(sb + GB_READY, k & 1);
        mbar_arrive_if(lane == 0, sb + GB_ACK);
        k++;
#pragma unroll 1
        for (uint32_t kb = t.kb0; kb < t.kb0 + t.nkb; kb++) {
          mbar_wait(sb + GB_EMPTY + 8 * st, ph);
          if (elect_one()) bulk_g2s(sb + st * 32768 + up, asrc + (size_t)kb * 16384 + up, (t.e & E_HALF) ? 8192 : 16384, sb + GB_FULL + 8 * st);
          if (++st == G_NST) { st = 0; ph ^= 1; }
        }
      }
    } else if (wid == 18) {
      while (t.next(prm, col)) {
        if (!t.nkb) continue;
        const bool lower = t.type == T_A && (t.e & (E_HALF | E_UP)) == E_HALF;
        poll_ge(&g_cnt[(lower ? C_HALF + t.lb : c_phase(t.type, t.lb)) * CSTRIDE], prm.need[t.type][t.lb]);
        fence_async_global();
        GLOG(t.id_(prm.pend), 2, gtime());
        mbar_wait(sb + GB_ACK, (k & 1) ^ 1);
        mbar_arrive_if(lane == 0, sb + GB_READY);
        k++;
      }
    } else {
      uint32_t live = 3, par = 0, g = 0;
      while (live) {
        const bool ev = lane < 2 && ((live >> lane) & 1) && mbar_test(sb + GB_SIG + 8 * lane, (par >> lane) & 1);
        const uint32_t evs = __ballot_sync(~0u, ev);
        if (!evs) { guard(g); __nanosleep(20); continue; }
        const uint32_t msg = ev ? lds32(sb + GS_SIG + 4 * lane) : 0;
        mbar_arrive_if(ev, sb + GB_SACK + 8 * lane);
        mbar_arrive_if(msg >> 31, sb + GB_GATE + 8 * lane);
        if (msg) red_rel(&g_cnt[(msg & 0xffff) * CSTRIDE], (msg >> 16) & 255);
        par ^= evs;
        live &= ~__ballot_sync(~0u, ev && !msg);
        g = 0;
      }
      asm volatile("griddepcontrol.wait;" ::: "memory");
      if (col < 80 && lane < 16) g_mem[(col >> 4) * 2048 + (lane >> 3) * 1024 + 512 + prm.moff + (col & 15) * 8 + (lane & 7)] = make_uint4(~0u, ~0u, ~0u, ~0u);
      uint32_t last = 0;
      if (lane == 0) last = atomicAdd(&g_cnt[C_EXIT * CSTRIDE], 1) == gridDim.x - 1;
      if (__shfl_sync(~0u, last, 0)) {
        g_cnt[C_TICKET * CSTRIDE + lane] = 0;
        for (int i = lane; i < C_USED; i += 32) g_cnt[i * CSTRIDE] = 0;
      }
    }
  } else {
    asm volatile("setmaxnreg.inc.sync.aligned.u32 %0;" ::"n"(GRC));
    const int cw = wid & 7, wk = wid >> 3;
    GIter t(prm, col);
    uint32_t pos = 0, seen = 0, waited = 0;
    uint32_t nsig = 0;
    auto signal = [&](uint32_t msg) {
      mbar_wait(sb + GB_SACK + 8 * wk, (nsig++ & 1) ^ 1);
      if (cw == 0) sts32(sb + GS_SIG + 4 * wk, msg);
      __syncwarp();
      mbar_arrive_if(lane == 0, sb + GB_SIG + 8 * wk);
    };
    if (col < G_EARLY) {
      spin(prm.gd);
#pragma unroll 1
      for (int rg = 96 + col * 2 + wk; rg < 256; rg += 2 * G_EARLY) {
        uint32_t a[10];
        const uint32_t* src = prm.x + (size_t)(rg * 8 + (lane >> 2)) * (DM / 2) + cw * 40 + (lane & 3);
#pragma unroll
        for (int i = 0; i < 10; i++) a[i] = __ldg(src + i * 4);
        first_ln(a, rg, sb + GS_RED + wk * 512, cw, lane, 1 + wk);
        signal((C_XN + (rg >> 4)) | ((XN_TARGET / NF) << 16));
        bar_sync(1 + wk, 256);
      }
    }
    while (t.next(prm, col)) {
      const uint32_t pos0 = pos;
      pos = (pos + t.nkb) % (2 * G_NST);
      if (((t.e >> 29) & 1) != wk) { seen += (t.e >> 30) & 1; continue; }
      const uint32_t type = t.type, blk = t.lb & 15, layer = t.lb >> 4, n0 = t.n0;
      if (cw == 0 && t.valid) GLOG(t.id_(prm.pend), 0, 0x80000000u | type | (t.lb << 3) | (n0 << 8) | (t.nkb << 16));
      if (!t.gemm) {
        if (!t.valid) continue;
        const int rg = blk * 16 + n0;
        float4 v[5];
        const int off = (n0 * 40 + cw * 5) * 32 + lane, npl = t.kb0;
        const uint2* src = acc_planes(t.lb, type == T_F2) + off;
        if (cw == 0) {
          poll_ge(&g_cnt[c_phase(type, t.lb) * CSTRIDE], prm.need[type][t.lb]);
          mbar_arrive_if((t.e & E_EXCL) && lane == 0, sb + GB_GATE + 8 * wk);
          GLOG(t.id_(prm.pend), 2, gtime()); GLOG(t.id_(prm.pend), 3, gtime());
        }
        bar_sync(1 + wk, 256);
        {
          const uint32_t eye = (lane >> 3) == (lane & 3) ? ((lane & 4) ? 0x3f800000u : 0x00003f80u) : 0u;
#pragma unroll
          for (int i = 0; i < 5; i++) v[i] = make_float4(0.f, 0.f, 0.f, 0.f);
#pragma unroll 1
          for (int p0 = 0; p0 < npl; p0 += FPL) {
            uint32_t r[FPL / 2][5][4];
#pragma unroll
            for (int p = 0; p < FPL; p++)
#pragma unroll
              for (int i = 0; i < 5; i++) {
                const uint2 w = p0 + p < npl ? __ldcg(src + (size_t)(p0 + p) * PLANE + i * 32) : make_uint2(0, 0);
                r[p >> 1][i][(p & 1) * 2] = w.x; r[p >> 1][i][(p & 1) * 2 + 1] = w.y;
              }
#pragma unroll
            for (int p = 0; p < FPL / 2; p++) {
              if (p0 + 2 * p >= npl) break;
              if (t.e & E_EXCL) {
#pragma unroll
                for (int i = 0; i < 5; i++) mma16816(&v[i].x, r[p][i], eye, eye);
              } else {
#pragma unroll
                for (int i = 0; i < 5; i++) {
                  const uint32_t* w = r[p][i];
                  v[i].x += blo(w[0]) + blo(w[2]); v[i].y += bhi(w[0]) + bhi(w[2]); v[i].z += blo(w[1]) + blo(w[3]); v[i].w += bhi(w[1]) + bhi(w[3]);
                }
              }
            }
          }
        }
        if (type == T_F2 && layer == 1) {
          uint2* dst = (uint2*)prm.out + (size_t)(rg * 8 + (lane >> 2)) * (DM / 4) + cw * 20 + (lane & 1) * 2 + ((lane >> 1) & 1);
#pragma unroll
          for (int i = 0; i < 5; i++) {
            const uint32_t a = pack2(v[i].x, v[i].y), b = pack2(v[i].z, v[i].w);
            const uint32_t o = __shfl_xor_sync(~0u, (lane & 1) ? a : b, 1);
            dst[i * 4] = (lane & 1) ? make_uint2(o, b) : make_uint2(a, o);
          }
        } else {
          uint2* nx = (type == T_F1 ? acc_planes(t.lb, 1) : acc_planes(NBLK + blk, 0)) + off;
#pragma unroll
          for (int i = 0; i < 5; i++) {
            const uint2 w = make_uint2(pack2(v[i].x, v[i].y), pack2(v[i].z, v[i].w));
            nx[i * 32] = w;
            v[i] = make_float4(blo(w.x), bhi(w.x), blo(w.y), bhi(w.y));
          }
          float mean, rstd;
          ln_stats(v, sb + GS_RED + wk * 512, cw, lane, 1 + wk, mean, rstd);
          if (type == T_F2) store_img<4, 2048>(xn_row_group(1, rg) + lane, v, cw, mean, rstd);
          else store_img<3, 4096>(g_xa + (size_t)(blk * 10 * 4096 + n0 * 256) + lane, v, cw, mean, rstd);
        }
      } else {
        float acc[64];
#pragma unroll
        for (int j = 0; j < 64; j++) acc[j] = 0.f;
        if (waited != seen) { mbar_wait(sb + GB_ORD + 8 * (wk ^ 1), waited & 1); waited++; }
        const uint32_t hand = (t.e & E_HAND) ? sb + GB_ORD + 8 * wk : 0;
        if (!t.valid) { mbar_arrive_if(hand && lane == 0, hand); continue; }
        if (cw == 0) GLOG(t.id_(prm.pend), 3, gtime());
        const uint32_t ph = pos0 >= G_NST, st = pos0 - ph * G_NST, early = (t.e & E_EXCL) ? 0 : hand;
        const bool idle = (t.e & E_HALF) && ((t.e >> 8) & 1) != (cw >> 2);
        if (idle) {
          uint32_t s2 = st, p2 = ph;
#pragma unroll 1
          for (uint32_t kb = 0; kb < t.nkb; kb++) {
            mbar_wait(sb + GB_FULL + 8 * s2, p2);
            mbar_arrive_if(lane == 0, sb + GB_EMPTY + 8 * s2);
            if (++s2 == G_NST) { s2 = 0; p2 ^= 1; }
          }
          mbar_arrive_if(early && lane == 0, early);
        } else if (type == T_A) g_mainloop<1>(acc, sb, early, sb + GB_GATE + 8 * (wk ^ 1), t.nkb, cw, lane, st, ph);
        else g_mainloop<0>(acc, sb, early, sb + GB_GATE + 8 * (wk ^ 1), t.nkb, cw, lane, st, ph);
        if (cw == 0) GLOG(t.id_(prm.pend), 4, gtime());
        if (idle) {
        } else if (type == T_U) {
          uint32_t* dst = g_h + (size_t)((blk * 24 + n0) * 4096 + cw * 512) + lane;
#pragma unroll
          for (int j = 0; j < 8; j++) {
            float h[4];
#pragma unroll
            for (int e = 0; e < 4; e++) {
              float th;
              asm("tanh.approx.f32 %0, %1;" : "=f"(th) : "f"(0.5f * acc[4 * j + e]));
              h[e] = acc[32 + 4 * j + e] * fmaf(th, 0.5f, 0.5f);
            }
            dst[j * 32] = pack2(h[0], h[1]);
            dst[j * 32 + 256] = pack2(h[2], h[3]);
          }
        } else {
          uint2* dst = acc_planes(t.lb, type == T_D) + (size_t)((1 + (n0 >> 3)) * PLANE + (2 * cw * 40 + (n0 & 7) * 8) * 32) + lane;
#pragma unroll
          for (int j = 0; j < 16; j++) {
            const float* a = acc + (j >> 1) * 8 + (j & 1) * 2;
            dst[(j >> 1) * 32 + (j & 1) * 1280] = make_uint2(pack2(a[0], a[1]), pack2(a[4], a[5]));
          }
        }
        mbar_arrive_if(hand != early && lane == 0, hand);
      }
      if (cw == 0) GLOG(t.id_(prm.pend), 5, gtime());
      if (cw == 0) GLOG(t.id_(prm.pend), 6, gtime());
      if (type == T_F2 && layer == 1) mbar_arrive_if((t.e & E_EXCL) && cw == 0 && lane == 0, sb + GB_GATE + 8 * wk);
      else
        signal((type != T_F2 ? c_phase(type + 1, t.lb) | (1 << 16) : (C_XN + NBLK + blk) | ((XN_TARGET / NF) << 16)) | (t.gemm ? 0 : t.e & E_EXCL));
    }
    signal(0);
  }
}

typedef CUresult (*EncodeFn)(CUtensorMap*, CUtensorMapDataType, cuuint32_t, void*, const cuuint64_t*, const cuuint64_t*, const cuuint32_t*,
                             const cuuint32_t*, CUtensorMapInterleave, CUtensorMapSwizzle, CUtensorMapL2promotion, CUtensorMapFloatOOBfill);
static CUtensorMap make_map(EncodeFn fn, const void* p, uint64_t inner, uint64_t outer, uint32_t bi, uint32_t bo) {
  CUtensorMap m;
  cuuint64_t dims[2] = {inner, outer}, str[1] = {inner * 2};
  cuuint32_t box[2] = {bi, bo}, es[2] = {1, 1};
  fn(&m, CU_TENSOR_MAP_DATA_TYPE_BFLOAT16, 2, (void*)p, dims, str, box, es, CU_TENSOR_MAP_INTERLEAVE_NONE, CU_TENSOR_MAP_SWIZZLE_128B,
     CU_TENSOR_MAP_L2_PROMOTION_L2_256B, CU_TENSOR_MAP_FLOAT_OOB_FILL_NONE);
  return m;
}
struct Tune {
  int lag = 11, excl = 7, gonly = 0, xl = 1, ronly = 0, pn = 30;
  int da = 100, db = 350, dc = 650, dd = 650, d2 = 2000, p1 = 400, p2 = 800;
  int ea = 60, eb = 310, ec = 550, ed = 550, e2 = 2200, q1 = 200, q2 = 400, d3 = 60, moff = 192, ds = 400, dh = 60, pa = 0, pb = 0, pc = 0, pd = 0, pe = 0, pf = 0, pg = 0, ph = 0, hold = 1, wpf = 4, gd = 22000;
};
static void fill_r(RParams& p, const Tune& t, int lag, int n0, int n1) {
  r_fill_desc(p);
  p.nslots = 0; p.d3 = t.d3; p.pn = t.pn; p.moff = t.moff; p.ds = t.ds; p.dh = t.dh;
  for (int c = 0; c < 5; c++) { p.d2[c] = t.d2 + (c == 0 ? 0 : c < 3 ? t.p1 : t.p2); p.d2[5 + c] = t.e2 + (c == 0 ? 0 : c < 3 ? t.q1 : t.q2); }
  const int d1[8] = {t.da, t.db, t.dc, t.dd, t.ea, t.eb, t.ec, t.ed};
  for (int i = 0; i < 8; i++) p.d1[i] = d1[i];
  int last[2] = {0, 0}, n = 0;
  for (int s0 = 0; s0 < NSEG + lag; s0++)
    for (int l = 0; l < 2; l++) {
      const int s = l ? s0 - lag : s0;
      if (s < 0 || s >= NSEG) continue;
      if (n >= n0 && n < n1) { p.slot[p.nslots] = s | (l << 6) | (last[l] << 8) | (((s & 3) == 3 ? C_O + l * NBLK + s / 4 : s == (l ? 61 : 1) ? C_HALF + l * NBLK + s / 4 : 0) << 16); last[l] = ++p.nslots; }
      n++;
    }
  for (int i = 0; i + 1 < p.nslots; i++) if (((p.slot[i] ^ p.slot[i + 1]) >> 6) & 1) p.slot[i] |= 128;
}
static uint32_t g_entry(int grp, int type, int layer, int blk, int i, int ks) {
  int n0 = i, kb0 = 0, kb1 = type == T_U ? 10 : 0;
  if (type == T_F1 || type == T_F2) kb0 = kb1 = ks + 1;
  if (type == T_A || type == T_D) {
    const int KB = type == T_A ? 96 : 24, sp = i / 5;
    n0 = i % 5 | (sp << 3); kb0 = sp * KB / ks; kb1 = (sp + 1) * KB / ks;
  }
  return type | (layer << 3) | (blk << 4) | (n0 << 9) | (kb0 << 16) | ((kb1 - kb0) << 23) | (grp ? E_GRP : 0);
}
static bool g_is_gemm(uint32_t e) { return (e & 7) == T_A || (e & 7) == T_U || (e & 7) == T_D; }
static void g_handover(uint32_t* e, int len) {
  uint32_t next = 0;
  for (int i = len - 1; i >= 0; i--)
    if (g_is_gemm(e[i])) { if ((e[i] & E_GRP) != next) e[i] |= E_HAND; next = e[i] & E_GRP; }
}
struct GList {
  GParams& g; uint32_t* tab; int ncol, stride, len, n[G_LATE], load[G_LATE], grp[G_LATE];
  GList(GParams& g_, uint32_t* t, int nc, int st, int l) : g(g_), tab(t), ncol(nc), stride(st), len(l) { for (int c = 0; c < nc; c++) { n[c] = load[c] = 0; grp[c] = 1; } }
  void add(int type, int lb, int ks, int c0, int c1, uint32_t flags = 0, int i0 = 0, int i1 = 999, int step = 1) {
    const int half = (flags & E_HALF) != 0, ln = type == T_F1 || type == T_F2;
    const int cnt = (type == T_U ? 24 : ln ? NF : 5 * ks) << half;
    if (type < T_F2) g.need[type + 1][lb] = cnt;
    int used[G_LATE] = {0};
    for (int i = i0; i < cnt && i < i1; i += step) {
      int best = c0;
      for (int c = c0; c < c1; c++) if (used[c] < used[best] || (used[c] == used[best] && load[c] < load[best])) best = c;
      used[best]++;
      if (!ln) grp[best] ^= 1;
      const uint32_t e = g_entry(grp[best], type, lb >> 4, lb & 15, i >> half, ks) | flags | (ln ? E_EXCL : 0) | ((i & half) ? E_UP : 0);
      if (n[best] >= len) abort();
      tab[best * stride + n[best]++] = e;
      load[best] += (((e >> 23) & 31) >> half) + 2;
    }
  }
  void finish() { for (int c = 0; c < ncol; c++) g_handover(tab + c * stride, len); }
};
static void fill_g(GParams& g, const Tune& t, void* out) {
  g.out = (__nv_bfloat16*)out;  g.pend = NBLK - 1;
  for (int b = 0; b < 2 * NBLK; b++) {
    g.need[T_A][b] = 96; g.need[T_F1][b] = 20; g.need[T_U][b] = NF; g.need[T_D][b] = 32; g.need[T_F2][b] = 15;
  }
  {
    const uint8_t perm[G_EARLY] = {0, 1, 2, 3, 16, 17, 18, 19, 34, 35, 4, 20, 21, 15, 22, 23, 5, 6, 7, 8, 9, 24, 25, 26, 10, 11, 12, 13, 14, 27, 28, 29, 30, 31, 32, 33};
    const uint8_t first[9] = {0, 10, 13, 16, 20, 24, 28, 32, 36};
    const int* pk = &t.pa;
    for (int i = 0; i < G_EARLY; i++) g.perm[i] = t.pa ? (pk[i / 5] >> (6 * (i % 5))) & 63 : perm[i];
    for (int i = 0; i < 9; i++) g.first[i] = first[i];
  }
  for (uint32_t& e : g.tab) e = T_NONE;
  GList pr(g, g.tab, G_EARLY, EL, PL);
  pr.add(T_A, 0, 7, 1, 36, E_HALF, 0, 999, 2); pr.add(T_A, 0, 7, 1, 36, E_HALF, 1, 999, 2); pr.add(T_F1, 0, 7, 20, 36); pr.add(T_U, 0, 0, 12, 36);
  pr.add(T_D, 0, 3, 20, 36); pr.add(T_F2, 0, 3, 20, 36);
  pr.finish();
  const int d = 3;
  const uint32_t xa = (t.excl & 1) ? E_EXCL : 0, xu = (t.excl & 2) ? E_EXCL : 0, xd = (t.excl & 4) ? E_EXCL : 0;
  for (int c = 0; c < G_EARLY; c++) {
    uint32_t* e = g.tab + c * EL + PL;
    if (c < 20) {
      *e++ = g_entry(0, T_A, 0, 0, c, 4) | xa;
      if (c < NF) *e++ = g_entry(0, T_F1, 0, 0, c, 4) | ((t.xl & 1) ? E_EXCL : 0);
      *e++ = g_entry(1, T_A, 1, d, c, 4);
      if (c >= 20 - NF) *e++ = g_entry(1, T_F1, 1, d, c - (20 - NF), 4);
    } else {
      const int j = c - 20;
      const uint32_t hf = E_HALF | ((j & 1) ? E_UP : 0);
      *e++ = g_entry(0, T_U, 0, 0, j, 0);
      *e++ = g_entry(1, T_U, 0, 0, 16 + j / 2, 0) | hf | xu;
      *e++ = g_entry(0, T_U, 1, d + 1, 16 + j / 2, 0) | hf;
      if (j < 15) *e++ = g_entry(1, T_D, 0, 0, j, 3) | xd;
      *e++ = g_entry(1, T_F2, 0, 0, j, 3) | ((t.xl & 2) ? E_EXCL : 0);
      if (j < 15) *e++ = g_entry(0, T_D, 1, d + 2, j, 3);
      *e++ = g_entry(0, T_U, 1, d + 1, j, 0);
      *e++ = g_entry(1, T_F2, 1, d + 2, j, 3);
    }
    g_handover(g.tab + c * EL + PL, ML);
  }
  GList dr(g, g.tab + PL + ML, G_EARLY, EL, DL);
  GList tl(g, g.tab + TAB_TAIL, G_LATE, TL, TL);
  const int L1 = NBLK;
  auto ufull = [&](int lb) { dr.add(T_U, lb, 0, 20, 36, 0, 0, 16); g.need[T_D][lb] = 32; };
  auto uhalf = [&](int lb) { dr.add(T_U, lb, 0, 20, 36, E_HALF, 32); g.need[T_D][lb] = 32; };
  dr.add(T_A, 15, 4, 0, 20, E_EXCL);
  dr.add(T_F1, 15, 4, 0, 16);
  dr.add(T_U, 15, 0, 12, 36, E_EXCL);
  dr.add(T_A, L1 + 12, 4, 0, 20); dr.add(T_F1, L1 + 12, 4, 0, 16);
  uhalf(L1 + 11);
  dr.add(T_D, 15, 3, 20, 36, E_EXCL); dr.add(T_F2, 15, 3, 20, 36);
  dr.add(T_A, L1 + 13, 4, 0, 20); dr.add(T_F1, L1 + 13, 4, 0, 20);
  ufull(L1 + 11);
  dr.add(T_D, L1 + 10, 3, 20, 36);
  ufull(L1 + 12); uhalf(L1 + 12);
  dr.add(T_A, L1 + 14, 4, 0, 20);
  dr.add(T_A, L1 + 15, 7, 0, 35, E_HALF, 0, 999, 2); dr.add(T_A, L1 + 15, 7, 0, 35, E_HALF | E_EXCL, 1, 999, 2);
  dr.add(T_F1, L1 + 14, 4, 0, 16);
  dr.add(T_F1, L1 + 15, 7, 20, 36);
  dr.add(T_F2, L1 + 10, 3, 0, 16); dr.add(T_F2, L1 + 11, 3, 4, 20); dr.add(T_F2, L1 + 12, 3, 0, 20);
  dr.add(T_D, L1 + 13, 3, 20, 36, (t.hold & 1) ? E_UP : 0); dr.add(T_F2, L1 + 13, 3, 20, 36);
  dr.finish();
  tl.add(T_D, L1 + 11, 3, 0, 24); tl.add(T_D, L1 + 12, 3, 48, G_LATE);
  tl.add(T_U, L1 + 14, 0, 0, 24); tl.add(T_U, L1 + 13, 0, 24, 48);
  tl.add(T_D, L1 + 14, 4, 0, 48, E_HALF);
  tl.add(T_F2, L1 + 14, 4, 0, 48);
  tl.add(T_U, L1 + 15, 0, 48, G_LATE, E_HALF);
  tl.add(T_D, L1 + 15, 4, 48, G_LATE, E_HALF);
  tl.add(T_F2, L1 + 15, 4, 48, G_LATE);
  tl.finish();
}
static void launch_all(void* const* d_in, void* d_out, const Tune& t, cudaStream_t st) {
  static EncodeFn fn = nullptr;
  if (!fn) {
    void* f = nullptr;
    cudaDriverEntryPointQueryResult qr;
    cudaGetDriverEntryPoint("cuTensorMapEncodeTiled", &f, cudaEnableDefault, &qr);
    fn = (EncodeFn)f;
    cudaFuncSetAttribute(r_kernel, cudaFuncAttributeMaxDynamicSharedMemorySize, R_SMEM);
    cudaFuncSetAttribute(g_kernel, cudaFuncAttributeMaxDynamicSharedMemorySize, G_SMEM);
  }
  const CUtensorMap mq = make_map(fn, d_in[2], HD, DM, 64, 128), mk = make_map(fn, d_in[3], HD, DM, 64, 128), mv = make_map(fn, d_in[4], HD, DM, 64, 128),
                    mo = make_map(fn, d_in[5], DM, HD, 64, 64), mg = make_map(fn, d_in[8], FF, DM, 64, 64), mu = make_map(fn, d_in[9], FF, DM, 64, 64),
                    md = make_map(fn, d_in[10], DM, FF, 64, 64);
  auto launch_r = [&](int lag, int n0, int n1) {
    RParams p;
    fill_r(p, t, lag, n0, n1);
    for (int i = 0; i < 4; i++) p.w[i] = (const char*)d_in[2 + i];
    p.mem0 = (const uint4*)d_in[1]; p.x = (const uint32_t*)d_in[0]; p.pf = t.wpf;
    cudaLaunchConfig_t cfg = {};
    cfg.gridDim = dim3(3, NH); cfg.blockDim = dim3(512); cfg.dynamicSmemBytes = R_SMEM; cfg.stream = st;
    cudaLaunchAttribute at[1];
    at[0].id = cudaLaunchAttributeClusterDimension; at[0].val.clusterDim.x = 3; at[0].val.clusterDim.y = 1; at[0].val.clusterDim.z = 1;
    cfg.attrs = at; cfg.numAttrs = 1;
    cudaLaunchKernelEx(&cfg, r_kernel, mq, mk, mv, mo, p);
  };
  auto launch_g = [&](const GParams& g, bool pdl) {
    cudaLaunchConfig_t cfg = {};
    cfg.gridDim = dim3(132); cfg.blockDim = dim3(640); cfg.dynamicSmemBytes = G_SMEM; cfg.stream = st;
    cudaLaunchAttribute at[2];
    at[0].id = cudaLaunchAttributeProgrammaticStreamSerialization; at[0].val.programmaticStreamSerializationAllowed = 1;
    cfg.attrs = at; cfg.numAttrs = pdl ? 1 : 0;
    cudaLaunchKernelEx(&cfg, g_kernel, mo, mg, mu, md, g);
  };
  GParams g;
  fill_g(g, t, d_out);
  g.moff = t.moff; g.gd = t.gd; g.x = (const uint32_t*)d_in[0];
  launch_r(t.lag, 0, 2 * NSEG);
  launch_g(g, true);
}

extern "C" void kernel_launch(void* const* d_in, const int* in_sizes, int n_in, void* d_out, int out_size) {
  launch_all(d_in, d_out, Tune(), cudaStreamPerThread);
}
```

```cpp
#include <cuda_runtime.h>
#include <cuda_bf16.h>
#include <cuda.h>
#include <stdint.h>
#include <stdlib.h>

constexpr int SEQ = 2048, DM = 640, NH = 32, DH = 192, HD = NH * DH, FF = 1536;
constexpr int NSEG = 64, SEGL = 32, NMEM = 8;
constexpr int NBLK = 16;

#define DI __device__ __forceinline__

DI uint32_t smem_base() {
  extern __shared__ __align__(1024) unsigned char smem_raw[];
  uint32_t a;
  asm volatile("{.reg .u64 t; cvta.to.shared.u64 t, %1; cvt.u32.u64 %0, t;}" : "=r"(a) : "l"(smem_raw));
  return a;
}
DI uint32_t mapa(uint32_t a, uint32_t r) {
  uint32_t o;
  asm("mapa.shared::cluster.u32 %0, %1, %2;" : "=r"(o) : "r"(a), "r"(r));
  return o;
}
DI void mbar_init(uint32_t bar, uint32_t cnt) { asm volatile("mbarrier.init.shared::cta.b64 [%0], %1;" ::"r"(bar), "r"(cnt) : "memory"); }
DI void mbar_arrive(uint32_t bar) { asm volatile("mbarrier.arrive.shared::cta.b64 _, [%0];" ::"r"(bar) : "memory"); }
DI void mbar_arrive_remote(uint32_t bar) { asm volatile("mbarrier.arrive.release.cluster.shared::cluster.b64 _, [%0];" ::"r"(bar) : "memory"); }
DI void mbar_expect(uint32_t bar, uint32_t tx) { asm volatile("mbarrier.arrive.expect_tx.shared::cta.b64 _, [%0], %1;" ::"r"(bar), "r"(tx) : "memory"); }
DI void mbar_arrive_if(bool p, uint32_t bar) { asm volatile("{.reg .pred p; setp.ne.b32 p, %1, 0; @p mbarrier.arrive.shared::cta.b64 _, [%0];}" ::"r"(bar), "r"((int)p) : "memory"); }
DI void mbar_arrive_if(bool p, uint32_t bar, uint32_t cnt) {
  asm volatile("{.reg .pred p; setp.ne.b32 p, %1, 0; @p mbarrier.arrive.shared::cta.b64 _, [%0], %2;}" ::"r"(bar), "r"((int)p), "r"(cnt) : "memory");
}
DI void mbar_expect_if(bool p, uint32_t bar, uint32_t tx) {
  asm volatile("{.reg .pred p; setp.ne.b32 p, %2, 0; @p mbarrier.arrive.expect_tx.shared::cta.b64 _, [%0], %1;}" ::"r"(bar), "r"(tx), "r"((int)p) : "memory");
}
DI bool mbar_test(uint32_t bar, uint32_t par) {
  uint32_t ok;
  asm volatile("{.reg .pred p; mbarrier.test_wait.parity.shared::cta.b64 p, [%1], %2; selp.u32 %0, 1, 0, p;}" : "=r"(ok) : "r"(bar), "r"(par) : "memory");
  return ok;
}
DI void mbar_wait(uint32_t bar, uint32_t par) {
  asm volatile(
      "{.reg .pred p;\n"
      "LOOP:\n"
      "mbarrier.try_wait.parity.shared::cta.b64 p, [%0], %1;\n"
      "@!p bra LOOP;\n}" ::"r"(bar), "r"(par) : "memory");
}
DI void mbar_wait_wd(uint32_t bar, uint32_t par) {
  asm volatile(
      "{.reg .pred p; .reg .u32 c;\n"
      "mov.u32 c, 0;\n"
      "LOOP:\n"
      "mbarrier.try_wait.parity.shared::cta.b64 p, [%0], %1;\n"
      "@p bra DONE;\n"
      "add.u32 c, c, 1;\n"
      "setp.lt.u32 p, c, 4000000;\n"
      "@p bra LOOP;\n"
      "trap;\n"
      "DONE:\n}" ::"r"(bar), "r"(par) : "memory");
}
DI void fence_async_smem() { asm volatile("fence.proxy.async.shared::cta;" ::: "memory"); }
DI void fence_async_global() { asm volatile("fence.proxy.async.global;" ::: "memory"); }
DI void bar_sync(int id, int n) { asm volatile("bar.sync %0, %1;" ::"r"(id), "r"(n) : "memory"); }
DI void bar_arrive(int id, int n) { asm volatile("bar.arrive %0, %1;" ::"r"(id), "r"(n) : "memory"); }
DI void cluster_sync() { asm volatile("barrier.cluster.arrive.release.aligned; barrier.cluster.wait.acquire.aligned;" ::: "memory"); }
DI bool elect_one() {
  uint32_t p;
  asm volatile("{.reg .pred p; elect.sync _|p, 0xffffffff; selp.u32 %0, 1, 0, p;}" : "=r"(p));
  return p;
}
DI void bulk_g2s(uint32_t dst, const void* src, uint32_t bytes, uint32_t bar) {
  asm volatile("cp.async.bulk.shared::cluster.global.mbarrier::complete_tx::bytes [%0], [%1], %2, [%3];" ::"r"(dst), "l"(src), "r"(bytes), "r"(bar) : "memory");
}
DI void bulk_g2s_mc(uint32_t dst, const void* src, uint32_t bytes, uint32_t bar, uint16_t mask) {
  asm volatile("cp.async.bulk.shared::cluster.global.mbarrier::complete_tx::bytes.multicast::cluster [%0], [%1], %2, [%3], %4;" ::"r"(dst), "l"(src), "r"(bytes), "r"(bar), "h"(mask) : "memory");
}
DI void bulk_s2s(uint32_t dst, uint32_t src, uint32_t bytes, uint32_t bar) {
  asm volatile("cp.async.bulk.shared::cluster.shared::cta.mbarrier::complete_tx::bytes [%0], [%1], %2, [%3];" ::"r"(dst), "r"(src), "r"(bytes), "r"(bar) : "memory");
}
DI void tma_2d(uint32_t dst, const CUtensorMap* map, int c0, int c1, uint32_t bar) {
  asm volatile("cp.async.bulk.tensor.2d.shared::cluster.global.mbarrier::complete_tx::bytes [%0], [%1, {%3, %4}], [%2];" ::"r"(dst), "l"(map), "r"(bar), "r"(c0), "r"(c1) : "memory");
}
DI void tma_pf(const CUtensorMap* map, int c0, int c1) {
  asm volatile("cp.async.bulk.prefetch.tensor.2d.L2.global [%0, {%1, %2}];" ::"l"(map), "r"(c0), "r"(c1) : "memory");
}
DI void st_async4(uint32_t a, uint32_t x, uint32_t y, uint32_t z, uint32_t w, uint32_t bar) {
  asm volatile("st.async.shared::cluster.mbarrier::complete_tx::bytes.v4.b32 [%0], {%1,%2,%3,%4}, [%5];" ::"r"(a), "r"(x), "r"(y), "r"(z), "r"(w), "r"(bar) : "memory");
}
DI void st_async2(uint32_t a, uint32_t x, uint32_t y, uint32_t bar) {
  asm volatile("st.async.shared::cluster.mbarrier::complete_tx::bytes.v2.b32 [%0], {%1,%2}, [%3];" ::"r"(a), "r"(x), "r"(y), "r"(bar) : "memory");
}
DI void st_async1(uint32_t a, uint32_t x, uint32_t bar) {
  asm volatile("st.async.shared::cluster.mbarrier::complete_tx::bytes.b32 [%0], %1, [%2];" ::"r"(a), "r"(x), "r"(bar) : "memory");
}
DI void sts32(uint32_t a, uint32_t x) { asm volatile("st.shared.b32 [%0], %1;" ::"r"(a), "r"(x) : "memory"); }
DI void sts128(uint32_t a, uint4 v) { asm volatile("st.shared.v4.b32 [%0], {%1,%2,%3,%4};" ::"r"(a), "r"(v.x), "r"(v.y), "r"(v.z), "r"(v.w) : "memory"); }
DI uint32_t lds32(uint32_t a) { uint32_t v; asm volatile("ld.shared.b32 %0, [%1];" : "=r"(v) : "r"(a) : "memory"); return v; }
DI uint2 lds64(uint32_t a) { uint2 v; asm volatile("ld.shared.v2.b32 {%0,%1}, [%2];" : "=r"(v.x), "=r"(v.y) : "r"(a) : "memory"); return v; }
DI uint4 lds128(uint32_t a) { uint4 v; asm volatile("ld.shared.v4.b32 {%0,%1,%2,%3}, [%4];" : "=r"(v.x), "=r"(v.y), "=r"(v.z), "=r"(v.w) : "r"(a) : "memory"); return v; }
DI void stsm4(uint32_t a, uint32_t r0, uint32_t r1, uint32_t r2, uint32_t r3) {
  asm volatile("stmatrix.sync.aligned.m8n8.x4.shared.b16 [%0], {%1,%2,%3,%4};" ::"r"(a), "r"(r0), "r"(r1), "r"(r2), "r"(r3) : "memory");
}
DI void stsm2(uint32_t a, uint32_t r0, uint32_t r1) {
  asm volatile("stmatrix.sync.aligned.m8n8.x2.shared.b16 [%0], {%1,%2};" ::"r"(a), "r"(r0), "r"(r1) : "memory");
}
DI uint32_t movm(uint32_t a) { uint32_t d; asm volatile("movmatrix.sync.aligned.m8n8.trans.b16 %0, %1;" : "=r"(d) : "r"(a)); return d; }
DI uint32_t pack2(float lo, float hi) { uint32_t d; asm("cvt.rn.bf16x2.f32 %0, %1, %2;" : "=r"(d) : "f"(hi), "f"(lo)); return d; }
DI uint4 ld_rlx4(const void* p) {
  uint4 v;
  asm volatile("ld.relaxed.gpu.global.v4.u32 {%0,%1,%2,%3}, [%4];" : "=r"(v.x), "=r"(v.y), "=r"(v.z), "=r"(v.w) : "l"(p) : "memory");
  return v;
}
DI void st_rlx4(void* p, uint32_t x, uint32_t y, uint32_t z, uint32_t w) {
  asm volatile("st.relaxed.gpu.global.v4.u32 [%0], {%1,%2,%3,%4};" ::"l"(p), "r"(x), "r"(y), "r"(z), "r"(w) : "memory");
}
DI void st_rlx1(void* p, uint32_t x) { asm volatile("st.relaxed.gpu.global.u32 [%0], %1;" ::"l"(p), "r"(x) : "memory"); }
DI uint32_t ld_acq(const uint32_t* p) { uint32_t v; asm volatile("ld.acquire.gpu.global.u32 %0, [%1];" : "=r"(v) : "l"(p) : "memory"); return v; }
DI uint32_t ld_rlx(const uint32_t* p) { uint32_t v; asm volatile("ld.relaxed.gpu.global.u32 %0, [%1];" : "=r"(v) : "l"(p) : "memory"); return v; }
DI void red_rel(uint32_t* p, uint32_t v) { asm volatile("red.release.gpu.global.add.u32 [%0], %1;" ::"l"(p), "r"(v) : "memory"); }
DI void guard(uint32_t& g) { asm volatile("{.reg .pred p; add.u32 %0, %0, 1; setp.gt.u32 p, %0, 8000000; @p trap;}" : "+r"(g)); }
DI void poll_ge(const uint32_t* p, uint32_t target) {
  asm volatile(
      "{.reg .pred p; .reg .u32 v;\n"
      "LOOP:\n"
      "ld.acquire.gpu.global.u32 v, [%0];\n"
      "setp.lt.u32 p, v, %1;\n"
      "vote.sync.any.pred p, p, 0xffffffff;\n"
      "@p bra.uni LOOP;\n}" ::"l"(p), "r"(target) : "memory");
}
DI float ex2(float x) { float y; asm("ex2.approx.ftz.f32 %0, %1;" : "=f"(y) : "f"(x)); return y; }

DI void wg_fence() { asm volatile("wgmma.fence.sync.aligned;" ::: "memory"); }
DI void wg_commit() { asm volatile("wgmma.commit_group.sync.aligned;" ::: "memory"); }
template <int N> DI void wg_wait() { asm volatile("wgmma.wait_group.sync.aligned %0;" ::"n"(N) : "memory"); }
template <int N> DI void reg_fence(float* d) {
#pragma unroll
  for (int i = 0; i < N; i++) asm volatile("" : "+f"(d[i])::"memory");
}
__host__ __device__ constexpr uint64_t mkdesc(uint32_t addr, uint32_t lbo, uint32_t sbo, uint32_t sw) {
  return (uint64_t)((addr & 0x3FFFF) >> 4) | ((uint64_t)(lbo >> 4) << 16) | ((uint64_t)(sbo >> 4) << 32) | ((uint64_t)sw << 62);
}

#define ACC4(d, o) "+f"(d[o]), "+f"(d[o + 1]), "+f"(d[o + 2]), "+f"(d[o + 3])
#define ACC16(d, o) ACC4(d, o), ACC4(d, o + 4), ACC4(d, o + 8), ACC4(d, o + 12)
#define ACC20(d) ACC16(d, 0), ACC4(d, 16)

template <int TA, int TB> DI void wg_ss40(float* d, uint64_t da, uint64_t db, int sc) {
  asm volatile("{.reg .pred p; setp.ne.b32 p, %22, 0;\n"
               "wgmma.mma_async.sync.aligned.m64n40k16.f32.bf16.bf16 {%0,%1,%2,%3,%4,%5,%6,%7,%8,%9,%10,%11,%12,%13,%14,%15,%16,%17,%18,%19}, %20, %21, p, 1, 1, %23, %24;}"
               : ACC20(d) : "l"(da), "l"(db), "r"(sc), "n"(TA), "n"(TB));
}
DI void wg_rs40(float* d, uint32_t a0, uint32_t a1, uint32_t a2, uint32_t a3, uint64_t db, int sc) {
  asm volatile("{.reg .pred p; setp.ne.b32 p, %25, 0;\n"
               "wgmma.mma_async.sync.aligned.m64n40k16.f32.bf16.bf16 {%0,%1,%2,%3,%4,%5,%6,%7,%8,%9,%10,%11,%12,%13,%14,%15,%16,%17,%18,%19}, {%20,%21,%22,%23}, %24, p, 1, 1, 0;}"
               : ACC20(d) : "r"(a0), "r"(a1), "r"(a2), "r"(a3), "l"(db), "r"(sc));
}
DI void wg_rs32(float* d, uint32_t a0, uint32_t a1, uint32_t a2, uint32_t a3, uint64_t db, int sc) {
  asm volatile("{.reg .pred p; setp.ne.b32 p, %21, 0;\n"
               "wgmma.mma_async.sync.aligned.m64n32k16.f32.bf16.bf16 {%0,%1,%2,%3,%4,%5,%6,%7,%8,%9,%10,%11,%12,%13,%14,%15}, {%16,%17,%18,%19}, %20, p, 1, 1, 0;}"
               : ACC16(d, 0) : "r"(a0), "r"(a1), "r"(a2), "r"(a3), "l"(db), "r"(sc));
}
DI void wg_rs8(float* d, uint32_t a0, uint32_t a1, uint32_t a2, uint32_t a3, uint64_t db, int sc) {
  asm volatile("{.reg .pred p; setp.ne.b32 p, %9, 0;\n"
               "wgmma.mma_async.sync.aligned.m64n8k16.f32.bf16.bf16 {%0,%1,%2,%3}, {%4,%5,%6,%7}, %8, p, 1, 1, 0;}"
               : ACC4(d, 0) : "r"(a0), "r"(a1), "r"(a2), "r"(a3), "l"(db), "r"(sc));
}
DI void mma16816(float* c, const uint32_t* a, uint32_t b0, uint32_t b1) {
  asm volatile("mma.sync.aligned.m16n8k16.row.col.f32.bf16.bf16.f32 {%0,%1,%2,%3}, {%4,%5,%6,%7}, {%8,%9}, {%0,%1,%2,%3};"
               : ACC4(c, 0) : "r"(a[0]), "r"(a[1]), "r"(a[2]), "r"(a[3]), "r"(b0), "r"(b1));
}
DI void wg_ss8(float* d, uint64_t da, uint64_t db, int sc) {
  asm volatile("{.reg .pred p; setp.ne.b32 p, %6, 0;\n"
               "wgmma.mma_async.sync.aligned.m64n8k16.f32.bf16.bf16 {%0,%1,%2,%3}, %4, %5, p, 1, 1, 1, 1;}"
               : ACC4(d, 0) : "l"(da), "l"(db), "r"(sc));
}
DI void wg_rs16(float* d, uint32_t a0, uint32_t a1, uint32_t a2, uint32_t a3, uint64_t db, int sc) {
  asm volatile("{.reg .pred p; setp.ne.b32 p, %13, 0;\n"
               "wgmma.mma_async.sync.aligned.m64n16k16.f32.bf16.bf16 {%0,%1,%2,%3,%4,%5,%6,%7}, {%8,%9,%10,%11}, %12, p, 1, 1, 0;}"
               : ACC4(d, 0), ACC4(d, 4) : "r"(a0), "r"(a1), "r"(a2), "r"(a3), "l"(db), "r"(sc));
}
__device__ uint4 g_xn[2 * NSEG * 10 * 256];
__device__ uint4 g_oT[2 * NBLK * 96 * 1024];
constexpr int PART_RING = 96 * 256;
__device__ uint4 g_part[4 * PART_RING];
constexpr int MEM_OFF = 192;
#define P4 ~0u, ~0u, ~0u, ~0u
#define P16 P4, P4, P4, P4
#define P256 P16, P16, P16, P16, P16, P16, P16, P16, P16, P16, P16, P16, P16, P16, P16, P16
#define P2K P256, P256, P256, P256, P256, P256, P256, P256
#define P8K P2K, P2K, P2K, P2K
__device__ __align__(8192) uint32_t g_mem32[5 * 2 * 2 * 2048] = {P8K, P8K, P8K, P8K, P8K};
#define g_mem ((uint4*)g_mem32)
constexpr int C_XN = 0;
constexpr int C_O = C_XN + 2 * NBLK;
constexpr int C_HALF = C_O + 6 * 2 * NBLK;
constexpr int C_TOTAL = 512;
constexpr int CSTRIDE = 32;
__device__ uint32_t g_cnt[C_TOTAL * CSTRIDE];
constexpr uint32_t XN_TARGET = 128;

#define TRACE(c, n, i, v)
#define SLOG(i)
#define PROF(i)
#define PROFA(c)
#define PROFV(i, v)

constexpr uint32_t SMEM0 = 1024;
constexpr uint32_t SM_WK = 0, SM_WO = 81920, SM_H = 163840, SM_QT = 215040, QSTR = 1056  , SM_KT = SM_QT + 5 * QSTR + 1024,
                   SM_SR = SM_KT + 5120  , SM_PROF = SM_SR + 5760, R_SMEM = 232448,
                   SM_RED = SM_QT + 1024, SM_BAR = SM_RED + 768;
constexpr uint32_t SM_P = SM_KT, SM_OB = SM_QT + 3200;
constexpr uint32_t B_HFULL = SM_BAR, B_HEMPTY = SM_BAR + 40, B_MTRY = SM_BAR + 80, B_W = SM_BAR + 112, B_SR = B_W + 32,
                   B_PMEM = B_SR + 24, B_PTOK = B_SR + 32, B_OB = B_SR + 40, B_OPD = B_SR + 48, B_RFREE = B_SR + 56,
                   B_GATE = B_SR + 64, B_PSUM = B_SR + 72, B_END = B_SR + 80, B_PVI = B_SR + 88,
                   B_OPI = B_SR + 96, B_OTOK = B_SR + 112, SM_TOPI = B_SR + 128, B_PACE = SM_TOPI + 8,
                   SM_RS = SM_QT + 2 * QSTR + 1024;
static_assert(B_PACE + 32 <= SM_QT + 2 * QSTR, "barriers must fit the unused q row group");

struct RParams {
  uint64_t dH, dHt, dWK, dWO, dQT, dKT, dP, dOB[6];
  const char* w[4];
  const uint4* mem0;
  const uint32_t* x;
  int pf;
  int nslots, d3, pn, moff, ds, dh, dq;
  int d2[10], d1[8];
  uint32_t slot[2 * NSEG];
};
static void r_fill_desc(RParams& p) {
  p.dH = mkdesc(SMEM0 + SM_H, 128, 2048, 0);
  p.dHt = mkdesc(SMEM0 + SM_H + 2048, 128, 2048, 0);
  p.dWK = mkdesc(SMEM0 + SM_WK, 1024, 1024, 1);
  p.dWO = mkdesc(SMEM0 + SM_WO, 1024, 1024, 1);
  for (int i = 0; i < 6; i++) p.dOB[i] = mkdesc(SMEM0 + SM_OB + (i < 3 ? 0 : (i - 3) * 1024), 128, 128, 0);
  p.dQT = mkdesc(SMEM0 + SM_QT, 128, QSTR, 0);
  p.dKT = mkdesc(SMEM0 + SM_KT, 128, 1024, 0);
  p.dP = mkdesc(SMEM0 + SM_P, 128, 640, 0);
}
DI uint64_t dadd(uint64_t d, int bytes) {
  uint64_t r;
  asm volatile("add.u64 %0, %1, %2;" : "=l"(r) : "l"(d), "l"((long long)(bytes / 16)));
  return r;
}
template <int BYTES> DI void dstep(uint64_t& d) { asm volatile("add.u64 %0, %0, %1;" : "+l"(d) : "n"((long long)(BYTES / 16))); }
__host__ __device__ constexpr int hoff(int ks) { return (ks >> 3) * 10240 + (ks & 7) * 256; }

DI int opaque(int v) { asm volatile("" : "+r"(v)); return v; }
DI uint32_t pin(uint32_t v, int lane) { return __shfl_sync(~0u, v + (lane >> 5), lane); }
DI char* pin(char* p, int lane) { return (char*)__shfl_sync(~0u, (unsigned long long)p, lane); }
DI float blo(uint32_t w) { return __uint_as_float(w << 16); }
DI float bhi(uint32_t w) { return __uint_as_float(w & 0xffff0000u); }
#define R_FB 1
#define PIN_DST 1
#define RG0 232
#define RG1 216
#define RG2 40
#define RG3 24
DI void ldsm4t(uint32_t* r, uint32_t a) {
  asm volatile("ldmatrix.sync.aligned.m8n8.x4.trans.shared.b16 {%0,%1,%2,%3}, [%4];" : "=r"(r[0]), "=r"(r[1]), "=r"(r[2]), "=r"(r[3]) : "r"(a) : "memory");
}
DI void st_tagged(void* p, float a, float b, uint32_t keep, uint32_t tagbit) {
  asm volatile("{.reg .b32 t; cvt.rn.bf16x2.f32 t, %2, %1; lop3.b32 t, t, %3, %4, 0xea; st.relaxed.gpu.global.b32 [%0], t;}" ::"l"(p), "f"(a), "f"(b),
               "r"(keep), "r"(tagbit) : "memory");
}
DI uint32_t lop_bad(uint32_t a, uint32_t b, uint32_t m) { uint32_t d; asm("lop3.b32 %0, %1, %2, %3, 0x7e;" : "=r"(d) : "r"(a), "r"(b), "r"(m)); return d; }
DI uint32_t lop_or3(uint32_t a, uint32_t b, uint32_t c) { uint32_t d; asm("lop3.b32 %0, %1, %2, %3, 0xfe;" : "=r"(d) : "r"(a), "r"(b), "r"(c)); return d; }
DI uint32_t clk() { uint32_t t; asm volatile("mov.u32 %0, %%clock;" : "=r"(t)); return t; }
DI void spin(uint32_t cyc) { const uint32_t t0 = clk(); while (__any_sync(~0u, clk() - t0 < cyc)) {} }
template <int NL> DI float2 poll_sum(const uint32_t* src, uint32_t tag, uint32_t even, uint32_t& g) {
  uint32_t r[NL];
  while (true) {
#pragma unroll
    for (int i = 0; i < NL; i++) r[i] = ld_rlx(src + i * 32);
    uint32_t bad = lop_or3(lop_bad(r[0], r[1], tag), lop_bad(r[2], r[3], tag), lop_bad(r[4], r[5], tag));
    if (NL == 12) bad = lop_or3(bad, lop_bad(r[6], r[7], tag), lop_bad(r[8], r[9], tag));
    asm volatile("lop3.b32 %0, %0, %1, %2, 0xa8;" : "+r"(bad) : "r"(lop_bad(r[NL - 2], r[NL - 1], tag)), "r"(even));
    if (!__any_sync(~0u, bad)) break;
    g++;
  }
  float x[NL / 2], y[NL / 2];
#pragma unroll
  for (int i = 0; i < NL / 2; i++) { x[i] = blo(r[2 * i]) + blo(r[2 * i + 1]); y[i] = bhi(r[2 * i]) + bhi(r[2 * i + 1]); }
  float2 u = make_float2((x[0] + x[1]) + (x[2] + x[3]), (y[0] + y[1]) + (y[2] + y[3]));
  if (NL == 12) { u.x += x[4] + x[5]; u.y += y[4] + y[5]; }
  return u;
}

constexpr int PLANE = 16 * 40 * 32, MAXPL = 13;
__device__ uint2 g_acc[(size_t)2 * NBLK * 2 * MAXPL * PLANE];
DI uint2* acc_planes(int lb, int d) { return g_acc + (size_t)((lb * 2 + d) * MAXPL) * PLANE; }
DI void ln_stats(const float4* v, uint32_t red, int warp, int lane, int bar, float& mean, float& rstd) {
  float s = 0.f;
#pragma unroll
  for (int i = 0; i < 5; i++) s += (v[i].x + v[i].y) + (v[i].z + v[i].w);
  s += __shfl_xor_sync(~0u, s, 1);
  s += __shfl_xor_sync(~0u, s, 2);
  s *= 1.f / 80;
  float q = 0.f;
#pragma unroll
  for (int i = 0; i < 5; i++) q += ((v[i].x - s) * (v[i].x - s) + (v[i].y - s) * (v[i].y - s)) + ((v[i].z - s) * (v[i].z - s) + (v[i].w - s) * (v[i].w - s));
  q += __shfl_xor_sync(~0u, q, 1);
  q += __shfl_xor_sync(~0u, q, 2);
  if ((lane & 3) == 0) asm volatile("st.shared.v2.f32 [%0], {%1,%2};" ::"r"(red + lane * 16 + warp * 8), "f"(s), "f"(q) : "memory");
  bar_sync(bar, 256);
  const uint4 t = lds128(red + lane * 16);
  const float m0 = __uint_as_float(t.x), m1 = __uint_as_float(t.z);
  mean = m0 + m1;
  mean += __shfl_xor_sync(~0u, mean, 1);
  mean += __shfl_xor_sync(~0u, mean, 2);
  mean *= 0.125f;
  q = __uint_as_float(t.y) + __uint_as_float(t.w) + 80.f * ((m0 - mean) * (m0 - mean) + (m1 - mean) * (m1 - mean));
  q += __shfl_xor_sync(~0u, q, 1);
  q += __shfl_xor_sync(~0u, q, 2);
  rstd = rsqrtf(q * (1.f / DM) + 1e-5f);
}
template <int SH, int STR> DI void store_img(uint32_t* dst, const float4* v, int warp, float mean, float rstd) {
#pragma unroll
  for (int i = 0; i < 5; i++) {
    const int U = 10 * warp + 2 * i;
    uint32_t* p = dst + (U >> SH) * STR + (U & ((1 << SH) - 1)) * 32;
    p[0] = pack2((v[i].x - mean) * rstd, (v[i].y - mean) * rstd);
    p[32] = pack2((v[i].z - mean) * rstd, (v[i].w - mean) * rstd);
  }
}
DI uint32_t* xn_row_group(int layer, int rg) { return (uint32_t*)(g_xn + (size_t)((layer * NSEG + (rg >> 2)) * 2560 + (rg & 3) * 128)); }

DI void first_ln(const uint32_t* a, int rg, uint32_t red, int warp, int lane, int bar) {
  float4 v[5];
#pragma unroll
  for (int i = 0; i < 5; i++) {
    v[i] = make_float4(blo(a[2 * i]), bhi(a[2 * i]), blo(a[2 * i + 1]), bhi(a[2 * i + 1]));
    acc_planes(rg >> 4, 0)[((rg & 15) * 40 + warp * 5 + i) * 32 + lane] = make_uint2(a[2 * i], a[2 * i + 1]);
  }
  float mean, rstd;
  ln_stats(v, red, warp, lane, bar, mean, rstd);
  store_img<4, 2048>(xn_row_group(0, rg) + lane, v, warp, mean, rstd);
}
#define SOLO 1
#define QK_P0 32
#define QK_KB 0
struct QKOrder { int op[76]; };
__host__ __device__ constexpr QKOrder qk_order() {
  QKOrder o = {};
  int n = 0, k = 0, q = 0;
  for (; k < QK_P0; k++, q++) { o.op[n++] = 64 | k; o.op[n++] = q; }
  for (int i = 0; i < QK_KB; i++) o.op[n++] = 64 | k++;
  for (int i = 0; i < -QK_KB; i++) o.op[n++] = q++;
  const int nk = 40 - k, nq = 36 - q;
  for (int i = 0, dk = 0, dq = 0; i < nk + nq; i++) {
    if (dq * nk <= dk * nq + (QK_KB ? 0 : -nq) && dq < nq) { o.op[n++] = q++; dq++; } else if (dk < nk) { o.op[n++] = 64 | k++; dk++; } else { o.op[n++] = q++; dq++; }
  }
  return o;
}
__global__ void __launch_bounds__(512, 1)
r_kernel(const __grid_constant__ CUtensorMap mapWq, const __grid_constant__ CUtensorMap mapWk, const __grid_constant__ CUtensorMap mapWv,
         const __grid_constant__ CUtensorMap mapWo, const __grid_constant__ RParams prm) {
  const uint32_t sb = smem_base();
  const int wid = __shfl_sync(~0u, threadIdx.x >> 5, 0);
  const int lane0 = __shfl_sync(~0u, threadIdx.x & 31, threadIdx.x & 31);
  const int lane = lane0;
  const int warp = wid & 3, wg = wid >> 2;
  const uint32_t rank = blockIdx.x, head = blockIdx.y, cta = head * 3 + rank;
  const uint32_t peer1 = mapa(sb, rank == 2 ? 0 : rank + 1), peer2 = mapa(sb, rank == 0 ? 2 : rank - 1);
  const int nslots = prm.nslots;

  SLOG(0);
  if (threadIdx.x == 384) {
    if ((sb & 0x3FFFF) != SMEM0) __trap();
    for (int c = 0; c < 5; c++) { mbar_init(sb + B_HFULL + 8 * c, 2); mbar_init(sb + B_HEMPTY + 8 * c, c == 4 ? 8 : 4); }
    for (int c = 0; c < 11; c++) mbar_init(sb + B_MTRY + 8 * c, 1);
    mbar_init(sb + B_PTOK, rank == 0 ? 3 : 2); mbar_init(sb + B_OB, 5); mbar_init(sb + B_OPD, 4);
    mbar_init(sb + B_OPI, 1); mbar_init(sb + B_OPI + 8, 1); mbar_init(sb + B_RFREE, 1); mbar_init(sb + B_GATE, 1); mbar_init(sb + B_PMEM, 2); mbar_init(sb + B_PSUM, 2); mbar_init(sb + B_PVI, 5); mbar_init(sb + B_OTOK, 4); mbar_init(sb + B_OTOK + 8, 4); mbar_init(sb + B_END, 15);
    for (int c = 0; c < 4; c++) mbar_init(sb + B_PACE + 8 * c, 1);
    asm volatile("fence.mbarrier_init.release.cluster;" ::: "memory");
    fence_async_smem();
  }
  asm volatile("griddepcontrol.launch_dependents;");
  asm volatile("barrier.cluster.arrive.release.aligned;" ::: "memory");

  if (wg < 2) {
  {
    uint32_t xa[10];
    const uint32_t* src = prm.x + (size_t)(cta * 8 + (lane >> 2)) * (DM / 2) + wid * 40 + (lane & 3);
#pragma unroll
    for (int i = 0; i < 10; i++) xa[i] = __ldg(src + i * 4);
    asm volatile("barrier.cluster.wait.acquire.aligned;" ::: "memory");
    first_ln(xa, cta, sb + SM_SR, wid, lane, 8);
    bar_arrive(10, 288);
  }
  if (wg == 0) {
    asm volatile("setmaxnreg.inc.sync.aligned.u32 %0;" ::"n"(RG0));
    uint32_t wq[160];
    SLOG(1);
    mbar_wait(sb + B_W, 0);
    SLOG(2);
    {
      const uint32_t ld_off = ((lane >> 4) * 8 + (lane & 7)) * 128 + (((2 * warp + ((lane >> 3) & 1)) ^ (lane & 7)) << 4);
#pragma unroll
      for (int ks = 0; ks < 40; ks++) ldsm4t(wq + 4 * ks, sb + SM_WO + ks * 2048 + ld_off);
    }
    fence_async_smem();
    bar_arrive(5, 160);
    mbar_wait(sb + B_W + 16, 0);
    SLOG(3);
    const uint32_t st_addr = pin(sb + SM_QT + (lane >> 4) * 1024 + (2 * warp + ((lane >> 3) & 1)) * 128 + (lane & 7) * 16, lane);
    const uint32_t sq_addr = pin(sb + SM_QT + (2 + (lane & 3)) * QSTR + warp * 256 + (lane >> 2) * 16, lane);
    const uint32_t to_lo = warp == 0 ? peer1 : mapa(sb, warp == 2 ? 2 : 0), to_hi = warp == 0 ? peer2 : mapa(sb, warp == 1 ? 1 : 0);
    const uint32_t sr_off = SM_SR + warp * 1920 + rank * 640, sr_bar = B_SR + warp * 8;
    const uint32_t sa0 = pin(to_lo + sr_off + lane * 16, lane), sb0 = pin(to_lo + sr_bar, lane), sa1 = pin(to_lo + sr_off + 512 + lane * 4, lane), sb1 = pin(sb0, lane);
    const uint32_t sa2 = pin(to_hi + sr_off + lane * 16, lane), sb2 = pin(to_hi + sr_bar, lane), sa3 = pin(to_hi + sr_off + 512 + lane * 4, lane), sb3 = pin(sb2, lane);
    uint32_t nsolo = 0;
#pragma unroll 1
    for (int n = 0; n < nslots; n++) {
      const uint32_t par = n & 1;
      PROFA(warp == PW);
      const bool alt = prm.slot[n] & 128;
      auto next = [&](uint64_t& d, int ks) { if ((ks & 7) == 7) dstep<10240 - 7 * 256>(d); else dstep<256>(d); };
      auto store_k = [&](const float* ka) {
        stsm2(st_addr + (SM_KT - SM_QT), pack2(ka[0], ka[1]), pack2(ka[2], ka[3]));
        stsm4(st_addr + (SM_KT - SM_QT) + 1024, pack2(ka[4], ka[5]), pack2(ka[6], ka[7]), pack2(ka[8], ka[9]), pack2(ka[10], ka[11]));
        stsm4(st_addr + (SM_KT - SM_QT) + 3072, pack2(ka[12], ka[13]), pack2(ka[14], ka[15]), pack2(ka[16], ka[17]), pack2(ka[18], ka[19]));
      };
      auto store_qt = [&](const float* q) {
        sts128(sq_addr, make_uint4(pack2(q[0], q[1]), pack2(q[4], q[5]), pack2(q[8], q[9]), pack2(q[12], q[13])));
        sts128(sq_addr + 128, make_uint4(pack2(q[2], q[3]), pack2(q[6], q[7]), pack2(q[10], q[11]), pack2(q[14], q[15])));
      };
      if (SOLO && n > 0 && ((prm.slot[n] >> 8) & 255) == n) {
        {
          float qt[16];
          uint64_t rh = prm.dHt;
          mbar_wait(sb + B_PVI, nsolo++ & 1);
          mbar_wait(sb + B_OPD, par ^ 1);
          spin(prm.dq);
          wg_fence();
#pragma unroll
          for (int ks = 0; ks < 40; ks++) { wg_rs32(qt, wq[4 * ks], wq[4 * ks + 1], wq[4 * ks + 2], wq[4 * ks + 3], rh, ks != 0); if (ks < 39) next(rh, ks); }
          wg_commit();
          wg_wait<0>();
          reg_fence<16>(qt);
          store_qt(qt);
        }
        float qm[4], ka[20];
        uint64_t rk = prm.dWK, rh = prm.dH, rq;
        bool ok = false;
#pragma unroll
        for (int g = 0; g < 18; g++) {
          if ((g & 3) == 0 && !ok) mbar_wait(sb + B_HFULL + 2 * g, par);
          if (g == 0) PROF(0);
          if ((g & 3) == 3) ok = mbar_test(sb + B_HFULL + 2 * (g + 1), par);
          if ((g & 3) == 0) wg_fence();
#pragma unroll
          for (int ks = 2 * g; ks < 2 * g + 2; ks++) {
            wg_ss40<1, 0>(ka, rk, rh, ks != 0);
            wg_rs8(qm, wq[4 * ks], wq[4 * ks + 1], wq[4 * ks + 2], wq[4 * ks + 3], rh, ks != 0);
            dstep<2048>(rk); next(rh, ks);
          }
        }
        wg_commit();
        rq = rh;
#pragma unroll
        for (int ks = 36; ks < 40; ks++) { wg_ss40<1, 0>(ka, rk, rh, 1); if (ks < 39) { dstep<2048>(rk); dstep<256>(rh); } }
        wg_commit();
#pragma unroll
        for (int ks = 36; ks < 40; ks++) { wg_rs8(qm, wq[4 * ks], wq[4 * ks + 1], wq[4 * ks + 2], wq[4 * ks + 3], rq, 1); if (ks < 39) dstep<256>(rq); }
        wg_commit();
        wg_wait<2>();
        if (alt) bar_arrive(2, 256);
        wg_wait<1>();
        if (!alt) bar_arrive(2, 256);
        reg_fence<20>(ka);
        store_k(ka);
        wg_wait<0>();
        reg_fence<4>(qm);
        PROF(9);
        stsm2(st_addr, pack2(qm[0], qm[1]), pack2(qm[2], qm[3]));
      } else {
      float qa[20], ka[20];
      uint64_t rk = prm.dWK, rh = prm.dH, rq;
      auto K = [&](int ks) { wg_ss40<1, 0>(ka, rk, rh, ks != 0); };
      auto Q = [&](int ks, uint64_t db) { wg_rs40(qa, wq[4 * ks], wq[4 * ks + 1], wq[4 * ks + 2], wq[4 * ks + 3], db, ks != 0); };
      constexpr QKOrder ord = qk_order();
      auto first = [&](int g, int c) { for (int i = 0; i < 76; i++) if ((ord.op[i] & 63) >> 3 == c) return i >> 2 == g; return false; };
      bool ok = true;
      mbar_wait(sb + B_HFULL, par);
#pragma unroll
      for (int g = 0; g < 19; g++) {
        if (!ok) {
#pragma unroll
          for (int c = 1; c < 5; c++) if (first(g, c)) mbar_wait(sb + B_HFULL + 8 * c, par);
          mbar_wait(sb + B_GATE, 1);
        }
        if (g == 0) PROF(0);
        if (g < 18) ok = mbar_test(sb + B_GATE, 1);
#pragma unroll
        for (int c = 1; c < 5; c++) if (first(g + 1, c)) ok &= mbar_test(sb + B_HFULL + 8 * c, par);
        wg_fence();
#pragma unroll
        for (int i = 4 * g; i < 4 * g + 4; i++) {
          const int ks = ord.op[i] & 63;
          if (i < 2 * QK_P0) {
            if (ord.op[i] & 64) K(ks);
            else { Q(ks, rh); dstep<2048>(rk); next(rh, ks); if (i == 2 * QK_P0 - 1) rq = rh; }
          } else if (ord.op[i] & 64) { K(ks); if (ks < 39) { dstep<2048>(rk); next(rh, ks); } }
          else { Q(ks, rq); next(rq, ks); }
        }
        if (g == 17) wg_commit();
      }
      wg_commit();
#pragma unroll
      for (int ks = 36; ks < 40; ks++) { Q(ks, rq); if (ks < 39) dstep<256>(rq); }
      wg_commit();
      wg_wait<2>();
      if (alt) bar_arrive(2, 256);
      mbar_wait(sb + B_OPD, par ^ 1);
      wg_wait<1>();
      if (!alt) bar_arrive(2, 256);
      reg_fence<20>(ka);
      store_k(ka);
      wg_wait<0>();
      reg_fence<20>(qa);
      PROF(9);
      stsm2(st_addr, pack2(qa[0], qa[1]), pack2(qa[2], qa[3]));
      store_qt(qa + 4);
      }
      mbar_arrive_if(lane == 0, sb + B_HEMPTY + 32);
      fence_async_smem();
      bar_sync(1, 128);
      PROF(1);
      float qa[20];
      wg_fence();
#pragma unroll
      for (int k = 0; k < 4; k++) wg_ss40<1, 1>(qa, dadd(prm.dQT, k * 256), dadd(prm.dKT, k * 256), k != 0);
      wg_commit();
      bar_arrive(7, 256);
      wg_wait<0>();
      reg_fence<20>(qa);
      PROF(3);
      if (warp < 3) {
        uint32_t p[5];
#pragma unroll
        for (int j = 0; j < 5; j++) p[j] = pack2(qa[4 * j], qa[4 * j + 1]);
        if (warp == 0) {
          st_async4(sa0, p[0], p[1], p[2], p[3], sb0);
          st_async4(sa2, p[0], p[1], p[2], p[3], sb2);
          st_async1(sa1, p[4], sb1);
          st_async1(sa3, p[4], sb3);
          sts128(sb + sr_off + lane * 16, make_uint4(p[0], p[1], p[2], p[3]));
          sts32(sb + sr_off + 512 + lane * 4, p[4]);
          __syncwarp();
          mbar_expect_if(lane == 0, sb + B_SR, 1280);
        } else {
          uint32_t h[5];
#pragma unroll
          for (int j = 0; j < 5; j++) h[j] = pack2(qa[4 * j + 2], qa[4 * j + 3]);
          spin(prm.d3);
          st_async4(sa0, p[0], p[1], p[2], p[3], sb0);
          st_async4(sa2, h[0], h[1], h[2], h[3], sb2);
          st_async1(sa1, p[4], sb1);
          st_async1(sa3, h[4], sb3);
        }
      }
    }
  } else {
    asm volatile("setmaxnreg.inc.sync.aligned.u32 %0;" ::"n"(RG1));
    uint32_t wv[160];
    mbar_wait(sb + B_W + 8, 0);
    SLOG(4);
    {
      const uint32_t ld_off = ((lane >> 4) * 8 + (lane & 7)) * 128 + (((2 * warp + ((lane >> 3) & 1)) ^ (lane & 7)) << 4);
#pragma unroll
      for (int ks = 0; ks < 40; ks++) ldsm4t(wv + 4 * ks, sb + SM_WO + ks * 2048 + ld_off);
    }
    fence_async_smem();
    bar_arrive(6, 160);
    const uint64_t dH = prm.dH;
    uint32_t op[8];
    const uint32_t ob_off = SM_OB + (4 * rank + warp) * 256 + lane * 4;
    const uint32_t oa0 = pin(peer1 + ob_off, lane), ob0 = pin(peer1 + B_OB, lane), oa1 = pin(peer2 + ob_off, lane), ob1 = pin(peer2 + B_OB, lane);
    const uint32_t oa2 = pin(oa0 + 128, lane), ob2 = pin(ob0, lane), oa3 = pin(oa1 + 128, lane), ob3 = pin(ob1, lane);
    const uint32_t o_loc = pin(sb + ob_off, lane), rs_addr = pin(sb + SM_RS + (lane & 3) * 8, lane);
    const uint32_t tok_off = pin((cta * 1024 + 64 * warp + (lane ^ (lane >> 3))) * 16, lane), keep = pin((lane & 1) ? ~0u : ~1u, lane);
    const uint32_t pb_off = pin((8 * rank + 2 * warp) * 4096 + head * 128 + lane * 4, lane);
    const uint32_t ph_off = pin(72 * 4096 + 2 * warp * 12288 + cta * 64 + (lane & 2) * 3072 + (lane >> 2) * 8 + (lane & 1) * 4, lane);
    auto store_tok = [&](int m, int lane) {
      const uint32_t ls = prm.slot[m] & 127, sig = prm.slot[m] >> 16;
      uint4* dst = (uint4*)((char*)(g_oT + (size_t)((ls >> 2) * (96 * 1024) + (ls & 3) * 256)) + tok_off);
      dst[0] = make_uint4(op[0], op[1], op[2], op[3]);
      dst[32] = make_uint4(op[4], op[5], op[6], op[7]);
      __syncwarp();
      mbar_arrive_if(sig && lane == 0, sb + B_OTOK + (ls >> 6) * 8);
    };
#pragma unroll 1
    for (int n = 0; n < nslots; n++) {
      const uint32_t par = n & 1;
      const int lane = opaque(lane0);
      PROFA(warp == PW);
      float va[20];
      const bool alt = prm.slot[n] & 128;
      mbar_expect_if(warp == 0 && lane == 0, sb + B_PTOK, rank == 0 ? 1280 : 1920);
      bar_sync(2, 256);
#pragma unroll
      for (int g = 0; g < 10; g++) {
        wg_fence();
#pragma unroll
        for (int ks = 4 * g; ks < 4 * g + 4; ks++) { wg_rs40(va, wv[4 * ks], wv[4 * ks + 1], wv[4 * ks + 2], wv[4 * ks + 3], dadd(dH, hoff(ks)), ks != 0); }
        wg_commit();
        if (g >= 2 && !(g & 1)) {
          wg_wait<1>();
          if (lane == 0) mbar_arrive(sb + B_HEMPTY + 8 * (g / 2 - 1));
        }
        if (g == 1 ? !alt : g == 2 && alt) bar_sync(7, 256);
      }
      wg_wait<0>();
      reg_fence<20>(va);
      if (lane == 0) mbar_arrive(sb + B_HEMPTY + 32);
      PROF(10);
      uint32_t vf[10];
#pragma unroll
      for (int j = 0; j < 10; j++) {
        const int i = (j + 4) % 10;
        asm volatile("cvt.rn.bf16x2.f32 %0, %1, %2;" : "=r"(vf[i]) : "f"(va[2 * i + 1]), "f"(va[2 * i]));
        if (j == 5) mbar_wait(sb + B_W + 8, 0);
      }
      uint32_t z0, z1;
      asm volatile("shr.u32 %0, %2, 5; shr.u32 %1, %2, 6;" : "=r"(z0), "=r"(z1) : "r"(lane));
      const uint32_t info = prm.slot[n];
      const uint32_t tagbit = ~(info >> 1) & ~keep;
      char* const ring = (char*)(g_part + (size_t)((((info >> 5) & 2) + (info & 1)) * PART_RING));
      char* const pb = pin(ring + pb_off, lane);
      char* const ph = ring + ph_off;
      mbar_wait(sb + B_PMEM, par);
      float om[4];
      wg_fence();
      wg_rs8(om, vf[0], vf[1], vf[2], vf[3], prm.dP, 0);
      wg_rs8(om, vf[4], vf[5], vf[6], vf[7], dadd(prm.dP, 256), 1);
      wg_rs8(om, vf[8], vf[9], z0, z1, dadd(prm.dP, 512 - (128 << 16)), 1);
      wg_commit();
      {
        wg_wait<0>();
        reg_fence<4>(om);
        const uint32_t b0 = pack2(om[0], om[1]), b1 = pack2(om[2], om[3]);
        st_async1(oa0, b0, ob0);
        st_async1(oa1, b0, ob1);
        st_async1(oa2, b1, ob2);
        st_async1(oa3, b1, ob3);
        sts32(o_loc, b0);
        sts32(o_loc + 128, b1);
        fence_async_smem();
        __syncwarp();
        mbar_arrive_if(lane == 0, sb + B_OB);
      }
      PROF(11);
      {
        float c[8];
        mbar_wait(sb + B_PSUM, par);
        const uint2 rs = lds64(rs_addr);
        const float r0 = __uint_as_float(rs.x), r1 = __uint_as_float(rs.y);
        if (n == 0) { SLOG(5); mbar_wait(sb + B_W + 24, 0); SLOG(6); }
        mbar_wait(sb + B_OB, par);
        asm volatile("fence.proxy.async::generic.acquire.sync_restrict::shared::cluster.cluster;" ::: "memory");
        PROF(16);
        if ((info & 63) == NSEG - 1) {
          mbar_wait(sb + B_OPI + par * 8, (n >> 1) & 1);
          mbar_arrive_if(warp == 3 && lane == 0, sb + B_GATE);
#pragma unroll
          for (int p = 0; p < 6; p++) st_rlx1(pb + (p >> 1) * 98304 + (p & 1) * 4096, tagbit);
          st_rlx1(ph, tagbit);
          st_rlx1(ph + 12288, tagbit);
        } else {
#pragma unroll
        for (int p = 0; p < 4; p++) {
          float* const cur = c + 4 * (p & 1);
          float* const prv = c + 4 * (~p & 1);
          if (p == 2) mbar_wait(sb + B_OPI + par * 8, (n >> 1) & 1);
          wg_fence();
#pragma unroll
          for (int ks = 0; ks < (p < 3 ? 12 : 4); ks++) {
            wg_ss8(cur, dadd(prm.dWO, p * 24576 + ks * 2048), dadd(prm.dOB[p < 3 ? p : 3 + rank], ks * 256), ks != 0);
            if (p == 3 && ks == 3) mbar_arrive_if(warp == 3 && lane == 0, sb + B_GATE);
            if (p > 0 && ks == 3) {
              wg_commit();
              wg_wait<1>();
              reg_fence<4>(prv);
              st_tagged(pb + (p - 1) * 98304, prv[0] * r0, prv[1] * r1, keep, tagbit);
              st_tagged(pb + (p - 1) * 98304 + 4096, prv[2] * r0, prv[3] * r1, keep, tagbit);
            }
          }
          if (p < 3) wg_commit();
        }
        wg_wait<0>();
        reg_fence<4>(c + 4);
        st_tagged(ph, c[4] * r0, c[5] * r1, keep, tagbit);
        st_tagged(ph + 12288, c[6] * r0, c[7] * r1, keep, tagbit);
        }
        PROF(17);
      }
      mbar_wait(sb + B_PTOK, par);
      PROF(12);
      {
        float ot[16];
        wg_fence();
        wg_rs32(ot, vf[0], vf[1], vf[2], vf[3], dadd(prm.dP, 640), 0);
        wg_rs32(ot, vf[4], vf[5], vf[6], vf[7], dadd(prm.dP, 640 + 256), 1);
        wg_rs32(ot, vf[8], vf[9], z0, z1, dadd(prm.dP, 640 + 512 - (128 << 16)), 1);
        wg_commit();
        wg_wait<0>();
        reg_fence<16>(ot);
#pragma unroll
        for (int i = 0; i < 8; i++) op[(i & 1) * 4 + (i >> 1)] = pack2(ot[2 * i], ot[2 * i + 1]);
      }
      if (lane == 0) mbar_arrive(sb + B_OPD);
      PROF(13);
      if (info & 128) spin(prm.ds);
      store_tok(n, lane);
    }
  }
  } else if (wg == 2) {
    asm volatile("setmaxnreg.dec.sync.aligned.u32 %0;" ::"n"(RG2));
    asm volatile("barrier.cluster.wait.acquire.aligned;" ::: "memory");
    if (warp == 1) {
      const uint32_t depth = prm.pf & 7;
#pragma unroll 1
      for (uint32_t i = 0; i < 20 + depth; i++) {
        if (i >= depth) {
          const uint32_t j = i - depth;
          mbar_wait_wd(sb + B_PACE + 8 * (j & 3), (j >> 2) & 1);
          if (j % 5 == 4) mbar_arrive_if(lane == 0 && (j != 14 || depth == 1), sb + B_W + (j == 4 ? 0 : j == 9 ? 16 : j == 14 ? 8 : 24));
        }
        if (i >= 20) continue;
        const uint32_t m = i / 5, k = i % 5, bar = sb + B_PACE + 8 * (i & 3);
        if (i == 10) bar_sync(5, 160);
        if (i == 15) {
          if ((prm.pf & 8) && elect_one())
            for (int q = 0; q < 4; q++) tma_pf(&mapWo, (q / 3 * 3 + rank) * 64, head * DH + q % 3 * 64);
#pragma unroll 1
          for (uint32_t j = 16 - depth; j < 15; j++) mbar_wait_wd(sb + B_PACE + 8 * (j & 3), (j >> 2) & 1);
          mbar_arrive_if(lane == 0 && depth > 1, sb + B_W + 8);
          bar_sync(6, 160);
        }
        if (elect_one()) {
          mbar_expect(bar, 16384);
          if (m < 3) tma_2d(sb + (m == 1 ? SM_WK : SM_WO) + k * 16384, m == 0 ? &mapWq : m == 1 ? &mapWk : &mapWv, cta * 64, k * 128, bar);
          else
            for (uint32_t q = 2 * k; q < 2 * k + 2; q++)
              tma_2d(sb + SM_WO + q * 8192, &mapWo, q < 9 ? (q / 3 * 3 + rank) * 64 : 576, head * DH + (q < 9 ? q % 3 : rank) * 64, bar);
        }
      }
    }
    if (warp == 2 && cta < 80 && lane < 16)
      g_mem[(cta >> 4) * 2048 + (lane >> 3) * 1024 + prm.moff + (cta & 15) * 8 + (lane & 7)] = prm.mem0[(lane & 7) * 80 + cta];
    if (warp == 3) {
      bar_sync(10, 288);
      if (lane == 0) red_rel(&g_cnt[(C_XN + (cta >> 4)) * CSTRIDE], 8);
    }
    const uint32_t grp = warp == 1 ? 1 + rank : 4 - (rank >> 1);
    constexpr float SC = 0.07216878364870322f * 1.4426950408889634f;
    const bool split = cta >= 72;
    const uint32_t wd = split ? 72 * 16 + cta * 16 : cta * 32;
    const uint32_t src_off = pin(split ? 72 * 4096 + (cta - 72) * 6144 + warp * 1536 + (lane & 2) * 32 + (lane >> 2) * 8 + (lane & 1) * 4 : cta * 4096 + warp * 1024 + lane * 4, lane);
    const uint32_t dst_off = pin(((wd >> 9) * 8192 + prm.moff * 4 + (wd & 511) + lane) * 4, lane);
    const uint32_t red = pin(sb + SM_RED + (warp < 2 ? 0 : (warp - 1) * 256) + lane * 8, lane);
    const uint32_t fl = (warp & 2) * 8 + (lane >> 3) * 4 + (lane & 3), hf = lane & 4;
    const uint32_t s0 = pin(sb + SM_SR + fl * 16 + hf * 2, lane), s1 = pin(sb + fl * 4, lane), pd = pin(s1 + hf * 64, lane);
    const uint32_t even = pin(~lane & 1, lane);
    uint32_t nred = 0;
    const uint32_t arm = pin(warp == 0 && (lane == 5 || ((lane == 1 || lane == 2) && lane + rank != 3)) ? sb + B_SR + lane * 8 : 0, lane);
#pragma unroll 1
    for (int n = 0; n < nslots; n++) {
      const uint32_t par = n & 1;
      const int lane = opaque(lane0);
      PROFA(warp == PW2);
      const uint32_t info = prm.slot[n], s = info & 63, l = (info >> 6) & 1;
      {
        mbar_expect_if(arm, arm, lane == 5 ? 2048 : 1920);
        if (warp == 0 || warp == 3) {
          mbar_wait(sb + B_SR, par);
          PROF(4);
          const uint2 a0 = lds64(s0), a1 = lds64(s0 + 640), a2 = lds64(s0 + 1280);
          const uint32_t b0 = lds32(s1 + SM_SR + 512), b1 = lds32(s1 + SM_SR + 1152), b2 = lds32(s1 + SM_SR + 1792);
          float v[6];
          v[0] = blo(a0.x) + blo(a1.x) + blo(a2.x); v[1] = bhi(a0.x) + bhi(a1.x) + bhi(a2.x);
          v[2] = blo(a0.y) + blo(a1.y) + blo(a2.y); v[3] = bhi(a0.y) + bhi(a1.y) + bhi(a2.y);
          v[4] = blo(b0) + blo(b1) + blo(b2); v[5] = bhi(b0) + bhi(b1) + bhi(b2);
          float m = fmaxf(fmaxf(v[0], v[1]), fmaxf(v[2], v[3]));
          m = fmaxf(fmaxf(m, __shfl_xor_sync(~0u, m, 4)), fmaxf(v[4], v[5]));
          {
            const float m1 = __shfl_xor_sync(~0u, m, 1), m2 = __shfl_xor_sync(~0u, m, 2), m3 = __shfl_xor_sync(~0u, m, 3);
            m = fmaxf(fmaxf(m, m1), fmaxf(m2, m3));
          }
          const float ms = -m * SC;
#pragma unroll
          for (int i = 0; i < 6; i++) v[i] = ex2(fmaf(v[i], SC, ms));
          float sum = (v[0] + v[1]) + (v[2] + v[3]);
          const float so = __shfl_xor_sync(~0u, sum, 4);
          sts32(pd + SM_P, pack2(v[0], v[1]));
          sts32(pd + SM_P + 128, pack2(v[2], v[3]));
          sts32(s1 + SM_P + 512, pack2(v[4], v[5]));
          fence_async_smem();
          __syncwarp();
          mbar_arrive_if(lane == 0, sb + B_PMEM);
          PROF(5);
          sum += so + (v[4] + v[5]);
          {
            const float t1 = __shfl_xor_sync(~0u, sum, 1), t2 = __shfl_xor_sync(~0u, sum, 2), t3 = __shfl_xor_sync(~0u, sum, 3);
            sum = (sum + t1) + (t2 + t3);
          }
          float r;
          asm("rcp.approx.ftz.f32 %0, %1;" : "=f"(r) : "f"(sum));
          sts32(sb + SM_RS + (warp & 2) * 8 + (lane >> 3) * 4, __float_as_uint(r));
          __syncwarp();
          mbar_arrive_if(lane == 0, sb + B_PSUM);
        } else {
          if (warp + rank != 3) {
            const uint32_t src = sb + SM_SR + warp * 1920;
            mbar_wait(sb + B_SR + warp * 8, par);
            const uint4 a0 = lds128(src + lane * 16), a1 = lds128(src + 640 + lane * 16), a2 = lds128(src + 1280 + lane * 16);
            const uint32_t b0 = lds32(src + 512 + lane * 4), b1 = lds32(src + 1152 + lane * 4), b2 = lds32(src + 1792 + lane * 4);
            float v[10];
            v[0] = blo(a0.x) + blo(a1.x) + blo(a2.x); v[1] = bhi(a0.x) + bhi(a1.x) + bhi(a2.x);
            v[2] = blo(a0.y) + blo(a1.y) + blo(a2.y); v[3] = bhi(a0.y) + bhi(a1.y) + bhi(a2.y);
            v[4] = blo(a0.z) + blo(a1.z) + blo(a2.z); v[5] = bhi(a0.z) + bhi(a1.z) + bhi(a2.z);
            v[6] = blo(a0.w) + blo(a1.w) + blo(a2.w); v[7] = bhi(a0.w) + bhi(a1.w) + bhi(a2.w);
            v[8] = blo(b0) + blo(b1) + blo(b2); v[9] = bhi(b0) + bhi(b1) + bhi(b2);
            {
              const int lim = 6 + 2 * grp + (lane & 24) + ((lane >> 2) & 1) - 2 * (lane & 3);
#pragma unroll
              for (int i = 2; i < 10; i++) if ((i >> 1) * 8 + (i & 1) > lim) v[i] = -INFINITY;
            }
            float m = fmaxf(fmaxf(fmaxf(v[0], v[1]), fmaxf(v[2], v[3])), fmaxf(fmaxf(v[4], v[5]), fmaxf(v[6], v[7])));
            m = fmaxf(m, fmaxf(v[8], v[9]));
            {
              const float m1 = __shfl_xor_sync(~0u, m, 1), m2 = __shfl_xor_sync(~0u, m, 2), m3 = __shfl_xor_sync(~0u, m, 3);
              m = fmaxf(fmaxf(m, m1), fmaxf(m2, m3));
            }
            const float ms = -m * SC;
#pragma unroll
            for (int i = 0; i < 10; i++) v[i] = ex2(fmaf(v[i], SC, ms));
            float sum = ((v[0] + v[1]) + (v[2] + v[3])) + ((v[4] + v[5]) + (v[6] + v[7])) + (v[8] + v[9]);
            {
              const float s1 = __shfl_xor_sync(~0u, sum, 1), s2 = __shfl_xor_sync(~0u, sum, 2), s3 = __shfl_xor_sync(~0u, sum, 3);
              sum = (sum + s1) + (s2 + s3);
            }
            float r;
            asm("rcp.approx.ftz.f32 %0, %1;" : "=f"(r) : "f"(sum));
            {
              const uint32_t row = SM_P + grp * 640;
#pragma unroll
              for (int j = 0; j < 5; j++) sts32(sb + row + j * 128 + lane * 4, pack2(v[2 * j] * r, v[2 * j + 1] * r));
              fence_async_smem();
              __syncwarp();
              mbar_arrive_if(lane == 0, sb + B_PTOK);
              if (elect_one()) {
                bulk_s2s(peer1 + row, sb + row, 640, peer1 + B_PTOK);
                bulk_s2s(peer2 + row, sb + row, 640, peer2 + B_PTOK);
              }
            }
          }
        }
      }
      const uint32_t* const src = (const uint32_t*)((char*)(g_part + (size_t)((l * 2 + (s & 1)) * PART_RING)) + src_off);
      uint32_t* const dst = (uint32_t*)pin((char*)(g_mem + l * 1024 + (~s & 1) * 512) + dst_off, lane);
      {
        const uint32_t d1 = prm.d1[cta / 24 + ((info >> 5) & 4)];
        if (warp == 3) {
          mbar_wait(sb + B_OB, par);
          mbar_arrive_if(lane == 0, sb + B_GATE);
          sts32(sb + SM_TOPI + par * 4, clk());
          __syncwarp();
          mbar_arrive_if(lane == 0, sb + B_OPI + par * 8);
          TRACE(true, n, 0, gtl());
        }
        const bool reduce = cta < 88 && s != NSEG - 1;
        if (reduce || warp == 0) mbar_wait(sb + B_OPI + par * 8, (n >> 1) & 1);
        if (!reduce) continue;
        mbar_wait(sb + B_RFREE, (nred++ & 1) ^ 1);
        mbar_wait(sb + B_GATE, 1);
        if (d1) spin(d1);
      }
      {
        uint32_t g = 0;
        float2 u;
        PROF(14);
        if (!split) {
          u = poll_sum<8>(src, ~(s >> 1), even, g);
        } else {
          u = poll_sum<12>(src, ~(s >> 1), even, g);
          u.x += __shfl_xor_sync(~0u, u.x, 2);
          u.y += __shfl_xor_sync(~0u, u.y, 2);
        }
        PROF(18);
        if (warp != 1) {
          asm volatile("st.shared.v2.f32 [%0], {%1,%2};" ::"r"(red), "f"(u.x), "f"(u.y) : "memory");
          bar_arrive(3, 128);
        } else {
          bar_sync(3, 128);
          const uint2 o0 = lds64(red), o1 = lds64(red + 256), o2 = lds64(red + 512);
          const uint32_t w = movm(pack2((u.x + __uint_as_float(o0.x)) + (__uint_as_float(o1.x) + __uint_as_float(o2.x)),
                                        (u.y + __uint_as_float(o0.y)) + (__uint_as_float(o1.y) + __uint_as_float(o2.y))));
          if (!split || lane < 16) {
            st_rlx1(dst, w);
            st_rlx1(dst + ((s & 1) ? 2048 : -2048), ~0u);
          }
          mbar_arrive_if(lane == 0, sb + B_RFREE);
        }
        PROF(19);
        PROFV(2, g);
        TRACE(warp == 1, n, 1, gtl());
        TRACE(g, n, 2, g);
      }
    }
  } else {
    asm volatile("setmaxnreg.dec.sync.aligned.u32 %0;" ::"n"(RG3));
    asm volatile("barrier.cluster.wait.acquire.aligned;" ::: "memory");
    const uint32_t chk = lane * 32 + ((lane >> 2) << 2);
    const uint32_t bar = sb + B_MTRY + 8 * warp;
    uint32_t mph = 0, waited = 0, pub = 0, pph = 0, nsolo = 0;
    auto publish = [&](uint32_t upto) {
#pragma unroll 1
      for (; pub < upto; pub++) {
        const uint32_t e = prm.slot[pub], l = (e >> 6) & 1;
        if (warp == 3 && (e >> 16)) {
          mbar_wait_wd(sb + B_OTOK + l * 8, (pph >> l) & 1);
          pph ^= 1 << l;
          if (elect_one()) red_rel(&g_cnt[(e >> 16) * CSTRIDE], 1);
        }
      }
    };
#pragma unroll 1
    for (int m = 0; m < nslots; m++) {
      const uint32_t info = prm.slot[m], prod = (info >> 8) & 255, ls = info & 127;
      uint32_t g = 0;
#pragma unroll 1
      for (; waited < prod && waited + 1 < m; waited++) mbar_wait_wd(sb + B_OPI + (waited & 1) * 8, (waited >> 1) & 1);
      uint32_t t0 = lds32(sb + SM_TOPI + (~waited & 1) * 4);
      publish(waited);
      if ((ls & 3) == 0) {
        while (__any_sync(~0u, ld_acq(&g_cnt[(C_XN + (ls >> 2)) * CSTRIDE]) < XN_TARGET)) guard(g);
        fence_async_global();
      }
#pragma unroll 1
      for (uint32_t c = warp; c < 5; c += 4) {
        const uint32_t dst = sb + SM_H + c * 10240, full = sb + B_HFULL + 8 * c;
        const uint4* src = g_mem + (c * 2048 + (ls >> 6) * 1024 + (ls & 1) * 512 + prm.moff);
        const uint32_t d = prod ? prm.d2[(m - prod) * 5 + c] : 0;
        const uint4* tok = g_xn + (size_t)(ls * 2560 + c * 512);
        const uint32_t pp = (m & 1) ^ 1;
        const bool single = waited < prod;
        mbar_wait_wd(full, pp);
        const bool solo = SOLO && m > 0 && prod == m;
        const uint32_t tokb = solo ? sb + B_PVI : full;
        if (solo && c < 4) mbar_wait_wd(tokb, (nsolo++ & 1) ^ 1);
        mbar_expect_if(lane < 2 && !(solo && c == 4 && lane == 0), lane ? bar : tokb, lane ? 2048 : 8192);
        if (!single) while (__any_sync(~0u, clk() - t0 < d)) {}
        if (c >= 2) mbar_wait_wd(sb + B_HEMPTY + 8 * c, pp);
        mbar_wait_wd(sb + (c < 2 ? B_HEMPTY + 8 * c : c == 2 && !single ? B_PMEM : B_OB), pp);
        if ((c != 2 || single) && !(solo && c == 4)) { if (elect_one()) bulk_g2s(dst + 2048, tok, 8192, tokb); }
        if (single) {
          mbar_wait_wd(sb + B_OPI + (waited & 1) * 8, (waited >> 1) & 1);
          waited++;
          t0 = lds32(sb + SM_TOPI + (~waited & 1) * 4);
          if (solo && c == 0 && elect_one()) {
            mbar_expect(tokb, 8192);
            bulk_g2s(dst + 4 * 10240 + 2048, tok + 2048, 8192, tokb);
          }
          publish(waited);
          while (__any_sync(~0u, clk() - t0 < d)) {}
        }
        else if (c < 2) spin(prm.dh);
        if (elect_one()) bulk_g2s(dst, src, 2048, bar);
        if (c == 2 && !single) {
          mbar_wait_wd(sb + B_OB, pp);
          if (elect_one()) bulk_g2s(dst + 2048, tok, 8192, full);
        }
        g = 0;
        while (true) {
          mbar_wait_wd(bar, mph);
          mph ^= 1;
          const uint32_t v0 = lds32(dst + chk), v1 = lds32(dst + chk + 1024);
          if (__all_sync(~0u, v0 != ~0u && v1 != ~0u)) break;
          if (elect_one()) {
            mbar_expect(bar, 2048);
            bulk_g2s(dst, src, 2048, bar);
          }
          guard(g);
        }
        mbar_arrive_if(lane == 0, full, solo ? 2 : 1);
        TRACE(c < 2, m, 3 + 2 * c, gtl());
        TRACE(c < 2, m, 4 + 2 * c, g);
      }
    }
    publish(nslots);
    if (warp == 0) mbar_wait_wd(sb + B_END, 0);
  }
  __syncwarp();
  if (wid != 12 && lane0 == 0) mbar_arrive(sb + B_END);
  cluster_sync();
}
__device__ uint32_t g_xa[NBLK * 10 * 4096];
__device__ uint32_t g_h[NBLK * 24 * 4096];

enum { T_A = 0, T_F1 = 1, T_U = 2, T_D = 3, T_F2 = 4, T_NONE = 7 };
__host__ __device__ constexpr int c_phase(int type, int lb) { return C_O + type * 32 + lb; }
constexpr int C_TICKET = c_phase(5, 0), C_EXIT = C_TICKET + 1, C_USED = C_HALF + 2 * NBLK;
constexpr int G_NST = 7;
constexpr uint32_t GS_RED = G_NST * 32768, GS_BAR = GS_RED + 1088, G_SMEM = GS_BAR + 224;
constexpr uint32_t GB_FULL = GS_BAR, GB_EMPTY = GS_BAR + 64, GB_ORD = GS_BAR + 128, GB_READY = GS_BAR + 144, GB_ACK = GS_BAR + 152, GB_GATE = GS_BAR + 160, GB_SIG = GS_BAR + 176, GB_SACK = GS_BAR + 192,
                   GS_SIG = GS_BAR + 208, GS_COL = GS_BAR + 216;
#define FPL 6
constexpr int NF = 16;
constexpr int G_EARLY = 36;
constexpr int G_LATE = 96, PL = 6, ML = 8, DL = 24, TL = 10;
constexpr int GRC = 112, GRP = 32;
constexpr uint32_t E_UP = 1u << 8, E_HALF = 1u << 28, E_GRP = 1u << 29, E_HAND = 1u << 30, E_EXCL = 1u << 31;

struct GParams {
  __nv_bfloat16* out;
  const uint32_t* x;
  int moff, gd;
  int pend;
  uint8_t perm[G_EARLY], first[9];
  uint8_t need[5][2 * NBLK];
  uint32_t tab[G_EARLY * (PL + ML + DL) + G_LATE * TL];
};
constexpr int EL = PL + ML + DL, TAB_TAIL = G_EARLY * EL;
struct GIter {
  int p, left, period;
  uint32_t e, type, lb, n0, kb0, nkb;
  bool gemm, valid;
  DI GIter(const GParams& prm, int col) {
    if (col < G_EARLY) { p = col * EL; left = PL; period = 0; }
    else { p = TAB_TAIL + (col - G_EARLY) * TL; left = TL; period = prm.pend; }
  }
  DI bool next(const GParams& prm, int col) {
    do {
      if (left == 0) {
        if (++period > prm.pend) return false;
        left = period < prm.pend ? ML : DL;
        if (period > 1 && period < prm.pend) p -= ML;
      }
      e = prm.tab[p++]; left--;
    } while ((e & 7) == T_NONE);
    const int b = (e >> 4) & 15, blk = period < prm.pend ? period - b : b;
    type = e & 7; valid = blk >= 0; lb = (e & 8) * 2 + (blk & 15); n0 = (e >> 9) & 127; kb0 = (e >> 16) & 127;
    gemm = type != T_F1 && type != T_F2;
    nkb = valid ? (e >> 23) & 31 : 0;
    return true;
  }
  DI int id_(int pend) const { return period < pend ? period * 10 + ML - left : 160 + DL - left; }
};

#define GLOG(nt, i, v)
template <int TA> DI void wg_ss128(float* d, uint64_t da, uint64_t db, int sc) {
  asm volatile("{.reg .pred p; setp.ne.b32 p, %66, 0;\n"
               "wgmma.mma_async.sync.aligned.m64n128k16.f32.bf16.bf16 "
               "{%0,%1,%2,%3,%4,%5,%6,%7,%8,%9,%10,%11,%12,%13,%14,%15,%16,%17,%18,%19,%20,%21,%22,%23,%24,%25,%26,%27,%28,%29,%30,%31,"
               "%32,%33,%34,%35,%36,%37,%38,%39,%40,%41,%42,%43,%44,%45,%46,%47,%48,%49,%50,%51,%52,%53,%54,%55,%56,%57,%58,%59,%60,%61,%62,%63}, "
               "%64, %65, p, 1, 1, %67, 1;}"
               : ACC16(d, 0), ACC16(d, 16), ACC16(d, 32), ACC16(d, 48) : "l"(da), "l"(db), "r"(sc), "n"(TA));
}

template <int TA> DI void g_mainloop(float* acc, uint32_t sb, uint32_t hand, uint32_t gate, int nkb, int cw, int lane, uint32_t st, uint32_t ph) {
  const uint64_t da0 = (TA ? mkdesc(SMEM0, 4096, 512, 2) : mkdesc(SMEM0, 128, 1024, 0)) + (cw >> 2) * 512;
  const uint64_t db0 = mkdesc(SMEM0 + 16384, 8192, 1024, 1);
  uint32_t prev = 0;
#pragma unroll 1
  for (int kb = 0; kb < nkb; kb++) {
    mbar_wait(sb + GB_FULL + 8 * st, ph);
    mbar_wait(gate, 1);
    const uint64_t da = da0 + st * 2048, db = db0 + st * 2048;
    wg_fence();
#pragma unroll
    for (int k = 0; k < 4; k++) wg_ss128<TA>(acc, da + k * (TA ? 64 : 16), db + k * 128, 1);
    wg_commit();
    mbar_arrive_if(hand && kb == nkb - 1 && lane == 0, hand);
    wg_wait<1>();
    mbar_arrive_if(kb > 0 && lane == 0, sb + GB_EMPTY + 8 * prev);
    prev = st;
    if (++st == G_NST) { st = 0; ph ^= 1; }
  }
  wg_wait<0>();
  reg_fence<64>(acc);
  mbar_arrive_if(lane == 0, sb + GB_EMPTY + 8 * prev);
}

__global__ void __launch_bounds__(640, 1)
g_kernel(const __grid_constant__ CUtensorMap mapWo, const __grid_constant__ CUtensorMap mapWg, const __grid_constant__ CUtensorMap mapWu,
         const __grid_constant__ CUtensorMap mapWd, const __grid_constant__ GParams prm) {
  const uint32_t sb = smem_base();
  const int wid = __shfl_sync(~0u, threadIdx.x >> 5, 0), lane = threadIdx.x & 31;
  if (threadIdx.x == 0) {
    if ((sb & 0x3FFFF) != SMEM0) __trap();
    {
      uint32_t sm; asm volatile("mov.u32 %0, %%smid;" : "=r"(sm));
      uint32_t* const tk = &g_cnt[C_TICKET * CSTRIDE];
      uint32_t c = atomicAdd(tk, 1);
      if (c < G_EARLY) {
        const uint32_t k = sm < 64 ? (sm >> 1) & 7 : sm < 120 ? 1 + ((sm - 64) >> 1) % 7 : sm < 124 ? 1 + ((sm >> 1) & 1) : 0;
        const uint32_t t = atomicAdd(tk + 1 + k, 1);
        atomicAdd(tk + 9, 1);
        if (t < prm.first[k + 1] - prm.first[k]) c = prm.perm[prm.first[k] + t];
        else {
          uint32_t o = atomicAdd(tk + 10, 1), g = 0;
          while (ld_acq(tk + 9) < G_EARLY) guard(g);
          for (int j = 0; j < 8; j++)
            for (uint32_t i = prm.first[j] + ld_acq(tk + 1 + j); i < prm.first[j + 1]; i++) if (o-- == 0) c = prm.perm[i];
        }
      }
      sts32(sb + GS_COL, c);
    }
    for (int i = 0; i < G_NST; i++) { mbar_init(sb + GB_FULL + 8 * i, 1); mbar_init(sb + GB_EMPTY + 8 * i, 8); }
    mbar_init(sb + GB_ORD, 8); mbar_init(sb + GB_ORD + 8, 8); mbar_init(sb + GB_READY, 1); mbar_init(sb + GB_ACK, 1);
    mbar_init(sb + GB_GATE, 1); mbar_init(sb + GB_GATE + 8, 1);
    mbar_init(sb + GB_SIG, 8); mbar_init(sb + GB_SIG + 8, 8); mbar_init(sb + GB_SACK, 1); mbar_init(sb + GB_SACK + 8, 1);
    fence_async_smem();
  }
  __syncthreads();
  const int col = __shfl_sync(~0u, lds32(sb + GS_COL), 0);

  if (wid >= 16) {
    GIter t(prm, col);
    asm volatile("setmaxnreg.dec.sync.aligned.u32 %0;" ::"n"(GRP));
    uint32_t st = 0, ph = 1, k = 0;
    if (wid == 16) {
      while (t.next(prm, col)) {
        const CUtensorMap* m0 = t.type == T_A ? &mapWo : t.type == T_U ? &mapWg : &mapWd;
        const CUtensorMap* m1 = t.type == T_U ? &mapWu : m0;
        const int c0 = t.type == T_U ? t.n0 * 64 : (t.n0 & 7) * 128, c1 = t.type == T_U ? c0 : c0 + 64;
        if ((t.e & (E_HALF | E_UP)) == E_UP) poll_ge(&g_cnt[c_phase(t.type, t.lb) * CSTRIDE], prm.need[t.type][t.lb]);
#pragma unroll 1
        for (uint32_t kb = t.kb0; kb < t.kb0 + t.nkb; kb++) {
          mbar_wait(sb + GB_EMPTY + 8 * st, ph);
          if (elect_one()) {
            const uint32_t full = sb + GB_FULL + 8 * st, dst = sb + st * 32768;
            mbar_expect(full, (t.e & E_HALF) ? 24576 : 32768);
            tma_2d(dst + 16384, m0, c0, kb * 64, full);
            tma_2d(dst + 24576, m1, c1, kb * 64, full);
          }
          if (++st == G_NST) { st = 0; ph ^= 1; }
        }
      }
    } else if (wid == 17) {
      while (t.next(prm, col)) {
        if (!t.nkb) continue;
        const char* asrc = t.type == T_A ? (const char*)g_oT + (size_t)t.lb * (96 * 16384)
                         : t.type == T_U ? (const char*)g_xa + (size_t)(t.lb & 15) * (10 * 16384) : (const char*)g_h + (size_t)(t.lb & 15) * (24 * 16384);
        const uint32_t up = (t.e & E_HALF) ? (t.e & E_UP) * 32 : 0;
        GLOG(t.id_(prm.pend), 1, gtime());
        mbar_wait(sb + GB_READY, k & 1);
        mbar_arrive_if(lane == 0, sb + GB_ACK);
        k++;
#pragma unroll 1
        for (uint32_t kb = t.kb0; kb < t.kb0 + t.nkb; kb++) {
          mbar_wait(sb + GB_EMPTY + 8 * st, ph);
          if (elect_one()) bulk_g2s(sb + st * 32768 + up, asrc + (size_t)kb * 16384 + up, (t.e & E_HALF) ? 8192 : 16384, sb + GB_FULL + 8 * st);
          if (++st == G_NST) { st = 0; ph ^= 1; }
        }
      }
    } else if (wid == 18) {
      while (t.next(prm, col)) {
        if (!t.nkb) continue;
        const bool lower = t.type == T_A && (t.e & (E_HALF | E_UP)) == E_HALF;
        poll_ge(&g_cnt[(lower ? C_HALF + t.lb : c_phase(t.type, t.lb)) * CSTRIDE], prm.need[t.type][t.lb]);
        fence_async_global();
        GLOG(t.id_(prm.pend), 2, gtime());
        mbar_wait(sb + GB_ACK, (k & 1) ^ 1);
        mbar_arrive_if(lane == 0, sb + GB_READY);
        k++;
      }
    } else {
      uint32_t live = 3, par = 0, g = 0;
      while (live) {
        const bool ev = lane < 2 && ((live >> lane) & 1) && mbar_test(sb + GB_SIG + 8 * lane, (par >> lane) & 1);
        const uint32_t evs = __ballot_sync(~0u, ev);
        if (!evs) { guard(g); __nanosleep(20); continue; }
        const uint32_t msg = ev ? lds32(sb + GS_SIG + 4 * lane) : 0;
        mbar_arrive_if(ev, sb + GB_SACK + 8 * lane);
        mbar_arrive_if(msg >> 31, sb + GB_GATE + 8 * lane);
        if (msg) red_rel(&g_cnt[(msg & 0xffff) * CSTRIDE], (msg >> 16) & 255);
        par ^= evs;
        live &= ~__ballot_sync(~0u, ev && !msg);
        g = 0;
      }
      asm volatile("griddepcontrol.wait;" ::: "memory");
      if (col < 80 && lane < 16) g_mem[(col >> 4) * 2048 + (lane >> 3) * 1024 + 512 + prm.moff + (col & 15) * 8 + (lane & 7)] = make_uint4(~0u, ~0u, ~0u, ~0u);
      uint32_t last = 0;
      if (lane == 0) last = atomicAdd(&g_cnt[C_EXIT * CSTRIDE], 1) == gridDim.x - 1;
      if (__shfl_sync(~0u, last, 0)) {
        g_cnt[C_TICKET * CSTRIDE + lane] = 0;
        for (int i = lane; i < C_USED; i += 32) g_cnt[i * CSTRIDE] = 0;
      }
    }
  } else {
    asm volatile("setmaxnreg.inc.sync.aligned.u32 %0;" ::"n"(GRC));
    const int cw = wid & 7, wk = wid >> 3;
    GIter t(prm, col);
    uint32_t pos = 0, seen = 0, waited = 0;
    uint32_t nsig = 0;
    auto signal = [&](uint32_t msg) {
      mbar_wait(sb + GB_SACK + 8 * wk, (nsig++ & 1) ^ 1);
      if (cw == 0) sts32(sb + GS_SIG + 4 * wk, msg);
      __syncwarp();
      mbar_arrive_if(lane == 0, sb + GB_SIG + 8 * wk);
    };
    if (col < G_EARLY) {
      spin(prm.gd);
#pragma unroll 1
      for (int rg = 96 + col * 2 + wk; rg < 256; rg += 2 * G_EARLY) {
        uint32_t a[10];
        const uint32_t* src = prm.x + (size_t)(rg * 8 + (lane >> 2)) * (DM / 2) + cw * 40 + (lane & 3);
#pragma unroll
        for (int i = 0; i < 10; i++) a[i] = __ldg(src + i * 4);
        first_ln(a, rg, sb + GS_RED + wk * 512, cw, lane, 1 + wk);
        signal((C_XN + (rg >> 4)) | ((XN_TARGET / NF) << 16));
        bar_sync(1 + wk, 256);
      }
    }
    while (t.next(prm, col)) {
      const uint32_t pos0 = pos;
      pos = (pos + t.nkb) % (2 * G_NST);
      if (((t.e >> 29) & 1) != wk) { seen += (t.e >> 30) & 1; continue; }
      const uint32_t type = t.type, blk = t.lb & 15, layer = t.lb >> 4, n0 = t.n0;
      if (cw == 0 && t.valid) GLOG(t.id_(prm.pend), 0, 0x80000000u | type | (t.lb << 3) | (n0 << 8) | (t.nkb << 16));
      if (!t.gemm) {
        if (!t.valid) continue;
        const int rg = blk * 16 + n0;
        float4 v[5];
        const int off = (n0 * 40 + cw * 5) * 32 + lane, npl = t.kb0;
        const uint2* src = acc_planes(t.lb, type == T_F2) + off;
        if (cw == 0) {
          poll_ge(&g_cnt[c_phase(type, t.lb) * CSTRIDE], prm.need[type][t.lb]);
          mbar_arrive_if((t.e & E_EXCL) && lane == 0, sb + GB_GATE + 8 * wk);
          GLOG(t.id_(prm.pend), 2, gtime()); GLOG(t.id_(prm.pend), 3, gtime());
        }
        bar_sync(1 + wk, 256);
        {
          const uint32_t eye = (lane >> 3) == (lane & 3) ? ((lane & 4) ? 0x3f800000u : 0x00003f80u) : 0u;
#pragma unroll
          for (int i = 0; i < 5; i++) v[i] = make_float4(0.f, 0.f, 0.f, 0.f);
#pragma unroll 1
          for (int p0 = 0; p0 < npl; p0 += FPL) {
            uint32_t r[FPL / 2][5][4];
#pragma unroll
            for (int p = 0; p < FPL; p++)
#pragma unroll
              for (int i = 0; i < 5; i++) {
                const uint2 w = p0 + p < npl ? __ldcg(src + (size_t)(p0 + p) * PLANE + i * 32) : make_uint2(0, 0);
                r[p >> 1][i][(p & 1) * 2] = w.x; r[p >> 1][i][(p & 1) * 2 + 1] = w.y;
              }
#pragma unroll
            for (int p = 0; p < FPL / 2; p++) {
              if (p0 + 2 * p >= npl) break;
              if (t.e & E_EXCL) {
#pragma unroll
                for (int i = 0; i < 5; i++) mma16816(&v[i].x, r[p][i], eye, eye);
              } else {
#pragma unroll
                for (int i = 0; i < 5; i++) {
                  const uint32_t* w = r[p][i];
                  v[i].x += blo(w[0]) + blo(w[2]); v[i].y += bhi(w[0]) + bhi(w[2]); v[i].z += blo(w[1]) + blo(w[3]); v[i].w += bhi(w[1]) + bhi(w[3]);
                }
              }
            }
          }
        }
        if (type == T_F2 && layer == 1) {
          uint2* dst = (uint2*)prm.out + (size_t)(rg * 8 + (lane >> 2)) * (DM / 4) + cw * 20 + (lane & 1) * 2 + ((lane >> 1) & 1);
#pragma unroll
          for (int i = 0; i < 5; i++) {
            const uint32_t a = pack2(v[i].x, v[i].y), b = pack2(v[i].z, v[i].w);
            const uint32_t o = __shfl_xor_sync(~0u, (lane & 1) ? a : b, 1);
            dst[i * 4] = (lane & 1) ? make_uint2(o, b) : make_uint2(a, o);
          }
        } else {
          uint2* nx = (type == T_F1 ? acc_planes(t.lb, 1) : acc_planes(NBLK + blk, 0)) + off;
#pragma unroll
          for (int i = 0; i < 5; i++) {
            const uint2 w = make_uint2(pack2(v[i].x, v[i].y), pack2(v[i].z, v[i].w));
            nx[i * 32] = w;
            v[i] = make_float4(blo(w.x), bhi(w.x), blo(w.y), bhi(w.y));
          }
          float mean, rstd;
          ln_stats(v, sb + GS_RED + wk * 512, cw, lane, 1 + wk, mean, rstd);
          if (type == T_F2) store_img<4, 2048>(xn_row_group(1, rg) + lane, v, cw, mean, rstd);
          else store_img<3, 4096>(g_xa + (size_t)(blk * 10 * 4096 + n0 * 256) + lane, v, cw, mean, rstd);
        }
      } else {
        float acc[64];
#pragma unroll
        for (int j = 0; j < 64; j++) acc[j] = 0.f;
        if (waited != seen) { mbar_wait(sb + GB_ORD + 8 * (wk ^ 1), waited & 1); waited++; }
        const uint32_t hand = (t.e & E_HAND) ? sb + GB_ORD + 8 * wk : 0;
        if (!t.valid) { mbar_arrive_if(hand && lane == 0, hand); continue; }
        if (cw == 0) GLOG(t.id_(prm.pend), 3, gtime());
        const uint32_t ph = pos0 >= G_NST, st = pos0 - ph * G_NST, early = (t.e & E_EXCL) ? 0 : hand;
        const bool idle = (t.e & E_HALF) && ((t.e >> 8) & 1) != (cw >> 2);
        if (idle) {
          uint32_t s2 = st, p2 = ph;
#pragma unroll 1
          for (uint32_t kb = 0; kb < t.nkb; kb++) {
            mbar_wait(sb + GB_FULL + 8 * s2, p2);
            mbar_arrive_if(lane == 0, sb + GB_EMPTY + 8 * s2);
            if (++s2 == G_NST) { s2 = 0; p2 ^= 1; }
          }
          mbar_arrive_if(early && lane == 0, early);
        } else if (type == T_A) g_mainloop<1>(acc, sb, early, sb + GB_GATE + 8 * (wk ^ 1), t.nkb, cw, lane, st, ph);
        else g_mainloop<0>(acc, sb, early, sb + GB_GATE + 8 * (wk ^ 1), t.nkb, cw, lane, st, ph);
        if (cw == 0) GLOG(t.id_(prm.pend), 4, gtime());
        if (idle) {
        } else if (type == T_U) {
          uint32_t* dst = g_h + (size_t)((blk * 24 + n0) * 4096 + cw * 512) + lane;
#pragma unroll
          for (int j = 0; j < 8; j++) {
            float h[4];
#pragma unroll
            for (int e = 0; e < 4; e++) {
              float th;
              asm("tanh.approx.f32 %0, %1;" : "=f"(th) : "f"(0.5f * acc[4 * j + e]));
              h[e] = acc[32 + 4 * j + e] * fmaf(th, 0.5f, 0.5f);
            }
            dst[j * 32] = pack2(h[0], h[1]);
            dst[j * 32 + 256] = pack2(h[2], h[3]);
          }
        } else {
          uint2* dst = acc_planes(t.lb, type == T_D) + (size_t)((1 + (n0 >> 3)) * PLANE + (2 * cw * 40 + (n0 & 7) * 8) * 32) + lane;
#pragma unroll
          for (int j = 0; j < 16; j++) {
            const float* a = acc + (j >> 1) * 8 + (j & 1) * 2;
            dst[(j >> 1) * 32 + (j & 1) * 1280] = make_uint2(pack2(a[0], a[1]), pack2(a[4], a[5]));
          }
        }
        mbar_arrive_if(hand != early && lane == 0, hand);
      }
      if (cw == 0) GLOG(t.id_(prm.pend), 5, gtime());
      if (cw == 0) GLOG(t.id_(prm.pend), 6, gtime());
      if (type == T_F2 && layer == 1) mbar_arrive_if((t.e & E_EXCL) && cw == 0 && lane == 0, sb + GB_GATE + 8 * wk);
      else
        signal((type != T_F2 ? c_phase(type + 1, t.lb) | (1 << 16) : (C_XN + NBLK + blk) | ((XN_TARGET / NF) << 16)) | (t.gemm ? 0 : t.e & E_EXCL));
    }
    signal(0);
  }
}

typedef CUresult (*EncodeFn)(CUtensorMap*, CUtensorMapDataType, cuuint32_t, void*, const cuuint64_t*, const cuuint64_t*, const cuuint32_t*,
                             const cuuint32_t*, CUtensorMapInterleave, CUtensorMapSwizzle, CUtensorMapL2promotion, CUtensorMapFloatOOBfill);
static CUtensorMap make_map(EncodeFn fn, const void* p, uint64_t inner, uint64_t outer, uint32_t bi, uint32_t bo) {
  CUtensorMap m;
  cuuint64_t dims[2] = {inner, outer}, str[1] = {inner * 2};
  cuuint32_t box[2] = {bi, bo}, es[2] = {1, 1};
  fn(&m, CU_TENSOR_MAP_DATA_TYPE_BFLOAT16, 2, (void*)p, dims, str, box, es, CU_TENSOR_MAP_INTERLEAVE_NONE, CU_TENSOR_MAP_SWIZZLE_128B,
     CU_TENSOR_MAP_L2_PROMOTION_L2_256B, CU_TENSOR_MAP_FLOAT_OOB_FILL_NONE);
  return m;
}
struct Tune {
  int lag = 11, excl = 7, gonly = 0, xl = 1, ronly = 0, pn = 30;
  int da = 100, db = 350, dc = 650, dd = 650, d2 = 2000, p1 = 400, p2 = 800;
  int ea = 60, eb = 310, ec = 550, ed = 550, e2 = 2200, q1 = 200, q2 = 400, d3 = 60, moff = 192, ds = 400, dh = 60, pa = 0, pb = 0, pc = 0, pd = 0, pe = 0, pf = 0, pg = 0, ph = 0, hold = 1, wpf = 4, gd = 22000, dq = 600;
};
static void fill_r(RParams& p, const Tune& t, int lag, int n0, int n1) {
  r_fill_desc(p);
  p.nslots = 0; p.d3 = t.d3; p.pn = t.pn; p.moff = t.moff; p.ds = t.ds; p.dh = t.dh; p.dq = t.dq;
  for (int c = 0; c < 5; c++) { p.d2[c] = t.d2 + (c == 0 ? 0 : c < 3 ? t.p1 : t.p2); p.d2[5 + c] = t.e2 + (c == 0 ? 0 : c < 3 ? t.q1 : t.q2); }
  const int d1[8] = {t.da, t.db, t.dc, t.dd, t.ea, t.eb, t.ec, t.ed};
  for (int i = 0; i < 8; i++) p.d1[i] = d1[i];
  int last[2] = {0, 0}, n = 0;
  for (int s0 = 0; s0 < NSEG + lag; s0++)
    for (int l = 0; l < 2; l++) {
      const int s = l ? s0 - lag : s0;
      if (s < 0 || s >= NSEG) continue;
      if (n >= n0 && n < n1) { p.slot[p.nslots] = s | (l << 6) | (last[l] << 8) | (((s & 3) == 3 ? C_O + l * NBLK + s / 4 : s == (l ? 61 : 1) ? C_HALF + l * NBLK + s / 4 : 0) << 16); last[l] = ++p.nslots; }
      n++;
    }
  for (int i = 0; i + 1 < p.nslots; i++) if (((p.slot[i] ^ p.slot[i + 1]) >> 6) & 1) p.slot[i] |= 128;
}
static uint32_t g_entry(int grp, int type, int layer, int blk, int i, int ks) {
  int n0 = i, kb0 = 0, kb1 = type == T_U ? 10 : 0;
  if (type == T_F1 || type == T_F2) kb0 = kb1 = ks + 1;
  if (type == T_A || type == T_D) {
    const int KB = type == T_A ? 96 : 24, sp = i / 5;
    n0 = i % 5 | (sp << 3); kb0 = sp * KB / ks; kb1 = (sp + 1) * KB / ks;
  }
  return type | (layer << 3) | (blk << 4) | (n0 << 9) | (kb0 << 16) | ((kb1 - kb0) << 23) | (grp ? E_GRP : 0);
}
static bool g_is_gemm(uint32_t e) { return (e & 7) == T_A || (e & 7) == T_U || (e & 7) == T_D; }
static void g_handover(uint32_t* e, int len) {
  uint32_t next = 0;
  for (int i = len - 1; i >= 0; i--)
    if (g_is_gemm(e[i])) { if ((e[i] & E_GRP) != next) e[i] |= E_HAND; next = e[i] & E_GRP; }
}
struct GList {
  GParams& g; uint32_t* tab; int ncol, stride, len, n[G_LATE], load[G_LATE], grp[G_LATE];
  GList(GParams& g_, uint32_t* t, int nc, int st, int l) : g(g_), tab(t), ncol(nc), stride(st), len(l) { for (int c = 0; c < nc; c++) { n[c] = load[c] = 0; grp[c] = 1; } }
  void add(int type, int lb, int ks, int c0, int c1, uint32_t flags = 0, int i0 = 0, int i1 = 999, int step = 1) {
    const int half = (flags & E_HALF) != 0, ln = type == T_F1 || type == T_F2;
    const int cnt = (type == T_U ? 24 : ln ? NF : 5 * ks) << half;
    if (type < T_F2) g.need[type + 1][lb] = cnt;
    int used[G_LATE] = {0};
    for (int i = i0; i < cnt && i < i1; i += step) {
      int best = c0;
      for (int c = c0; c < c1; c++) if (used[c] < used[best] || (used[c] == used[best] && load[c] < load[best])) best = c;
      used[best]++;
      if (!ln) grp[best] ^= 1;
      const uint32_t e = g_entry(grp[best], type, lb >> 4, lb & 15, i >> half, ks) | flags | (ln ? E_EXCL : 0) | ((i & half) ? E_UP : 0);
      if (n[best] >= len) abort();
      tab[best * stride + n[best]++] = e;
      load[best] += (((e >> 23) & 31) >> half) + 2;
    }
  }
  void finish() { for (int c = 0; c < ncol; c++) g_handover(tab + c * stride, len); }
};
static void fill_g(GParams& g, const Tune& t, void* out) {
  g.out = (__nv_bfloat16*)out;  g.pend = NBLK - 1;
  for (int b = 0; b < 2 * NBLK; b++) {
    g.need[T_A][b] = 96; g.need[T_F1][b] = 20; g.need[T_U][b] = NF; g.need[T_D][b] = 32; g.need[T_F2][b] = 15;
  }
  {
    const uint8_t perm[G_EARLY] = {0, 1, 2, 3, 16, 17, 18, 19, 34, 35, 4, 20, 21, 15, 22, 23, 5, 6, 7, 8, 9, 24, 25, 26, 10, 11, 12, 13, 14, 27, 28, 29, 30, 31, 32, 33};
    const uint8_t first[9] = {0, 10, 13, 16, 20, 24, 28, 32, 36};
    const int* pk = &t.pa;
    for (int i = 0; i < G_EARLY; i++) g.perm[i] = t.pa ? (pk[i / 5] >> (6 * (i % 5))) & 63 : perm[i];
    for (int i = 0; i < 9; i++) g.first[i] = first[i];
  }
  for (uint32_t& e : g.tab) e = T_NONE;
  GList pr(g, g.tab, G_EARLY, EL, PL);
  pr.add(T_A, 0, 7, 1, 36, E_HALF, 0, 999, 2); pr.add(T_A, 0, 7, 1, 36, E_HALF, 1, 999, 2); pr.add(T_F1, 0, 7, 20, 36); pr.add(T_U, 0, 0, 12, 36);
  pr.add(T_D, 0, 3, 20, 36); pr.add(T_F2, 0, 3, 20, 36);
  pr.finish();
  const int d = 3;
  const uint32_t xa = (t.excl & 1) ? E_EXCL : 0, xu = (t.excl & 2) ? E_EXCL : 0, xd = (t.excl & 4) ? E_EXCL : 0;
  for (int c = 0; c < G_EARLY; c++) {
    uint32_t* e = g.tab + c * EL + PL;
    if (c < 20) {
      *e++ = g_entry(0, T_A, 0, 0, c, 4) | xa;
      if (c < NF) *e++ = g_entry(0, T_F1, 0, 0, c, 4) | ((t.xl & 1) ? E_EXCL : 0);
      *e++ = g_entry(1, T_A, 1, d, c, 4);
      if (c >= 20 - NF) *e++ = g_entry(1, T_F1, 1, d, c - (20 - NF), 4);
    } else {
      const int j = c - 20;
      const uint32_t hf = E_HALF | ((j & 1) ? E_UP : 0);
      *e++ = g_entry(0, T_U, 0, 0, j, 0);
      *e++ = g_entry(1, T_U, 0, 0, 16 + j / 2, 0) | hf | xu;
      *e++ = g_entry(0, T_U, 1, d + 1, 16 + j / 2, 0) | hf;
      if (j < 15) *e++ = g_entry(1, T_D, 0, 0, j, 3) | xd;
      *e++ = g_entry(1, T_F2, 0, 0, j, 3) | ((t.xl & 2) ? E_EXCL : 0);
      if (j < 15) *e++ = g_entry(0, T_D, 1, d + 2, j, 3);
      *e++ = g_entry(0, T_U, 1, d + 1, j, 0);
      *e++ = g_entry(1, T_F2, 1, d + 2, j, 3);
    }
    g_handover(g.tab + c * EL + PL, ML);
  }
  GList dr(g, g.tab + PL + ML, G_EARLY, EL, DL);
  GList tl(g, g.tab + TAB_TAIL, G_LATE, TL, TL);
  const int L1 = NBLK;
  auto ufull = [&](int lb) { dr.add(T_U, lb, 0, 20, 36, 0, 0, 16); g.need[T_D][lb] = 32; };
  auto uhalf = [&](int lb) { dr.add(T_U, lb, 0, 20, 36, E_HALF, 32); g.need[T_D][lb] = 32; };
  dr.add(T_A, 15, 4, 0, 20, E_EXCL);
  dr.add(T_F1, 15, 4, 0, 16);
  dr.add(T_U, 15, 0, 12, 36, E_EXCL);
  dr.add(T_A, L1 + 12, 4, 0, 20); dr.add(T_F1, L1 + 12, 4, 0, 16);
  uhalf(L1 + 11);
  dr.add(T_D, 15, 3, 20, 36, E_EXCL); dr.add(T_F2, 15, 3, 20, 36);
  dr.add(T_A, L1 + 13, 4, 0, 20); dr.add(T_F1, L1 + 13, 4, 0, 20);
  ufull(L1 + 11);
  dr.add(T_D, L1 + 10, 3, 20, 36);
  ufull(L1 + 12); uhalf(L1 + 12);
  dr.add(T_A, L1 + 14, 4, 0, 20);
  dr.add(T_A, L1 + 15, 7, 0, 35, E_HALF, 0, 999, 2); dr.add(T_A, L1 + 15, 7, 0, 35, E_HALF | E_EXCL, 1, 999, 2);
  dr.add(T_F1, L1 + 14, 4, 0, 16);
  dr.add(T_F1, L1 + 15, 7, 20, 36);
  dr.add(T_F2, L1 + 10, 3, 0, 16); dr.add(T_F2, L1 + 11, 3, 4, 20); dr.add(T_F2, L1 + 12, 3, 0, 20);
  dr.add(T_D, L1 + 13, 3, 20, 36, (t.hold & 1) ? E_UP : 0); dr.add(T_F2, L1 + 13, 3, 20, 36);
  dr.finish();
  tl.add(T_D, L1 + 11, 3, 0, 24); tl.add(T_D, L1 + 12, 3, 48, G_LATE);
  tl.add(T_U, L1 + 14, 0, 0, 24); tl.add(T_U, L1 + 13, 0, 24, 48);
  tl.add(T_D, L1 + 14, 4, 0, 48, E_HALF);
  tl.add(T_F2, L1 + 14, 4, 0, 48);
  tl.add(T_U, L1 + 15, 0, 48, G_LATE, E_HALF);
  tl.add(T_D, L1 + 15, 4, 48, G_LATE, E_HALF);
  tl.add(T_F2, L1 + 15, 4, 48, G_LATE);
  tl.finish();
}
static void launch_all(void* const* d_in, void* d_out, const Tune& t, cudaStream_t st) {
  static EncodeFn fn = nullptr;
  if (!fn) {
    void* f = nullptr;
    cudaDriverEntryPointQueryResult qr;
    cudaGetDriverEntryPoint("cuTensorMapEncodeTiled", &f, cudaEnableDefault, &qr);
    fn = (EncodeFn)f;
    cudaFuncSetAttribute(r_kernel, cudaFuncAttributeMaxDynamicSharedMemorySize, R_SMEM);
    cudaFuncSetAttribute(g_kernel, cudaFuncAttributeMaxDynamicSharedMemorySize, G_SMEM);
  }
  const CUtensorMap mq = make_map(fn, d_in[2], HD, DM, 64, 128), mk = make_map(fn, d_in[3], HD, DM, 64, 128), mv = make_map(fn, d_in[4], HD, DM, 64, 128),
                    mo = make_map(fn, d_in[5], DM, HD, 64, 64), mg = make_map(fn, d_in[8], FF, DM, 64, 64), mu = make_map(fn, d_in[9], FF, DM, 64, 64),
                    md = make_map(fn, d_in[10], DM, FF, 64, 64);
  auto launch_r = [&](int lag, int n0, int n1) {
    RParams p;
    fill_r(p, t, lag, n0, n1);
    for (int i = 0; i < 4; i++) p.w[i] = (const char*)d_in[2 + i];
    p.mem0 = (const uint4*)d_in[1]; p.x = (const uint32_t*)d_in[0]; p.pf = t.wpf;
    cudaLaunchConfig_t cfg = {};
    cfg.gridDim = dim3(3, NH); cfg.blockDim = dim3(512); cfg.dynamicSmemBytes = R_SMEM; cfg.stream = st;
    cudaLaunchAttribute at[1];
    at[0].id = cudaLaunchAttributeClusterDimension; at[0].val.clusterDim.x = 3; at[0].val.clusterDim.y = 1; at[0].val.clusterDim.z = 1;
    cfg.attrs = at; cfg.numAttrs = 1;
    cudaLaunchKernelEx(&cfg, r_kernel, mq, mk, mv, mo, p);
  };
  auto launch_g = [&](const GParams& g, bool pdl) {
    cudaLaunchConfig_t cfg = {};
    cfg.gridDim = dim3(132); cfg.blockDim = dim3(640); cfg.dynamicSmemBytes = G_SMEM; cfg.stream = st;
    cudaLaunchAttribute at[2];
    at[0].id = cudaLaunchAttributeProgrammaticStreamSerialization; at[0].val.programmaticStreamSerializationAllowed = 1;
    cfg.attrs = at; cfg.numAttrs = pdl ? 1 : 0;
    cudaLaunchKernelEx(&cfg, g_kernel, mo, mg, mu, md, g);
  };
  GParams g;
  fill_g(g, t, d_out);
  g.moff = t.moff; g.gd = t.gd; g.x = (const uint32_t*)d_in[0];
  launch_r(t.lag, 0, 2 * NSEG);
  launch_g(g, true);
}

extern "C" void kernel_launch(void* const* d_in, const int* in_sizes, int n_in, void* d_out, int out_size) {
  launch_all(d_in, d_out, Tune(), cudaStreamPerThread);
}
```

```cpp
#include <cuda_runtime.h>
#include <cuda_bf16.h>
#include <cuda.h>
#include <stdint.h>
#include <stdlib.h>

constexpr int SEQ = 2048, DM = 640, NH = 32, DH = 192, HD = NH * DH, FF = 1536;
constexpr int NSEG = 64, SEGL = 32, NMEM = 8;
constexpr int NBLK = 16;

#define DI __device__ __forceinline__

DI uint32_t smem_base() {
  extern __shared__ __align__(1024) unsigned char smem_raw[];
  uint32_t a;
  asm volatile("{.reg .u64 t; cvta.to.shared.u64 t, %1; cvt.u32.u64 %0, t;}" : "=r"(a) : "l"(smem_raw));
  return a;
}
DI uint32_t mapa(uint32_t a, uint32_t r) {
  uint32_t o;
  asm("mapa.shared::cluster.u32 %0, %1, %2;" : "=r"(o) : "r"(a), "r"(r));
  return o;
}
DI void mbar_init(uint32_t bar, uint32_t cnt) { asm volatile("mbarrier.init.shared::cta.b64 [%0], %1;" ::"r"(bar), "r"(cnt) : "memory"); }
DI void mbar_arrive(uint32_t bar) { asm volatile("mbarrier.arrive.shared::cta.b64 _, [%0];" ::"r"(bar) : "memory"); }
DI void mbar_arrive_remote(uint32_t bar) { asm volatile("mbarrier.arrive.release.cluster.shared::cluster.b64 _, [%0];" ::"r"(bar) : "memory"); }
DI void mbar_expect(uint32_t bar, uint32_t tx) { asm volatile("mbarrier.arrive.expect_tx.shared::cta.b64 _, [%0], %1;" ::"r"(bar), "r"(tx) : "memory"); }
DI void mbar_arrive_if(bool p, uint32_t bar) { asm volatile("{.reg .pred p; setp.ne.b32 p, %1, 0; @p mbarrier.arrive.shared::cta.b64 _, [%0];}" ::"r"(bar), "r"((int)p) : "memory"); }
DI void mbar_arrive_if(bool p, uint32_t bar, uint32_t cnt) {
  asm volatile("{.reg .pred p; setp.ne.b32 p, %1, 0; @p mbarrier.arrive.shared::cta.b64 _, [%0], %2;}" ::"r"(bar), "r"((int)p), "r"(cnt) : "memory");
}
DI void mbar_expect_if(bool p, uint32_t bar, uint32_t tx) {
  asm volatile("{.reg .pred p; setp.ne.b32 p, %2, 0; @p mbarrier.arrive.expect_tx.shared::cta.b64 _, [%0], %1;}" ::"r"(bar), "r"(tx), "r"((int)p) : "memory");
}
DI bool mbar_test(uint32_t bar, uint32_t par) {
  uint32_t ok;
  asm volatile("{.reg .pred p; mbarrier.test_wait.parity.shared::cta.b64 p, [%1], %2; selp.u32 %0, 1, 0, p;}" : "=r"(ok) : "r"(bar), "r"(par) : "memory");
  return ok;
}
DI void mbar_wait(uint32_t bar, uint32_t par) {
  asm volatile(
      "{.reg .pred p;\n"
      "LOOP:\n"
      "mbarrier.try_wait.parity.shared::cta.b64 p, [%0], %1;\n"
      "@!p bra LOOP;\n}" ::"r"(bar), "r"(par) : "memory");
}
DI void mbar_wait_wd(uint32_t bar, uint32_t par) {
  asm volatile(
      "{.reg .pred p; .reg .u32 c;\n"
      "mov.u32 c, 0;\n"
      "LOOP:\n"
      "mbarrier.try_wait.parity.shared::cta.b64 p, [%0], %1;\n"
      "@p bra DONE;\n"
      "add.u32 c, c, 1;\n"
      "setp.lt.u32 p, c, 4000000;\n"
      "@p bra LOOP;\n"
      "trap;\n"
      "DONE:\n}" ::"r"(bar), "r"(par) : "memory");
}
DI void fence_async_smem() { asm volatile("fence.proxy.async.shared::cta;" ::: "memory"); }
DI void fence_async_global() { asm volatile("fence.proxy.async.global;" ::: "memory"); }
DI void bar_sync(int id, int n) { asm volatile("bar.sync %0, %1;" ::"r"(id), "r"(n) : "memory"); }
DI void bar_arrive(int id, int n) { asm volatile("bar.arrive %0, %1;" ::"r"(id), "r"(n) : "memory"); }
DI void cluster_sync() { asm volatile("barrier.cluster.arrive.release.aligned; barrier.cluster.wait.acquire.aligned;" ::: "memory"); }
DI bool elect_one() {
  uint32_t p;
  asm volatile("{.reg .pred p; elect.sync _|p, 0xffffffff; selp.u32 %0, 1, 0, p;}" : "=r"(p));
  return p;
}
DI void bulk_g2s(uint32_t dst, const void* src, uint32_t bytes, uint32_t bar) {
  asm volatile("cp.async.bulk.shared::cluster.global.mbarrier::complete_tx::bytes [%0], [%1], %2, [%3];" ::"r"(dst), "l"(src), "r"(bytes), "r"(bar) : "memory");
}
DI void bulk_g2s_mc(uint32_t dst, const void* src, uint32_t bytes, uint32_t bar, uint16_t mask) {
  asm volatile("cp.async.bulk.shared::cluster.global.mbarrier::complete_tx::bytes.multicast::cluster [%0], [%1], %2, [%3], %4;" ::"r"(dst), "l"(src), "r"(bytes), "r"(bar), "h"(mask) : "memory");
}
DI void bulk_s2s(uint32_t dst, uint32_t src, uint32_t bytes, uint32_t bar) {
  asm volatile("cp.async.bulk.shared::cluster.shared::cta.mbarrier::complete_tx::bytes [%0], [%1], %2, [%3];" ::"r"(dst), "r"(src), "r"(bytes), "r"(bar) : "memory");
}
DI void tma_2d(uint32_t dst, const CUtensorMap* map, int c0, int c1, uint32_t bar) {
  asm volatile("cp.async.bulk.tensor.2d.shared::cluster.global.mbarrier::complete_tx::bytes [%0], [%1, {%3, %4}], [%2];" ::"r"(dst), "l"(map), "r"(bar), "r"(c0), "r"(c1) : "memory");
}
DI void tma_pf(const CUtensorMap* map, int c0, int c1) {
  asm volatile("cp.async.bulk.prefetch.tensor.2d.L2.global [%0, {%1, %2}];" ::"l"(map), "r"(c0), "r"(c1) : "memory");
}
DI void st_async4(uint32_t a, uint32_t x, uint32_t y, uint32_t z, uint32_t w, uint32_t bar) {
  asm volatile("st.async.shared::cluster.mbarrier::complete_tx::bytes.v4.b32 [%0], {%1,%2,%3,%4}, [%5];" ::"r"(a), "r"(x), "r"(y), "r"(z), "r"(w), "r"(bar) : "memory");
}
DI void st_async2(uint32_t a, uint32_t x, uint32_t y, uint32_t bar) {
  asm volatile("st.async.shared::cluster.mbarrier::complete_tx::bytes.v2.b32 [%0], {%1,%2}, [%3];" ::"r"(a), "r"(x), "r"(y), "r"(bar) : "memory");
}
DI void st_async1(uint32_t a, uint32_t x, uint32_t bar) {
  asm volatile("st.async.shared::cluster.mbarrier::complete_tx::bytes.b32 [%0], %1, [%2];" ::"r"(a), "r"(x), "r"(bar) : "memory");
}
DI void sts32(uint32_t a, uint32_t x) { asm volatile("st.shared.b32 [%0], %1;" ::"r"(a), "r"(x) : "memory"); }
DI void sts128(uint32_t a, uint4 v) { asm volatile("st.shared.v4.b32 [%0], {%1,%2,%3,%4};" ::"r"(a), "r"(v.x), "r"(v.y), "r"(v.z), "r"(v.w) : "memory"); }
DI uint32_t lds32(uint32_t a) { uint32_t v; asm volatile("ld.shared.b32 %0, [%1];" : "=r"(v) : "r"(a) : "memory"); return v; }
DI uint2 lds64(uint32_t a) { uint2 v; asm volatile("ld.shared.v2.b32 {%0,%1}, [%2];" : "=r"(v.x), "=r"(v.y) : "r"(a) : "memory"); return v; }
DI uint4 lds128(uint32_t a) { uint4 v; asm volatile("ld.shared.v4.b32 {%0,%1,%2,%3}, [%4];" : "=r"(v.x), "=r"(v.y), "=r"(v.z), "=r"(v.w) : "r"(a) : "memory"); return v; }
DI void stsm4(uint32_t a, uint32_t r0, uint32_t r1, uint32_t r2, uint32_t r3) {
  asm volatile("stmatrix.sync.aligned.m8n8.x4.shared.b16 [%0], {%1,%2,%3,%4};" ::"r"(a), "r"(r0), "r"(r1), "r"(r2), "r"(r3) : "memory");
}
DI void stsm2(uint32_t a, uint32_t r0, uint32_t r1) {
  asm volatile("stmatrix.sync.aligned.m8n8.x2.shared.b16 [%0], {%1,%2};" ::"r"(a), "r"(r0), "r"(r1) : "memory");
}
DI uint32_t movm(uint32_t a) { uint32_t d; asm volatile("movmatrix.sync.aligned.m8n8.trans.b16 %0, %1;" : "=r"(d) : "r"(a)); return d; }
DI uint32_t pack2(float lo, float hi) { uint32_t d; asm("cvt.rn.bf16x2.f32 %0, %1, %2;" : "=r"(d) : "f"(hi), "f"(lo)); return d; }
DI uint4 ld_rlx4(const void* p) {
  uint4 v;
  asm volatile("ld.relaxed.gpu.global.v4.u32 {%0,%1,%2,%3}, [%4];" : "=r"(v.x), "=r"(v.y), "=r"(v.z), "=r"(v.w) : "l"(p) : "memory");
  return v;
}
DI void st_rlx4(void* p, uint32_t x, uint32_t y, uint32_t z, uint32_t w) {
  asm volatile("st.relaxed.gpu.global.v4.u32 [%0], {%1,%2,%3,%4};" ::"l"(p), "r"(x), "r"(y), "r"(z), "r"(w) : "memory");
}
DI void st_rlx1(void* p, uint32_t x) { asm volatile("st.relaxed.gpu.global.u32 [%0], %1;" ::"l"(p), "r"(x) : "memory"); }
DI uint32_t ld_acq(const uint32_t* p) { uint32_t v; asm volatile("ld.acquire.gpu.global.u32 %0, [%1];" : "=r"(v) : "l"(p) : "memory"); return v; }
DI uint32_t ld_rlx(const uint32_t* p) { uint32_t v; asm volatile("ld.relaxed.gpu.global.u32 %0, [%1];" : "=r"(v) : "l"(p) : "memory"); return v; }
DI void red_rel(uint32_t* p, uint32_t v) { asm volatile("red.release.gpu.global.add.u32 [%0], %1;" ::"l"(p), "r"(v) : "memory"); }
DI void guard(uint32_t& g) { asm volatile("{.reg .pred p; add.u32 %0, %0, 1; setp.gt.u32 p, %0, 8000000; @p trap;}" : "+r"(g)); }
DI void poll_ge(const uint32_t* p, uint32_t target) {
  asm volatile(
      "{.reg .pred p; .reg .u32 v;\n"
      "LOOP:\n"
      "ld.acquire.gpu.global.u32 v, [%0];\n"
      "setp.lt.u32 p, v, %1;\n"
      "vote.sync.any.pred p, p, 0xffffffff;\n"
      "@p bra.uni LOOP;\n}" ::"l"(p), "r"(target) : "memory");
}
DI float ex2(float x) { float y; asm("ex2.approx.ftz.f32 %0, %1;" : "=f"(y) : "f"(x)); return y; }

DI void wg_fence() { asm volatile("wgmma.fence.sync.aligned;" ::: "memory"); }
DI void wg_commit() { asm volatile("wgmma.commit_group.sync.aligned;" ::: "memory"); }
template <int N> DI void wg_wait() { asm volatile("wgmma.wait_group.sync.aligned %0;" ::"n"(N) : "memory"); }
template <int N> DI void reg_fence(float* d) {
#pragma unroll
  for (int i = 0; i < N; i++) asm volatile("" : "+f"(d[i])::"memory");
}
__host__ __device__ constexpr uint64_t mkdesc(uint32_t addr, uint32_t lbo, uint32_t sbo, uint32_t sw) {
  return (uint64_t)((addr & 0x3FFFF) >> 4) | ((uint64_t)(lbo >> 4) << 16) | ((uint64_t)(sbo >> 4) << 32) | ((uint64_t)sw << 62);
}

#define ACC4(d, o) "+f"(d[o]), "+f"(d[o + 1]), "+f"(d[o + 2]), "+f"(d[o + 3])
#define ACC16(d, o) ACC4(d, o), ACC4(d, o + 4), ACC4(d, o + 8), ACC4(d, o + 12)
#define ACC20(d) ACC16(d, 0), ACC4(d, 16)

template <int TA, int TB> DI void wg_ss40(float* d, uint64_t da, uint64_t db, int sc) {
  asm volatile("{.reg .pred p; setp.ne.b32 p, %22, 0;\n"
               "wgmma.mma_async.sync.aligned.m64n40k16.f32.bf16.bf16 {%0,%1,%2,%3,%4,%5,%6,%7,%8,%9,%10,%11,%12,%13,%14,%15,%16,%17,%18,%19}, %20, %21, p, 1, 1, %23, %24;}"
               : ACC20(d) : "l"(da), "l"(db), "r"(sc), "n"(TA), "n"(TB));
}
DI void wg_rs40(float* d, uint32_t a0, uint32_t a1, uint32_t a2, uint32_t a3, uint64_t db, int sc) {
  asm volatile("{.reg .pred p; setp.ne.b32 p, %25, 0;\n"
               "wgmma.mma_async.sync.aligned.m64n40k16.f32.bf16.bf16 {%0,%1,%2,%3,%4,%5,%6,%7,%8,%9,%10,%11,%12,%13,%14,%15,%16,%17,%18,%19}, {%20,%21,%22,%23}, %24, p, 1, 1, 0;}"
               : ACC20(d) : "r"(a0), "r"(a1), "r"(a2), "r"(a3), "l"(db), "r"(sc));
}
DI void wg_rs32(float* d, uint32_t a0, uint32_t a1, uint32_t a2, uint32_t a3, uint64_t db, int sc) {
  asm volatile("{.reg .pred p; setp.ne.b32 p, %21, 0;\n"
               "wgmma.mma_async.sync.aligned.m64n32k16.f32.bf16.bf16 {%0,%1,%2,%3,%4,%5,%6,%7,%8,%9,%10,%11,%12,%13,%14,%15}, {%16,%17,%18,%19}, %20, p, 1, 1, 0;}"
               : ACC16(d, 0) : "r"(a0), "r"(a1), "r"(a2), "r"(a3), "l"(db), "r"(sc));
}
DI void wg_rs8(float* d, uint32_t a0, uint32_t a1, uint32_t a2, uint32_t a3, uint64_t db, int sc) {
  asm volatile("{.reg .pred p; setp.ne.b32 p, %9, 0;\n"
               "wgmma.mma_async.sync.aligned.m64n8k16.f32.bf16.bf16 {%0,%1,%2,%3}, {%4,%5,%6,%7}, %8, p, 1, 1, 0;}"
               : ACC4(d, 0) : "r"(a0), "r"(a1), "r"(a2), "r"(a3), "l"(db), "r"(sc));
}
DI void mma16816(float* c, const uint32_t* a, uint32_t b0, uint32_t b1) {
  asm volatile("mma.sync.aligned.m16n8k16.row.col.f32.bf16.bf16.f32 {%0,%1,%2,%3}, {%4,%5,%6,%7}, {%8,%9}, {%0,%1,%2,%3};"
               : ACC4(c, 0) : "r"(a[0]), "r"(a[1]), "r"(a[2]), "r"(a[3]), "r"(b0), "r"(b1));
}
DI void wg_ss8(float* d, uint64_t da, uint64_t db, int sc) {
  asm volatile("{.reg .pred p; setp.ne.b32 p, %6, 0;\n"
               "wgmma.mma_async.sync.aligned.m64n8k16.f32.bf16.bf16 {%0,%1,%2,%3}, %4, %5, p, 1, 1, 1, 1;}"
               : ACC4(d, 0) : "l"(da), "l"(db), "r"(sc));
}
DI void wg_rs16(float* d, uint32_t a0, uint32_t a1, uint32_t a2, uint32_t a3, uint64_t db, int sc) {
  asm volatile("{.reg .pred p; setp.ne.b32 p, %13, 0;\n"
               "wgmma.mma_async.sync.aligned.m64n16k16.f32.bf16.bf16 {%0,%1,%2,%3,%4,%5,%6,%7}, {%8,%9,%10,%11}, %12, p, 1, 1, 0;}"
               : ACC4(d, 0), ACC4(d, 4) : "r"(a0), "r"(a1), "r"(a2), "r"(a3), "l"(db), "r"(sc));
}
__device__ uint4 g_xn[2 * NSEG * 10 * 256];
__device__ uint4 g_oT[2 * NBLK * 96 * 1024];
constexpr int PART_RING = 96 * 256;
__device__ uint4 g_part[4 * PART_RING];
constexpr int MEM_OFF = 192;
#define P4 ~0u, ~0u, ~0u, ~0u
#define P16 P4, P4, P4, P4
#define P256 P16, P16, P16, P16, P16, P16, P16, P16, P16, P16, P16, P16, P16, P16, P16, P16
#define P2K P256, P256, P256, P256, P256, P256, P256, P256
#define P8K P2K, P2K, P2K, P2K
__device__ __align__(8192) uint32_t g_mem32[5 * 2 * 2 * 2048] = {P8K, P8K, P8K, P8K, P8K};
#define g_mem ((uint4*)g_mem32)
constexpr int C_XN = 0;
constexpr int C_O = C_XN + 2 * NBLK;
constexpr int C_HALF = C_O + 6 * 2 * NBLK;
constexpr int C_TOTAL = 512;
constexpr int CSTRIDE = 32;
__device__ uint32_t g_cnt[C_TOTAL * CSTRIDE];
constexpr uint32_t XN_TARGET = 128;

#define TRACE(c, n, i, v)
#define SLOG(i)
#define PROF(i)
#define PROFA(c)
#define PROFV(i, v)

constexpr uint32_t SMEM0 = 1024;
constexpr uint32_t SM_WK = 0, SM_WO = 81920, SM_H = 163840, SM_QT = 215040, QSTR = 1056  , SM_KT = SM_QT + 5 * QSTR + 1024,
                   SM_SR = SM_KT + 5120  , SM_PROF = SM_SR + 5760, R_SMEM = 232448,
                   SM_RED = SM_QT + 1024, SM_BAR = SM_RED + 768;
constexpr uint32_t SM_P = SM_KT, SM_OB = SM_QT + 3200;
constexpr uint32_t B_HFULL = SM_BAR, B_HEMPTY = SM_BAR + 40, B_MTRY = SM_BAR + 80, B_W = SM_BAR + 112, B_SR = B_W + 32,
                   B_PMEM = B_SR + 24, B_PTOK = B_SR + 32, B_OB = B_SR + 40, B_OPD = B_SR + 48, B_RFREE = B_SR + 56,
                   B_GATE = B_SR + 64, B_PSUM = B_SR + 72, B_END = B_SR + 80, B_PVI = B_SR + 88,
                   B_OPI = B_SR + 96, B_OTOK = B_SR + 112, SM_TOPI = B_SR + 128, B_PACE = SM_TOPI + 8,
                   SM_RS = SM_QT + 2 * QSTR + 1024;
static_assert(B_PACE + 32 <= SM_QT + 2 * QSTR, "barriers must fit the unused q row group");

struct RParams {
  uint64_t dH, dHt, dWK, dWO, dQT, dKT, dP, dOB[6];
  const char* w[4];
  const uint4* mem0;
  const uint32_t* x;
  int pf;
  int nslots, d3, pn, moff, ds, dh, dq;
  int d2[10], d1[8];
  uint32_t slot[2 * NSEG];
};
static void r_fill_desc(RParams& p) {
  p.dH = mkdesc(SMEM0 + SM_H, 128, 2048, 0);
  p.dHt = mkdesc(SMEM0 + SM_H + 2048, 128, 2048, 0);
  p.dWK = mkdesc(SMEM0 + SM_WK, 1024, 1024, 1);
  p.dWO = mkdesc(SMEM0 + SM_WO, 1024, 1024, 1);
  for (int i = 0; i < 6; i++) p.dOB[i] = mkdesc(SMEM0 + SM_OB + (i < 3 ? 0 : (i - 3) * 1024), 128, 128, 0);
  p.dQT = mkdesc(SMEM0 + SM_QT, 128, QSTR, 0);
  p.dKT = mkdesc(SMEM0 + SM_KT, 128, 1024, 0);
  p.dP = mkdesc(SMEM0 + SM_P, 128, 640, 0);
}
DI uint64_t dadd(uint64_t d, int bytes) {
  uint64_t r;
  asm volatile("add.u64 %0, %1, %2;" : "=l"(r) : "l"(d), "l"((long long)(bytes / 16)));
  return r;
}
template <int BYTES> DI void dstep(uint64_t& d) { asm volatile("add.u64 %0, %0, %1;" : "+l"(d) : "n"((long long)(BYTES / 16))); }
__host__ __device__ constexpr int hoff(int ks) { return (ks >> 3) * 10240 + (ks & 7) * 256; }

DI int opaque(int v) { asm volatile("" : "+r"(v)); return v; }
DI uint32_t pin(uint32_t v, int lane) { return __shfl_sync(~0u, v + (lane >> 5), lane); }
DI char* pin(char* p, int lane) { return (char*)__shfl_sync(~0u, (unsigned long long)p, lane); }
DI float blo(uint32_t w) { return __uint_as_float(w << 16); }
DI float bhi(uint32_t w) { return __uint_as_float(w & 0xffff0000u); }
#define R_FB 1
#define PIN_DST 1
#define RG0 232
#define RG1 216
#define RG2 40
#define RG3 24
DI void ldsm4t(uint32_t* r, uint32_t a) {
  asm volatile("ldmatrix.sync.aligned.m8n8.x4.trans.shared.b16 {%0,%1,%2,%3}, [%4];" : "=r"(r[0]), "=r"(r[1]), "=r"(r[2]), "=r"(r[3]) : "r"(a) : "memory");
}
DI void st_tagged(void* p, float a, float b, uint32_t keep, uint32_t tagbit) {
  asm volatile("{.reg .b32 t; cvt.rn.bf16x2.f32 t, %2, %1; lop3.b32 t, t, %3, %4, 0xea; st.relaxed.gpu.global.b32 [%0], t;}" ::"l"(p), "f"(a), "f"(b),
               "r"(keep), "r"(tagbit) : "memory");
}
DI uint32_t lop_bad(uint32_t a, uint32_t b, uint32_t m) { uint32_t d; asm("lop3.b32 %0, %1, %2, %3, 0x7e;" : "=r"(d) : "r"(a), "r"(b), "r"(m)); return d; }
DI uint32_t lop_or3(uint32_t a, uint32_t b, uint32_t c) { uint32_t d; asm("lop3.b32 %0, %1, %2, %3, 0xfe;" : "=r"(d) : "r"(a), "r"(b), "r"(c)); return d; }
DI uint32_t clk() { uint32_t t; asm volatile("mov.u32 %0, %%clock;" : "=r"(t)); return t; }
DI void spin(uint32_t cyc) { const uint32_t t0 = clk(); while (__any_sync(~0u, clk() - t0 < cyc)) {} }
template <int NL> DI float2 poll_sum(const uint32_t* src, uint32_t tag, uint32_t even, uint32_t& g) {
  uint32_t r[NL];
  while (true) {
#pragma unroll
    for (int i = 0; i < NL; i++) r[i] = ld_rlx(src + i * 32);
    uint32_t bad = lop_or3(lop_bad(r[0], r[1], tag), lop_bad(r[2], r[3], tag), lop_bad(r[4], r[5], tag));
    if (NL == 12) bad = lop_or3(bad, lop_bad(r[6], r[7], tag), lop_bad(r[8], r[9], tag));
    asm volatile("lop3.b32 %0, %0, %1, %2, 0xa8;" : "+r"(bad) : "r"(lop_bad(r[NL - 2], r[NL - 1], tag)), "r"(even));
    if (!__any_sync(~0u, bad)) break;
    g++;
  }
  float x[NL / 2], y[NL / 2];
#pragma unroll
  for (int i = 0; i < NL / 2; i++) { x[i] = blo(r[2 * i]) + blo(r[2 * i + 1]); y[i] = bhi(r[2 * i]) + bhi(r[2 * i + 1]); }
  float2 u = make_float2((x[0] + x[1]) + (x[2] + x[3]), (y[0] + y[1]) + (y[2] + y[3]));
  if (NL == 12) { u.x += x[4] + x[5]; u.y += y[4] + y[5]; }
  return u;
}

constexpr int PLANE = 16 * 40 * 32, MAXPL = 13;
__device__ uint2 g_acc[(size_t)2 * NBLK * 2 * MAXPL * PLANE];
DI uint2* acc_planes(int lb, int d) { return g_acc + (size_t)((lb * 2 + d) * MAXPL) * PLANE; }
DI void ln_stats(const float4* v, uint32_t red, int warp, int lane, int bar, float& mean, float& rstd) {
  float s = 0.f;
#pragma unroll
  for (int i = 0; i < 5; i++) s += (v[i].x + v[i].y) + (v[i].z + v[i].w);
  s += __shfl_xor_sync(~0u, s, 1);
  s += __shfl_xor_sync(~0u, s, 2);
  s *= 1.f / 80;
  float q = 0.f;
#pragma unroll
  for (int i = 0; i < 5; i++) q += ((v[i].x - s) * (v[i].x - s) + (v[i].y - s) * (v[i].y - s)) + ((v[i].z - s) * (v[i].z - s) + (v[i].w - s) * (v[i].w - s));
  q += __shfl_xor_sync(~0u, q, 1);
  q += __shfl_xor_sync(~0u, q, 2);
  if ((lane & 3) == 0) asm volatile("st.shared.v2.f32 [%0], {%1,%2};" ::"r"(red + lane * 16 + warp * 8), "f"(s), "f"(q) : "memory");
  bar_sync(bar, 256);
  const uint4 t = lds128(red + lane * 16);
  const float m0 = __uint_as_float(t.x), m1 = __uint_as_float(t.z);
  mean = m0 + m1;
  mean += __shfl_xor_sync(~0u, mean, 1);
  mean += __shfl_xor_sync(~0u, mean, 2);
  mean *= 0.125f;
  q = __uint_as_float(t.y) + __uint_as_float(t.w) + 80.f * ((m0 - mean) * (m0 - mean) + (m1 - mean) * (m1 - mean));
  q += __shfl_xor_sync(~0u, q, 1);
  q += __shfl_xor_sync(~0u, q, 2);
  rstd = rsqrtf(q * (1.f / DM) + 1e-5f);
}
template <int SH, int STR> DI void store_img(uint32_t* dst, const float4* v, int warp, float mean, float rstd) {
#pragma unroll
  for (int i = 0; i < 5; i++) {
    const int U = 10 * warp + 2 * i;
    uint32_t* p = dst + (U >> SH) * STR + (U & ((1 << SH) - 1)) * 32;
    p[0] = pack2((v[i].x - mean) * rstd, (v[i].y - mean) * rstd);
    p[32] = pack2((v[i].z - mean) * rstd, (v[i].w - mean) * rstd);
  }
}
DI uint32_t* xn_row_group(int layer, int rg) { return (uint32_t*)(g_xn + (size_t)((layer * NSEG + (rg >> 2)) * 2560 + (rg & 3) * 128)); }

DI void first_ln(const uint32_t* a, int rg, uint32_t red, int warp, int lane, int bar) {
  float4 v[5];
#pragma unroll
  for (int i = 0; i < 5; i++) {
    v[i] = make_float4(blo(a[2 * i]), bhi(a[2 * i]), blo(a[2 * i + 1]), bhi(a[2 * i + 1]));
    acc_planes(rg >> 4, 0)[((rg & 15) * 40 + warp * 5 + i) * 32 + lane] = make_uint2(a[2 * i], a[2 * i + 1]);
  }
  float mean, rstd;
  ln_stats(v, red, warp, lane, bar, mean, rstd);
  store_img<4, 2048>(xn_row_group(0, rg) + lane, v, warp, mean, rstd);
}
#define SOLO 1
#define QK_P0 32
#define QK_KB 0
struct QKOrder { int op[76]; };
__host__ __device__ constexpr QKOrder qk_order() {
  QKOrder o = {};
  int n = 0, k = 0, q = 0;
  for (; k < QK_P0; k++, q++) { o.op[n++] = 64 | k; o.op[n++] = q; }
  for (int i = 0; i < QK_KB; i++) o.op[n++] = 64 | k++;
  for (int i = 0; i < -QK_KB; i++) o.op[n++] = q++;
  const int nk = 40 - k, nq = 36 - q;
  for (int i = 0, dk = 0, dq = 0; i < nk + nq; i++) {
    if (dq * nk <= dk * nq + (QK_KB ? 0 : -nq) && dq < nq) { o.op[n++] = q++; dq++; } else if (dk < nk) { o.op[n++] = 64 | k++; dk++; } else { o.op[n++] = q++; dq++; }
  }
  return o;
}
__global__ void __launch_bounds__(512, 1)
r_kernel(const __grid_constant__ CUtensorMap mapWq, const __grid_constant__ CUtensorMap mapWk, const __grid_constant__ CUtensorMap mapWv,
         const __grid_constant__ CUtensorMap mapWo, const __grid_constant__ RParams prm) {
  const uint32_t sb = smem_base();
  const int wid = __shfl_sync(~0u, threadIdx.x >> 5, 0);
  const int lane0 = __shfl_sync(~0u, threadIdx.x & 31, threadIdx.x & 31);
  const int lane = lane0;
  const int warp = wid & 3, wg = wid >> 2;
  const uint32_t rank = blockIdx.x, head = blockIdx.y, cta = head * 3 + rank;
  const uint32_t peer1 = mapa(sb, rank == 2 ? 0 : rank + 1), peer2 = mapa(sb, rank == 0 ? 2 : rank - 1);
  const int nslots = prm.nslots;

  SLOG(0);
  if (threadIdx.x == 384) {
    if ((sb & 0x3FFFF) != SMEM0) __trap();
    for (int c = 0; c < 5; c++) { mbar_init(sb + B_HFULL + 8 * c, 2); mbar_init(sb + B_HEMPTY + 8 * c, c == 4 ? 8 : 4); }
    for (int c = 0; c < 11; c++) mbar_init(sb + B_MTRY + 8 * c, 1);
    mbar_init(sb + B_PTOK, rank == 0 ? 3 : 2); mbar_init(sb + B_OB, 5); mbar_init(sb + B_OPD, 4);
    mbar_init(sb + B_OPI, 1); mbar_init(sb + B_OPI + 8, 1); mbar_init(sb + B_RFREE, 1); mbar_init(sb + B_GATE, 1); mbar_init(sb + B_PMEM, 2); mbar_init(sb + B_PSUM, 2); mbar_init(sb + B_PVI, 5); mbar_init(sb + B_OTOK, 4); mbar_init(sb + B_OTOK + 8, 4); mbar_init(sb + B_END, 15);
    for (int c = 0; c < 4; c++) mbar_init(sb + B_PACE + 8 * c, 1);
    asm volatile("fence.mbarrier_init.release.cluster;" ::: "memory");
    fence_async_smem();
  }
  asm volatile("griddepcontrol.launch_dependents;");
  asm volatile("barrier.cluster.arrive.release.aligned;" ::: "memory");

  if (wg < 2) {
  {
    uint32_t xa[10];
    const uint32_t* src = prm.x + (size_t)(cta * 8 + (lane >> 2)) * (DM / 2) + wid * 40 + (lane & 3);
#pragma unroll
    for (int i = 0; i < 10; i++) xa[i] = __ldg(src + i * 4);
    asm volatile("barrier.cluster.wait.acquire.aligned;" ::: "memory");
    first_ln(xa, cta, sb + SM_SR, wid, lane, 8);
    bar_arrive(10, 288);
  }
  if (wg == 0) {
    asm volatile("setmaxnreg.inc.sync.aligned.u32 %0;" ::"n"(RG0));
    uint32_t wq[160];
    SLOG(1);
    mbar_wait(sb + B_W, 0);
    SLOG(2);
    {
      const uint32_t ld_off = ((lane >> 4) * 8 + (lane & 7)) * 128 + (((2 * warp + ((lane >> 3) & 1)) ^ (lane & 7)) << 4);
#pragma unroll
      for (int ks = 0; ks < 40; ks++) ldsm4t(wq + 4 * ks, sb + SM_WO + ks * 2048 + ld_off);
    }
    fence_async_smem();
    bar_arrive(5, 160);
    mbar_wait(sb + B_W + 16, 0);
    SLOG(3);
    const uint32_t st_addr = pin(sb + SM_QT + (lane >> 4) * 1024 + (2 * warp + ((lane >> 3) & 1)) * 128 + (lane & 7) * 16, lane);
    const uint32_t sq_addr = pin(sb + SM_QT + (2 + (lane & 3)) * QSTR + warp * 256 + (lane >> 2) * 16, lane);
    const uint32_t to_lo = warp == 0 ? peer1 : mapa(sb, warp == 2 ? 2 : 0), to_hi = warp == 0 ? peer2 : mapa(sb, warp == 1 ? 1 : 0);
    const uint32_t sr_off = SM_SR + warp * 1920 + rank * 640, sr_bar = B_SR + warp * 8;
    const uint32_t sa0 = pin(to_lo + sr_off + lane * 16, lane), sb0 = pin(to_lo + sr_bar, lane), sa1 = pin(to_lo + sr_off + 512 + lane * 4, lane), sb1 = pin(sb0, lane);
    const uint32_t sa2 = pin(to_hi + sr_off + lane * 16, lane), sb2 = pin(to_hi + sr_bar, lane), sa3 = pin(to_hi + sr_off + 512 + lane * 4, lane), sb3 = pin(sb2, lane);
    uint32_t nsolo = 0;
#pragma unroll 1
    for (int n = 0; n < nslots; n++) {
      const uint32_t par = n & 1;
      PROFA(warp == PW);
      const bool alt = prm.slot[n] & 128;
      auto next = [&](uint64_t& d, int ks) { if ((ks & 7) == 7) dstep<10240 - 7 * 256>(d); else dstep<256>(d); };
      auto store_k = [&](const float* ka) {
        stsm2(st_addr + (SM_KT - SM_QT), pack2(ka[0], ka[1]), pack2(ka[2], ka[3]));
        stsm4(st_addr + (SM_KT - SM_QT) + 1024, pack2(ka[4], ka[5]), pack2(ka[6], ka[7]), pack2(ka[8], ka[9]), pack2(ka[10], ka[11]));
        stsm4(st_addr + (SM_KT - SM_QT) + 3072, pack2(ka[12], ka[13]), pack2(ka[14], ka[15]), pack2(ka[16], ka[17]), pack2(ka[18], ka[19]));
      };
      auto store_qt = [&](const float* q) {
        sts128(sq_addr, make_uint4(pack2(q[0], q[1]), pack2(q[4], q[5]), pack2(q[8], q[9]), pack2(q[12], q[13])));
        sts128(sq_addr + 128, make_uint4(pack2(q[2], q[3]), pack2(q[6], q[7]), pack2(q[10], q[11]), pack2(q[14], q[15])));
      };
      if (SOLO && n > 0 && ((prm.slot[n] >> 8) & 255) == n) {
        {
          float qt[16];
          uint64_t rh = prm.dHt;
          mbar_wait(sb + B_OPD, par ^ 1);
          spin(prm.dq);
          mbar_wait(sb + B_PVI, nsolo++ & 1);
          wg_fence();
#pragma unroll
          for (int ks = 0; ks < 40; ks++) { wg_rs32(qt, wq[4 * ks], wq[4 * ks + 1], wq[4 * ks + 2], wq[4 * ks + 3], rh, ks != 0); if (ks < 39) next(rh, ks); }
          wg_commit();
          wg_wait<0>();
          reg_fence<16>(qt);
          store_qt(qt);
        }
        float qm[4], ka[20];
        uint64_t rk = prm.dWK, rh = prm.dH, rq;
        bool ok = false;
#pragma unroll
        for (int g = 0; g < 18; g++) {
          if ((g & 3) == 0 && !ok) mbar_wait(sb + B_HFULL + 2 * g, par);
          if (g == 0) PROF(0);
          if ((g & 3) == 3) ok = mbar_test(sb + B_HFULL + 2 * (g + 1), par);
          if ((g & 3) == 0) wg_fence();
#pragma unroll
          for (int ks = 2 * g; ks < 2 * g + 2; ks++) {
            wg_ss40<1, 0>(ka, rk, rh, ks != 0);
            wg_rs8(qm, wq[4 * ks], wq[4 * ks + 1], wq[4 * ks + 2], wq[4 * ks + 3], rh, ks != 0);
            dstep<2048>(rk); next(rh, ks);
          }
        }
        wg_commit();
        rq = rh;
#pragma unroll
        for (int ks = 36; ks < 40; ks++) { wg_ss40<1, 0>(ka, rk, rh, 1); if (ks < 39) { dstep<2048>(rk); dstep<256>(rh); } }
        wg_commit();
#pragma unroll
        for (int ks = 36; ks < 40; ks++) { wg_rs8(qm, wq[4 * ks], wq[4 * ks + 1], wq[4 * ks + 2], wq[4 * ks + 3], rq, 1); if (ks < 39) dstep<256>(rq); }
        wg_commit();
        wg_wait<2>();
        if (alt) bar_arrive(2, 256);
        wg_wait<1>();
        if (!alt) bar_arrive(2, 256);
        reg_fence<20>(ka);
        store_k(ka);
        wg_wait<0>();
        reg_fence<4>(qm);
        PROF(9);
        stsm2(st_addr, pack2(qm[0], qm[1]), pack2(qm[2], qm[3]));
      } else {
      float qa[20], ka[20];
      uint64_t rk = prm.dWK, rh = prm.dH, rq;
      auto K = [&](int ks) { wg_ss40<1, 0>(ka, rk, rh, ks != 0); };
      auto Q = [&](int ks, uint64_t db) { wg_rs40(qa, wq[4 * ks], wq[4 * ks + 1], wq[4 * ks + 2], wq[4 * ks + 3], db, ks != 0); };
      constexpr QKOrder ord = qk_order();
      auto first = [&](int g, int c) { for (int i = 0; i < 76; i++) if ((ord.op[i] & 63) >> 3 == c) return i >> 2 == g; return false; };
      bool ok = true;
      mbar_wait(sb + B_HFULL, par);
#pragma unroll
      for (int g = 0; g < 19; g++) {
        if (!ok) {
#pragma unroll
          for (int c = 1; c < 5; c++) if (first(g, c)) mbar_wait(sb + B_HFULL + 8 * c, par);
          mbar_wait(sb + B_GATE, 1);
        }
        if (g == 0) PROF(0);
        if (g < 18) ok = mbar_test(sb + B_GATE, 1);
#pragma unroll
        for (int c = 1; c < 5; c++) if (first(g + 1, c)) ok &= mbar_test(sb + B_HFULL + 8 * c, par);
        wg_fence();
#pragma unroll
        for (int i = 4 * g; i < 4 * g + 4; i++) {
          const int ks = ord.op[i] & 63;
          if (i < 2 * QK_P0) {
            if (ord.op[i] & 64) K(ks);
            else { Q(ks, rh); dstep<2048>(rk); next(rh, ks); if (i == 2 * QK_P0 - 1) rq = rh; }
          } else if (ord.op[i] & 64) { K(ks); if (ks < 39) { dstep<2048>(rk); next(rh, ks); } }
          else { Q(ks, rq); next(rq, ks); }
        }
        if (g == 17) wg_commit();
      }
      wg_commit();
#pragma unroll
      for (int ks = 36; ks < 40; ks++) { Q(ks, rq); if (ks < 39) dstep<256>(rq); }
      wg_commit();
      wg_wait<2>();
      if (alt) bar_arrive(2, 256);
      mbar_wait(sb + B_OPD, par ^ 1);
      wg_wait<1>();
      if (!alt) bar_arrive(2, 256);
      reg_fence<20>(ka);
      store_k(ka);
      wg_wait<0>();
      reg_fence<20>(qa);
      PROF(9);
      stsm2(st_addr, pack2(qa[0], qa[1]), pack2(qa[2], qa[3]));
      store_qt(qa + 4);
      }
      mbar_arrive_if(lane == 0, sb + B_HEMPTY + 32);
      fence_async_smem();
      bar_sync(1, 128);
      PROF(1);
      float qa[20];
      wg_fence();
#pragma unroll
      for (int k = 0; k < 4; k++) wg_ss40<1, 1>(qa, dadd(prm.dQT, k * 256), dadd(prm.dKT, k * 256), k != 0);
      wg_commit();
      bar_arrive(7, 256);
      wg_wait<0>();
      reg_fence<20>(qa);
      PROF(3);
      if (warp < 3) {
        uint32_t p[5];
#pragma unroll
        for (int j = 0; j < 5; j++) p[j] = pack2(qa[4 * j], qa[4 * j + 1]);
        if (warp == 0) {
          st_async4(sa0, p[0], p[1], p[2], p[3], sb0);
          st_async4(sa2, p[0], p[1], p[2], p[3], sb2);
          st_async1(sa1, p[4], sb1);
          st_async1(sa3, p[4], sb3);
          sts128(sb + sr_off + lane * 16, make_uint4(p[0], p[1], p[2], p[3]));
          sts32(sb + sr_off + 512 + lane * 4, p[4]);
          __syncwarp();
          mbar_expect_if(lane == 0, sb + B_SR, 1280);
        } else {
          uint32_t h[5];
#pragma unroll
          for (int j = 0; j < 5; j++) h[j] = pack2(qa[4 * j + 2], qa[4 * j + 3]);
          spin(prm.d3);
          st_async4(sa0, p[0], p[1], p[2], p[3], sb0);
          st_async4(sa2, h[0], h[1], h[2], h[3], sb2);
          st_async1(sa1, p[4], sb1);
          st_async1(sa3, h[4], sb3);
        }
      }
    }
  } else {
    asm volatile("setmaxnreg.inc.sync.aligned.u32 %0;" ::"n"(RG1));
    uint32_t wv[160];
    mbar_wait(sb + B_W + 8, 0);
    SLOG(4);
    {
      const uint32_t ld_off = ((lane >> 4) * 8 + (lane & 7)) * 128 + (((2 * warp + ((lane >> 3) & 1)) ^ (lane & 7)) << 4);
#pragma unroll
      for (int ks = 0; ks < 40; ks++) ldsm4t(wv + 4 * ks, sb + SM_WO + ks * 2048 + ld_off);
    }
    fence_async_smem();
    bar_arrive(6, 160);
    const uint64_t dH = prm.dH;
    uint32_t op[8];
    const uint32_t ob_off = SM_OB + (4 * rank + warp) * 256 + lane * 4;
    const uint32_t oa0 = pin(peer1 + ob_off, lane), ob0 = pin(peer1 + B_OB, lane), oa1 = pin(peer2 + ob_off, lane), ob1 = pin(peer2 + B_OB, lane);
    const uint32_t oa2 = pin(oa0 + 128, lane), ob2 = pin(ob0, lane), oa3 = pin(oa1 + 128, lane), ob3 = pin(ob1, lane);
    const uint32_t o_loc = pin(sb + ob_off, lane), rs_addr = pin(sb + SM_RS + (lane & 3) * 8, lane);
    const uint32_t tok_off = pin((cta * 1024 + 64 * warp + (lane ^ (lane >> 3))) * 16, lane), keep = pin((lane & 1) ? ~0u : ~1u, lane);
    const uint32_t pb_off = pin((8 * rank + 2 * warp) * 4096 + head * 128 + lane * 4, lane);
    const uint32_t ph_off = pin(72 * 4096 + 2 * warp * 12288 + cta * 64 + (lane & 2) * 3072 + (lane >> 2) * 8 + (lane & 1) * 4, lane);
    auto store_tok = [&](int m, int lane) {
      const uint32_t ls = prm.slot[m] & 127, sig = prm.slot[m] >> 16;
      uint4* dst = (uint4*)((char*)(g_oT + (size_t)((ls >> 2) * (96 * 1024) + (ls & 3) * 256)) + tok_off);
      dst[0] = make_uint4(op[0], op[1], op[2], op[3]);
      dst[32] = make_uint4(op[4], op[5], op[6], op[7]);
      __syncwarp();
      mbar_arrive_if(sig && lane == 0, sb + B_OTOK + (ls >> 6) * 8);
    };
#pragma unroll 1
    for (int n = 0; n < nslots; n++) {
      const uint32_t par = n & 1;
      const int lane = opaque(lane0);
      PROFA(warp == PW);
      float va[20];
      const bool alt = prm.slot[n] & 128;
      mbar_expect_if(warp == 0 && lane == 0, sb + B_PTOK, rank == 0 ? 1280 : 1920);
      bar_sync(2, 256);
#pragma unroll
      for (int g = 0; g < 10; g++) {
        wg_fence();
#pragma unroll
        for (int ks = 4 * g; ks < 4 * g + 4; ks++) { wg_rs40(va, wv[4 * ks], wv[4 * ks + 1], wv[4 * ks + 2], wv[4 * ks + 3], dadd(dH, hoff(ks)), ks != 0); }
        wg_commit();
        if (g >= 2 && !(g & 1)) {
          wg_wait<1>();
          if (lane == 0) mbar_arrive(sb + B_HEMPTY + 8 * (g / 2 - 1));
        }
        if (g == 1 ? !alt : g == 2 && alt) bar_sync(7, 256);
      }
      wg_wait<0>();
      reg_fence<20>(va);
      if (lane == 0) mbar_arrive(sb + B_HEMPTY + 32);
      PROF(10);
      uint32_t vf[10];
#pragma unroll
      for (int j = 0; j < 10; j++) {
        const int i = (j + 4) % 10;
        asm volatile("cvt.rn.bf16x2.f32 %0, %1, %2;" : "=r"(vf[i]) : "f"(va[2 * i + 1]), "f"(va[2 * i]));
        if (j == 5) mbar_wait(sb + B_W + 8, 0);
      }
      uint32_t z0, z1;
      asm volatile("shr.u32 %0, %2, 5; shr.u32 %1, %2, 6;" : "=r"(z0), "=r"(z1) : "r"(lane));
      const uint32_t info = prm.slot[n];
      const uint32_t tagbit = ~(info >> 1) & ~keep;
      char* const ring = (char*)(g_part + (size_t)((((info >> 5) & 2) + (info & 1)) * PART_RING));
      char* const pb = pin(ring + pb_off, lane);
      char* const ph = ring + ph_off;
      mbar_wait(sb + B_PMEM, par);
      float om[4];
      wg_fence();
      wg_rs8(om, vf[0], vf[1], vf[2], vf[3], prm.dP, 0);
      wg_rs8(om, vf[4], vf[5], vf[6], vf[7], dadd(prm.dP, 256), 1);
      wg_rs8(om, vf[8], vf[9], z0, z1, dadd(prm.dP, 512 - (128 << 16)), 1);
      wg_commit();
      {
        wg_wait<0>();
        reg_fence<4>(om);
        const uint32_t b0 = pack2(om[0], om[1]), b1 = pack2(om[2], om[3]);
        st_async1(oa0, b0, ob0);
        st_async1(oa1, b0, ob1);
        st_async1(oa2, b1, ob2);
        st_async1(oa3, b1, ob3);
        sts32(o_loc, b0);
        sts32(o_loc + 128, b1);
        fence_async_smem();
        __syncwarp();
        mbar_arrive_if(lane == 0, sb + B_OB);
      }
      PROF(11);
      {
        float c[8];
        mbar_wait(sb + B_PSUM, par);
        const uint2 rs = lds64(rs_addr);
        const float r0 = __uint_as_float(rs.x), r1 = __uint_as_float(rs.y);
        if (n == 0) { SLOG(5); mbar_wait(sb + B_W + 24, 0); SLOG(6); }
        mbar_wait(sb + B_OB, par);
        asm volatile("fence.proxy.async::generic.acquire.sync_restrict::shared::cluster.cluster;" ::: "memory");
        PROF(16);
        if ((info & 63) == NSEG - 1) {
          mbar_wait(sb + B_OPI + par * 8, (n >> 1) & 1);
          mbar_arrive_if(warp == 3 && lane == 0, sb + B_GATE);
#pragma unroll
          for (int p = 0; p < 6; p++) st_rlx1(pb + (p >> 1) * 98304 + (p & 1) * 4096, tagbit);
          st_rlx1(ph, tagbit);
          st_rlx1(ph + 12288, tagbit);
        } else {
#pragma unroll
        for (int p = 0; p < 4; p++) {
          float* const cur = c + 4 * (p & 1);
          float* const prv = c + 4 * (~p & 1);
          if (p == 2) mbar_wait(sb + B_OPI + par * 8, (n >> 1) & 1);
          wg_fence();
#pragma unroll
          for (int ks = 0; ks < (p < 3 ? 12 : 4); ks++) {
            wg_ss8(cur, dadd(prm.dWO, p * 24576 + ks * 2048), dadd(prm.dOB[p < 3 ? p : 3 + rank], ks * 256), ks != 0);
            if (p == 3 && ks == 3) mbar_arrive_if(warp == 3 && lane == 0, sb + B_GATE);
            if (p > 0 && ks == 3) {
              wg_commit();
              wg_wait<1>();
              reg_fence<4>(prv);
              st_tagged(pb + (p - 1) * 98304, prv[0] * r0, prv[1] * r1, keep, tagbit);
              st_tagged(pb + (p - 1) * 98304 + 4096, prv[2] * r0, prv[3] * r1, keep, tagbit);
            }
          }
          if (p < 3) wg_commit();
        }
        wg_wait<0>();
        reg_fence<4>(c + 4);
        st_tagged(ph, c[4] * r0, c[5] * r1, keep, tagbit);
        st_tagged(ph + 12288, c[6] * r0, c[7] * r1, keep, tagbit);
        }
        PROF(17);
      }
      mbar_wait(sb + B_PTOK, par);
      PROF(12);
      {
        float ot[16];
        wg_fence();
        wg_rs32(ot, vf[0], vf[1], vf[2], vf[3], dadd(prm.dP, 640), 0);
        wg_rs32(ot, vf[4], vf[5], vf[6], vf[7], dadd(prm.dP, 640 + 256), 1);
        wg_rs32(ot, vf[8], vf[9], z0, z1, dadd(prm.dP, 640 + 512 - (128 << 16)), 1);
        wg_commit();
        wg_wait<0>();
        reg_fence<16>(ot);
#pragma unroll
        for (int i = 0; i < 8; i++) op[(i & 1) * 4 + (i >> 1)] = pack2(ot[2 * i], ot[2 * i + 1]);
      }
      if (lane == 0) mbar_arrive(sb + B_OPD);
      PROF(13);
      if (info & 128) spin(prm.ds);
      store_tok(n, lane);
    }
  }
  } else if (wg == 2) {
    asm volatile("setmaxnreg.dec.sync.aligned.u32 %0;" ::"n"(RG2));
    asm volatile("barrier.cluster.wait.acquire.aligned;" ::: "memory");
    if (warp == 1) {
      const uint32_t depth = prm.pf & 7;
#pragma unroll 1
      for (uint32_t i = 0; i < 20 + depth; i++) {
        if (i >= depth) {
          const uint32_t j = i - depth;
          mbar_wait_wd(sb + B_PACE + 8 * (j & 3), (j >> 2) & 1);
          if (j % 5 == 4) mbar_arrive_if(lane == 0 && (j != 14 || depth == 1), sb + B_W + (j == 4 ? 0 : j == 9 ? 16 : j == 14 ? 8 : 24));
        }
        if (i >= 20) continue;
        const uint32_t m = i / 5, k = i % 5, bar = sb + B_PACE + 8 * (i & 3);
        if (i == 10) bar_sync(5, 160);
        if (i == 15) {
          if ((prm.pf & 8) && elect_one())
            for (int q = 0; q < 4; q++) tma_pf(&mapWo, (q / 3 * 3 + rank) * 64, head * DH + q % 3 * 64);
#pragma unroll 1
          for (uint32_t j = 16 - depth; j < 15; j++) mbar_wait_wd(sb + B_PACE + 8 * (j & 3), (j >> 2) & 1);
          mbar_arrive_if(lane == 0 && depth > 1, sb + B_W + 8);
          bar_sync(6, 160);
        }
        if (elect_one()) {
          mbar_expect(bar, 16384);
          if (m < 3) tma_2d(sb + (m == 1 ? SM_WK : SM_WO) + k * 16384, m == 0 ? &mapWq : m == 1 ? &mapWk : &mapWv, cta * 64, k * 128, bar);
          else
            for (uint32_t q = 2 * k; q < 2 * k + 2; q++)
              tma_2d(sb + SM_WO + q * 8192, &mapWo, q < 9 ? (q / 3 * 3 + rank) * 64 : 576, head * DH + (q < 9 ? q % 3 : rank) * 64, bar);
        }
      }
    }
    if (warp == 2 && cta < 80 && lane < 16)
      g_mem[(cta >> 4) * 2048 + (lane >> 3) * 1024 + prm.moff + (cta & 15) * 8 + (lane & 7)] = prm.mem0[(lane & 7) * 80 + cta];
    if (warp == 3) {
      bar_sync(10, 288);
      if (lane == 0) red_rel(&g_cnt[(C_XN + (cta >> 4)) * CSTRIDE], 8);
    }
    const uint32_t grp = warp == 1 ? 1 + rank : 4 - (rank >> 1);
    constexpr float SC = 0.07216878364870322f * 1.4426950408889634f;
    const bool split = cta >= 72;
    const uint32_t wd = split ? 72 * 16 + cta * 16 : cta * 32;
    const uint32_t src_off = pin(split ? 72 * 4096 + (cta - 72) * 6144 + warp * 1536 + (lane & 2) * 32 + (lane >> 2) * 8 + (lane & 1) * 4 : cta * 4096 + warp * 1024 + lane * 4, lane);
    const uint32_t dst_off = pin(((wd >> 9) * 8192 + prm.moff * 4 + (wd & 511) + lane) * 4, lane);
    const uint32_t red = pin(sb + SM_RED + (warp < 2 ? 0 : (warp - 1) * 256) + lane * 8, lane);
    const uint32_t fl = (warp & 2) * 8 + (lane >> 3) * 4 + (lane & 3), hf = lane & 4;
    const uint32_t s0 = pin(sb + SM_SR + fl * 16 + hf * 2, lane), s1 = pin(sb + fl * 4, lane), pd = pin(s1 + hf * 64, lane);
    const uint32_t even = pin(~lane & 1, lane);
    uint32_t nred = 0;
    const uint32_t arm = pin(warp == 0 && (lane == 5 || ((lane == 1 || lane == 2) && lane + rank != 3)) ? sb + B_SR + lane * 8 : 0, lane);
#pragma unroll 1
    for (int n = 0; n < nslots; n++) {
      const uint32_t par = n & 1;
      const int lane = opaque(lane0);
      PROFA(warp == PW2);
      const uint32_t info = prm.slot[n], s = info & 63, l = (info >> 6) & 1;
      {
        mbar_expect_if(arm, arm, lane == 5 ? 2048 : 1920);
        if (warp == 0 || warp == 3) {
          mbar_wait(sb + B_SR, par);
          PROF(4);
          const uint2 a0 = lds64(s0), a1 = lds64(s0 + 640), a2 = lds64(s0 + 1280);
          const uint32_t b0 = lds32(s1 + SM_SR + 512), b1 = lds32(s1 + SM_SR + 1152), b2 = lds32(s1 + SM_SR + 1792);
          float v[6];
          v[0] = blo(a0.x) + blo(a1.x) + blo(a2.x); v[1] = bhi(a0.x) + bhi(a1.x) + bhi(a2.x);
          v[2] = blo(a0.y) + blo(a1.y) + blo(a2.y); v[3] = bhi(a0.y) + bhi(a1.y) + bhi(a2.y);
          v[4] = blo(b0) + blo(b1) + blo(b2); v[5] = bhi(b0) + bhi(b1) + bhi(b2);
          float m = fmaxf(fmaxf(v[0], v[1]), fmaxf(v[2], v[3]));
          m = fmaxf(fmaxf(m, __shfl_xor_sync(~0u, m, 4)), fmaxf(v[4], v[5]));
          {
            const float m1 = __shfl_xor_sync(~0u, m, 1), m2 = __shfl_xor_sync(~0u, m, 2), m3 = __shfl_xor_sync(~0u, m, 3);
            m = fmaxf(fmaxf(m, m1), fmaxf(m2, m3));
          }
          const float ms = -m * SC;
#pragma unroll
          for (int i = 0; i < 6; i++) v[i] = ex2(fmaf(v[i], SC, ms));
          float sum = (v[0] + v[1]) + (v[2] + v[3]);
          const float so = __shfl_xor_sync(~0u, sum, 4);
          sts32(pd + SM_P, pack2(v[0], v[1]));
          sts32(pd + SM_P + 128, pack2(v[2], v[3]));
          sts32(s1 + SM_P + 512, pack2(v[4], v[5]));
          fence_async_smem();
          __syncwarp();
          mbar_arrive_if(lane == 0, sb + B_PMEM);
          PROF(5);
          sum += so + (v[4] + v[5]);
          {
            const float t1 = __shfl_xor_sync(~0u, sum, 1), t2 = __shfl_xor_sync(~0u, sum, 2), t3 = __shfl_xor_sync(~0u, sum, 3);
            sum = (sum + t1) + (t2 + t3);
          }
          float r;
          asm("rcp.approx.ftz.f32 %0, %1;" : "=f"(r) : "f"(sum));
          sts32(sb + SM_RS + (warp & 2) * 8 + (lane >> 3) * 4, __float_as_uint(r));
          __syncwarp();
          mbar_arrive_if(lane == 0, sb + B_PSUM);
        } else {
          if (warp + rank != 3) {
            const uint32_t src = sb + SM_SR + warp * 1920;
            mbar_wait(sb + B_SR + warp * 8, par);
            const uint4 a0 = lds128(src + lane * 16), a1 = lds128(src + 640 + lane * 16), a2 = lds128(src + 1280 + lane * 16);
            const uint32_t b0 = lds32(src + 512 + lane * 4), b1 = lds32(src + 1152 + lane * 4), b2 = lds32(src + 1792 + lane * 4);
            float v[10];
            v[0] = blo(a0.x) + blo(a1.x) + blo(a2.x); v[1] = bhi(a0.x) + bhi(a1.x) + bhi(a2.x);
            v[2] = blo(a0.y) + blo(a1.y) + blo(a2.y); v[3] = bhi(a0.y) + bhi(a1.y) + bhi(a2.y);
            v[4] = blo(a0.z) + blo(a1.z) + blo(a2.z); v[5] = bhi(a0.z) + bhi(a1.z) + bhi(a2.z);
            v[6] = blo(a0.w) + blo(a1.w) + blo(a2.w); v[7] = bhi(a0.w) + bhi(a1.w) + bhi(a2.w);
            v[8] = blo(b0) + blo(b1) + blo(b2); v[9] = bhi(b0) + bhi(b1) + bhi(b2);
            {
              const int lim = 6 + 2 * grp + (lane & 24) + ((lane >> 2) & 1) - 2 * (lane & 3);
#pragma unroll
              for (int i = 2; i < 10; i++) if ((i >> 1) * 8 + (i & 1) > lim) v[i] = -INFINITY;
            }
            float m = fmaxf(fmaxf(fmaxf(v[0], v[1]), fmaxf(v[2], v[3])), fmaxf(fmaxf(v[4], v[5]), fmaxf(v[6], v[7])));
            m = fmaxf(m, fmaxf(v[8], v[9]));
            {
              const float m1 = __shfl_xor_sync(~0u, m, 1), m2 = __shfl_xor_sync(~0u, m, 2), m3 = __shfl_xor_sync(~0u, m, 3);
              m = fmaxf(fmaxf(m, m1), fmaxf(m2, m3));
            }
            const float ms = -m * SC;
#pragma unroll
            for (int i = 0; i < 10; i++) v[i] = ex2(fmaf(v[i], SC, ms));
            float sum = ((v[0] + v[1]) + (v[2] + v[3])) + ((v[4] + v[5]) + (v[6] + v[7])) + (v[8] + v[9]);
            {
              const float s1 = __shfl_xor_sync(~0u, sum, 1), s2 = __shfl_xor_sync(~0u, sum, 2), s3 = __shfl_xor_sync(~0u, sum, 3);
              sum = (sum + s1) + (s2 + s3);
            }
            float r;
            asm("rcp.approx.ftz.f32 %0, %1;" : "=f"(r) : "f"(sum));
            {
              const uint32_t row = SM_P + grp * 640;
#pragma unroll
              for (int j = 0; j < 5; j++) sts32(sb + row + j * 128 + lane * 4, pack2(v[2 * j] * r, v[2 * j + 1] * r));
              fence_async_smem();
              __syncwarp();
              mbar_arrive_if(lane == 0, sb + B_PTOK);
              if (elect_one()) {
                bulk_s2s(peer1 + row, sb + row, 640, peer1 + B_PTOK);
                bulk_s2s(peer2 + row, sb + row, 640, peer2 + B_PTOK);
              }
            }
          }
        }
      }
      const uint32_t* const src = (const uint32_t*)((char*)(g_part + (size_t)((l * 2 + (s & 1)) * PART_RING)) + src_off);
      uint32_t* const dst = (uint32_t*)pin((char*)(g_mem + l * 1024 + (~s & 1) * 512) + dst_off, lane);
      {
        const uint32_t d1 = prm.d1[cta / 24 + ((info >> 5) & 4)];
        if (warp == 3) {
          mbar_wait(sb + B_OB, par);
          mbar_arrive_if(lane == 0, sb + B_GATE);
          sts32(sb + SM_TOPI + par * 4, clk());
          __syncwarp();
          mbar_arrive_if(lane == 0, sb + B_OPI + par * 8);
          TRACE(true, n, 0, gtl());
        }
        const bool reduce = cta < 88 && s != NSEG - 1;
        if (reduce || warp == 0) mbar_wait(sb + B_OPI + par * 8, (n >> 1) & 1);
        if (!reduce) continue;
        mbar_wait(sb + B_RFREE, (nred++ & 1) ^ 1);
        mbar_wait(sb + B_GATE, 1);
        if (d1) spin(d1);
      }
      {
        uint32_t g = 0;
        float2 u;
        PROF(14);
        if (!split) {
          u = poll_sum<8>(src, ~(s >> 1), even, g);
        } else {
          u = poll_sum<12>(src, ~(s >> 1), even, g);
          u.x += __shfl_xor_sync(~0u, u.x, 2);
          u.y += __shfl_xor_sync(~0u, u.y, 2);
        }
        PROF(18);
        if (warp != 1) {
          asm volatile("st.shared.v2.f32 [%0], {%1,%2};" ::"r"(red), "f"(u.x), "f"(u.y) : "memory");
          bar_arrive(3, 128);
        } else {
          bar_sync(3, 128);
          const uint2 o0 = lds64(red), o1 = lds64(red + 256), o2 = lds64(red + 512);
          const uint32_t w = movm(pack2((u.x + __uint_as_float(o0.x)) + (__uint_as_float(o1.x) + __uint_as_float(o2.x)),
                                        (u.y + __uint_as_float(o0.y)) + (__uint_as_float(o1.y) + __uint_as_float(o2.y))));
          if (!split || lane < 16) {
            st_rlx1(dst, w);
            st_rlx1(dst + ((s & 1) ? 2048 : -2048), ~0u);
          }
          mbar_arrive_if(lane == 0, sb + B_RFREE);
        }
        PROF(19);
        PROFV(2, g);
        TRACE(warp == 1, n, 1, gtl());
        TRACE(g, n, 2, g);
      }
    }
  } else {
    asm volatile("setmaxnreg.dec.sync.aligned.u32 %0;" ::"n"(RG3));
    asm volatile("barrier.cluster.wait.acquire.aligned;" ::: "memory");
    const uint32_t chk = lane * 32 + ((lane >> 2) << 2);
    const uint32_t bar = sb + B_MTRY + 8 * warp;
    uint32_t mph = 0, waited = 0, pub = 0, pph = 0, nsolo = 0;
    auto publish = [&](uint32_t upto) {
#pragma unroll 1
      for (; pub < upto; pub++) {
        const uint32_t e = prm.slot[pub], l = (e >> 6) & 1;
        if (warp == 3 && (e >> 16)) {
          mbar_wait_wd(sb + B_OTOK + l * 8, (pph >> l) & 1);
          pph ^= 1 << l;
          if (elect_one()) red_rel(&g_cnt[(e >> 16) * CSTRIDE], 1);
        }
      }
    };
#pragma unroll 1
    for (int m = 0; m < nslots; m++) {
      const uint32_t info = prm.slot[m], prod = (info >> 8) & 255, ls = info & 127;
      uint32_t g = 0;
#pragma unroll 1
      for (; waited < prod && waited + 1 < m; waited++) mbar_wait_wd(sb + B_OPI + (waited & 1) * 8, (waited >> 1) & 1);
      uint32_t t0 = lds32(sb + SM_TOPI + (~waited & 1) * 4);
      publish(waited);
      if ((ls & 3) == 0) {
        while (__any_sync(~0u, ld_acq(&g_cnt[(C_XN + (ls >> 2)) * CSTRIDE]) < XN_TARGET)) guard(g);
        fence_async_global();
      }
#pragma unroll 1
      for (uint32_t c = warp; c < 5; c += 4) {
        const uint32_t dst = sb + SM_H + c * 10240, full = sb + B_HFULL + 8 * c;
        const uint4* src = g_mem + (c * 2048 + (ls >> 6) * 1024 + (ls & 1) * 512 + prm.moff);
        const uint32_t d = prod ? prm.d2[(m - prod) * 5 + c] : 0;
        const uint4* tok = g_xn + (size_t)(ls * 2560 + c * 512);
        const uint32_t pp = (m & 1) ^ 1;
        const bool single = waited < prod;
        mbar_wait_wd(full, pp);
        const bool solo = SOLO && m > 0 && prod == m;
        const uint32_t tokb = solo ? sb + B_PVI : full;
        if (solo && c < 4) mbar_wait_wd(tokb, (nsolo++ & 1) ^ 1);
        mbar_expect_if(lane < 2 && !(solo && c == 4 && lane == 0), lane ? bar : tokb, lane ? 2048 : 8192);
        if (!single) while (__any_sync(~0u, clk() - t0 < d)) {}
        if (c >= 2) mbar_wait_wd(sb + B_HEMPTY + 8 * c, pp);
        mbar_wait_wd(sb + (c < 2 ? B_HEMPTY + 8 * c : c == 2 && !single ? B_PMEM : B_OB), pp);
        if ((c != 2 || single) && !(solo && c == 4)) { if (elect_one()) bulk_g2s(dst + 2048, tok, 8192, tokb); }
        if (single) {
          mbar_wait_wd(sb + B_OPI + (waited & 1) * 8, (waited >> 1) & 1);
          waited++;
          t0 = lds32(sb + SM_TOPI + (~waited & 1) * 4);
          if (solo && c == 0 && elect_one()) {
            mbar_expect(tokb, 8192);
            bulk_g2s(dst + 4 * 10240 + 2048, tok + 2048, 8192, tokb);
          }
          publish(waited);
          while (__any_sync(~0u, clk() - t0 < d)) {}
        }
        else if (c < 2) spin(prm.dh);
        if (elect_one()) bulk_g2s(dst, src, 2048, bar);
        if (c == 2 && !single) {
          mbar_wait_wd(sb + B_OB, pp);
          if (elect_one()) bulk_g2s(dst + 2048, tok, 8192, full);
        }
        g = 0;
        while (true) {
          mbar_wait_wd(bar, mph);
          mph ^= 1;
          const uint32_t v0 = lds32(dst + chk), v1 = lds32(dst + chk + 1024);
          if (__all_sync(~0u, v0 != ~0u && v1 != ~0u)) break;
          if (elect_one()) {
            mbar_expect(bar, 2048);
            bulk_g2s(dst, src, 2048, bar);
          }
          guard(g);
        }
        mbar_arrive_if(lane == 0, full, solo ? 2 : 1);
        TRACE(c < 2, m, 3 + 2 * c, gtl());
        TRACE(c < 2, m, 4 + 2 * c, g);
      }
    }
    publish(nslots);
    if (warp == 0) mbar_wait_wd(sb + B_END, 0);
  }
  __syncwarp();
  if (wid != 12 && lane0 == 0) mbar_arrive(sb + B_END);
  cluster_sync();
}
__device__ uint32_t g_xa[NBLK * 10 * 4096];
__device__ uint32_t g_h[NBLK * 24 * 4096];

enum { T_A = 0, T_F1 = 1, T_U = 2, T_D = 3, T_F2 = 4, T_NONE = 7 };
__host__ __device__ constexpr int c_phase(int type, int lb) { return C_O + type * 32 + lb; }
constexpr int C_TICKET = c_phase(5, 0), C_EXIT = C_TICKET + 1, C_USED = C_HALF + 2 * NBLK;
constexpr int G_NST = 7;
constexpr uint32_t GS_RED = G_NST * 32768, GS_BAR = GS_RED + 1088, G_SMEM = GS_BAR + 224;
constexpr uint32_t GB_FULL = GS_BAR, GB_EMPTY = GS_BAR + 64, GB_ORD = GS_BAR + 128, GB_READY = GS_BAR + 144, GB_ACK = GS_BAR + 152, GB_GATE = GS_BAR + 160, GB_SIG = GS_BAR + 176, GB_SACK = GS_BAR + 192,
                   GS_SIG = GS_BAR + 208, GS_COL = GS_BAR + 216;
#define FPL 6
constexpr int NF = 16;
constexpr int G_EARLY = 36;
constexpr int G_LATE = 96, PL = 6, ML = 8, DL = 30, TL = 10;
constexpr int GRC = 112, GRP = 32;
constexpr uint32_t E_UP = 1u << 8, E_HALF = 1u << 28, E_GRP = 1u << 29, E_HAND = 1u << 30, E_EXCL = 1u << 31;

struct GParams {
  __nv_bfloat16* out;
  const uint32_t* x;
  int moff, gd;
  int pend;
  uint8_t perm[G_EARLY], first[9];
  uint8_t need[5][2 * NBLK];
  uint32_t tab[G_EARLY * (PL + ML + DL) + G_LATE * TL];
};
constexpr int EL = PL + ML + DL, TAB_TAIL = G_EARLY * EL;
struct GIter {
  int p, left, period;
  uint32_t e, type, lb, n0, kb0, nkb;
  bool gemm, valid;
  DI GIter(const GParams& prm, int col) {
    if (col < G_EARLY) { p = col * EL; left = PL; period = 0; }
    else { p = TAB_TAIL + (col - G_EARLY) * TL; left = TL; period = prm.pend; }
  }
  DI bool next(const GParams& prm, int col) {
    do {
      if (left == 0) {
        if (++period > prm.pend) return false;
        left = period < prm.pend ? ML : DL;
        if (period > 1 && period < prm.pend) p -= ML;
      }
      e = prm.tab[p++]; left--;
    } while ((e & 7) == T_NONE);
    const int b = (e >> 4) & 15, blk = period < prm.pend ? period - b : b;
    type = e & 7; valid = blk >= 0; lb = (e & 8) * 2 + (blk & 15); n0 = (e >> 9) & 127; kb0 = (e >> 16) & 127;
    gemm = type != T_F1 && type != T_F2;
    nkb = valid ? (e >> 23) & 31 : 0;
    return true;
  }
  DI int id_(int pend) const { return period < pend ? period * 10 + ML - left : 160 + DL - left; }
};

#define GLOG(nt, i, v)
template <int TA> DI void wg_ss128(float* d, uint64_t da, uint64_t db, int sc) {
  asm volatile("{.reg .pred p; setp.ne.b32 p, %66, 0;\n"
               "wgmma.mma_async.sync.aligned.m64n128k16.f32.bf16.bf16 "
               "{%0,%1,%2,%3,%4,%5,%6,%7,%8,%9,%10,%11,%12,%13,%14,%15,%16,%17,%18,%19,%20,%21,%22,%23,%24,%25,%26,%27,%28,%29,%30,%31,"
               "%32,%33,%34,%35,%36,%37,%38,%39,%40,%41,%42,%43,%44,%45,%46,%47,%48,%49,%50,%51,%52,%53,%54,%55,%56,%57,%58,%59,%60,%61,%62,%63}, "
               "%64, %65, p, 1, 1, %67, 1;}"
               : ACC16(d, 0), ACC16(d, 16), ACC16(d, 32), ACC16(d, 48) : "l"(da), "l"(db), "r"(sc), "n"(TA));
}

template <int TA> DI void g_mainloop(float* acc, uint32_t sb, uint32_t hand, uint32_t gate, int nkb, int cw, int lane, uint32_t st, uint32_t ph) {
  const uint64_t da0 = (TA ? mkdesc(SMEM0, 4096, 512, 2) : mkdesc(SMEM0, 128, 1024, 0)) + (cw >> 2) * 512;
  const uint64_t db0 = mkdesc(SMEM0 + 16384, 8192, 1024, 1);
  uint32_t prev = 0;
#pragma unroll 1
  for (int kb = 0; kb < nkb; kb++) {
    mbar_wait(sb + GB_FULL + 8 * st, ph);
    mbar_wait(gate, 1);
    const uint64_t da = da0 + st * 2048, db = db0 + st * 2048;
    wg_fence();
#pragma unroll
    for (int k = 0; k < 4; k++) wg_ss128<TA>(acc, da + k * (TA ? 64 : 16), db + k * 128, 1);
    wg_commit();
    mbar_arrive_if(hand && kb == nkb - 1 && lane == 0, hand);
    wg_wait<1>();
    mbar_arrive_if(kb > 0 && lane == 0, sb + GB_EMPTY + 8 * prev);
    prev = st;
    if (++st == G_NST) { st = 0; ph ^= 1; }
  }
  wg_wait<0>();
  reg_fence<64>(acc);
  mbar_arrive_if(lane == 0, sb + GB_EMPTY + 8 * prev);
}

__global__ void __launch_bounds__(640, 1)
g_kernel(const __grid_constant__ CUtensorMap mapWo, const __grid_constant__ CUtensorMap mapWg, const __grid_constant__ CUtensorMap mapWu,
         const __grid_constant__ CUtensorMap mapWd, const __grid_constant__ GParams prm) {
  const uint32_t sb = smem_base();
  const int wid = __shfl_sync(~0u, threadIdx.x >> 5, 0), lane = threadIdx.x & 31;
  if (threadIdx.x == 0) {
    if ((sb & 0x3FFFF) != SMEM0) __trap();
    {
      uint32_t sm; asm volatile("mov.u32 %0, %%smid;" : "=r"(sm));
      uint32_t* const tk = &g_cnt[C_TICKET * CSTRIDE];
      uint32_t c = atomicAdd(tk, 1);
      if (c < G_EARLY) {
        const uint32_t k = sm < 64 ? (sm >> 1) & 7 : sm < 120 ? 1 + ((sm - 64) >> 1) % 7 : sm < 124 ? 1 + ((sm >> 1) & 1) : 0;
        const uint32_t t = atomicAdd(tk + 1 + k, 1);
        atomicAdd(tk + 9, 1);
        if (t < prm.first[k + 1] - prm.first[k]) c = prm.perm[prm.first[k] + t];
        else {
          uint32_t o = atomicAdd(tk + 10, 1), g = 0;
          while (ld_acq(tk + 9) < G_EARLY) guard(g);
          for (int j = 0; j < 8; j++)
            for (uint32_t i = prm.first[j] + ld_acq(tk + 1 + j); i < prm.first[j + 1]; i++) if (o-- == 0) c = prm.perm[i];
        }
      }
      sts32(sb + GS_COL, c);
    }
    for (int i = 0; i < G_NST; i++) { mbar_init(sb + GB_FULL + 8 * i, 1); mbar_init(sb + GB_EMPTY + 8 * i, 8); }
    mbar_init(sb + GB_ORD, 8); mbar_init(sb + GB_ORD + 8, 8); mbar_init(sb + GB_READY, 1); mbar_init(sb + GB_ACK, 1);
    mbar_init(sb + GB_GATE, 1); mbar_init(sb + GB_GATE + 8, 1);
    mbar_init(sb + GB_SIG, 8); mbar_init(sb + GB_SIG + 8, 8); mbar_init(sb + GB_SACK, 1); mbar_init(sb + GB_SACK + 8, 1);
    fence_async_smem();
  }
  __syncthreads();
  const int col = __shfl_sync(~0u, lds32(sb + GS_COL), 0);

  if (wid >= 16) {
    GIter t(prm, col);
    asm volatile("setmaxnreg.dec.sync.aligned.u32 %0;" ::"n"(GRP));
    uint32_t st = 0, ph = 1, k = 0;
    if (wid == 16) {
      while (t.next(prm, col)) {
        const CUtensorMap* m0 = t.type == T_A ? &mapWo : t.type == T_U ? &mapWg : &mapWd;
        const CUtensorMap* m1 = t.type == T_U ? &mapWu : m0;
        const int c0 = t.type == T_U ? t.n0 * 64 : (t.n0 & 7) * 128, c1 = t.type == T_U ? c0 : c0 + 64;
        if ((t.e & (E_HALF | E_UP)) == E_UP) poll_ge(&g_cnt[c_phase(t.type, t.lb) * CSTRIDE], prm.need[t.type][t.lb]);
#pragma unroll 1
        for (uint32_t kb = t.kb0; kb < t.kb0 + t.nkb; kb++) {
          mbar_wait(sb + GB_EMPTY + 8 * st, ph);
          if (elect_one()) {
            const uint32_t full = sb + GB_FULL + 8 * st, dst = sb + st * 32768;
            mbar_expect(full, (t.e & E_HALF) ? 24576 : 32768);
            tma_2d(dst + 16384, m0, c0, kb * 64, full);
            tma_2d(dst + 24576, m1, c1, kb * 64, full);
          }
          if (++st == G_NST) { st = 0; ph ^= 1; }
        }
      }
    } else if (wid == 17) {
      while (t.next(prm, col)) {
        if (!t.nkb) continue;
        const char* asrc = t.type == T_A ? (const char*)g_oT + (size_t)t.lb * (96 * 16384)
                         : t.type == T_U ? (const char*)g_xa + (size_t)(t.lb & 15) * (10 * 16384) : (const char*)g_h + (size_t)(t.lb & 15) * (24 * 16384);
        const uint32_t up = (t.e & E_HALF) ? (t.e & E_UP) * 32 : 0;
        GLOG(t.id_(prm.pend), 1, gtime());
        mbar_wait(sb + GB_READY, k & 1);
        mbar_arrive_if(lane == 0, sb + GB_ACK);
        k++;
#pragma unroll 1
        for (uint32_t kb = t.kb0; kb < t.kb0 + t.nkb; kb++) {
          mbar_wait(sb + GB_EMPTY + 8 * st, ph);
          if (elect_one()) bulk_g2s(sb + st * 32768 + up, asrc + (size_t)kb * 16384 + up, (t.e & E_HALF) ? 8192 : 16384, sb + GB_FULL + 8 * st);
          if (++st == G_NST) { st = 0; ph ^= 1; }
        }
      }
    } else if (wid == 18) {
      while (t.next(prm, col)) {
        if (!t.nkb) continue;
        const bool lower = t.type == T_A && (t.e & (E_HALF | E_UP)) == E_HALF;
        poll_ge(&g_cnt[(lower ? C_HALF + t.lb : c_phase(t.type, t.lb)) * CSTRIDE], prm.need[t.type][t.lb]);
        fence_async_global();
        GLOG(t.id_(prm.pend), 2, gtime());
        mbar_wait(sb + GB_ACK, (k & 1) ^ 1);
        mbar_arrive_if(lane == 0, sb + GB_READY);
        k++;
      }
    } else {
      uint32_t live = 3, par = 0, g = 0;
      while (live) {
        const bool ev = lane < 2 && ((live >> lane) & 1) && mbar_test(sb + GB_SIG + 8 * lane, (par >> lane) & 1);
        const uint32_t evs = __ballot_sync(~0u, ev);
        if (!evs) { guard(g); __nanosleep(20); continue; }
        const uint32_t msg = ev ? lds32(sb + GS_SIG + 4 * lane) : 0;
        mbar_arrive_if(ev, sb + GB_SACK + 8 * lane);
        mbar_arrive_if(msg >> 31, sb + GB_GATE + 8 * lane);
        if (msg) red_rel(&g_cnt[(msg & 0xffff) * CSTRIDE], (msg >> 16) & 255);
        par ^= evs;
        live &= ~__ballot_sync(~0u, ev && !msg);
        g = 0;
      }
      asm volatile("griddepcontrol.wait;" ::: "memory");
      if (col < 80 && lane < 16) g_mem[(col >> 4) * 2048 + (lane >> 3) * 1024 + 512 + prm.moff + (col & 15) * 8 + (lane & 7)] = make_uint4(~0u, ~0u, ~0u, ~0u);
      uint32_t last = 0;
      if (lane == 0) last = atomicAdd(&g_cnt[C_EXIT * CSTRIDE], 1) == gridDim.x - 1;
      if (__shfl_sync(~0u, last, 0)) {
        g_cnt[C_TICKET * CSTRIDE + lane] = 0;
        for (int i = lane; i < C_USED; i += 32) g_cnt[i * CSTRIDE] = 0;
      }
    }
  } else {
    asm volatile("setmaxnreg.inc.sync.aligned.u32 %0;" ::"n"(GRC));
    const int cw = wid & 7, wk = wid >> 3;
    GIter t(prm, col);
    uint32_t pos = 0, seen = 0, waited = 0;
    uint32_t nsig = 0;
    auto signal = [&](uint32_t msg) {
      mbar_wait(sb + GB_SACK + 8 * wk, (nsig++ & 1) ^ 1);
      if (cw == 0) sts32(sb + GS_SIG + 4 * wk, msg);
      __syncwarp();
      mbar_arrive_if(lane == 0, sb + GB_SIG + 8 * wk);
    };
    if (col < G_EARLY) {
      spin(prm.gd);
#pragma unroll 1
      for (int rg = 96 + col * 2 + wk; rg < 256; rg += 2 * G_EARLY) {
        uint32_t a[10];
        const uint32_t* src = prm.x + (size_t)(rg * 8 + (lane >> 2)) * (DM / 2) + cw * 40 + (lane & 3);
#pragma unroll
        for (int i = 0; i < 10; i++) a[i] = __ldg(src + i * 4);
        first_ln(a, rg, sb + GS_RED + wk * 512, cw, lane, 1 + wk);
        signal((C_XN + (rg >> 4)) | ((XN_TARGET / NF) << 16));
        bar_sync(1 + wk, 256);
      }
    }
    while (t.next(prm, col)) {
      const uint32_t pos0 = pos;
      pos = (pos + t.nkb) % (2 * G_NST);
      if (((t.e >> 29) & 1) != wk) { seen += (t.e >> 30) & 1; continue; }
      const uint32_t type = t.type, blk = t.lb & 15, layer = t.lb >> 4, n0 = t.n0;
      if (cw == 0 && t.valid) GLOG(t.id_(prm.pend), 0, 0x80000000u | type | (t.lb << 3) | (n0 << 8) | (t.nkb << 16));
      if (!t.gemm) {
        if (!t.valid) continue;
        const int rg = blk * 16 + n0;
        float4 v[5];
        const int off = (n0 * 40 + cw * 5) * 32 + lane, npl = t.kb0;
        const uint2* src = acc_planes(t.lb, type == T_F2) + off;
        if (cw == 0) {
          poll_ge(&g_cnt[c_phase(type, t.lb) * CSTRIDE], prm.need[type][t.lb]);
          mbar_arrive_if((t.e & E_EXCL) && lane == 0, sb + GB_GATE + 8 * wk);
          GLOG(t.id_(prm.pend), 2, gtime()); GLOG(t.id_(prm.pend), 3, gtime());
        }
        bar_sync(1 + wk, 256);
        {
          const uint32_t eye = (lane >> 3) == (lane & 3) ? ((lane & 4) ? 0x3f800000u : 0x00003f80u) : 0u;
#pragma unroll
          for (int i = 0; i < 5; i++) v[i] = make_float4(0.f, 0.f, 0.f, 0.f);
#pragma unroll 1
          for (int p0 = 0; p0 < npl; p0 += FPL) {
            uint32_t r[FPL / 2][5][4];
#pragma unroll
            for (int p = 0; p < FPL; p++)
#pragma unroll
              for (int i = 0; i < 5; i++) {
                const uint2 w = p0 + p < npl ? __ldcg(src + (size_t)(p0 + p) * PLANE + i * 32) : make_uint2(0, 0);
                r[p >> 1][i][(p & 1) * 2] = w.x; r[p >> 1][i][(p & 1) * 2 + 1] = w.y;
              }
#pragma unroll
            for (int p = 0; p < FPL / 2; p++) {
              if (p0 + 2 * p >= npl) break;
              if (t.e & E_EXCL) {
#pragma unroll
                for (int i = 0; i < 5; i++) mma16816(&v[i].x, r[p][i], eye, eye);
              } else {
#pragma unroll
                for (int i = 0; i < 5; i++) {
                  const uint32_t* w = r[p][i];
                  v[i].x += blo(w[0]) + blo(w[2]); v[i].y += bhi(w[0]) + bhi(w[2]); v[i].z += blo(w[1]) + blo(w[3]); v[i].w += bhi(w[1]) + bhi(w[3]);
                }
              }
            }
          }
        }
        if (type == T_F2 && layer == 1) {
          uint2* dst = (uint2*)prm.out + (size_t)(rg * 8 + (lane >> 2)) * (DM / 4) + cw * 20 + (lane & 1) * 2 + ((lane >> 1) & 1);
#pragma unroll
          for (int i = 0; i < 5; i++) {
            const uint32_t a = pack2(v[i].x, v[i].y), b = pack2(v[i].z, v[i].w);
            const uint32_t o = __shfl_xor_sync(~0u, (lane & 1) ? a : b, 1);
            dst[i * 4] = (lane & 1) ? make_uint2(o, b) : make_uint2(a, o);
          }
        } else {
          uint2* nx = (type == T_F1 ? acc_planes(t.lb, 1) : acc_planes(NBLK + blk, 0)) + off;
#pragma unroll
          for (int i = 0; i < 5; i++) {
            const uint2 w = make_uint2(pack2(v[i].x, v[i].y), pack2(v[i].z, v[i].w));
            nx[i * 32] = w;
            v[i] = make_float4(blo(w.x), bhi(w.x), blo(w.y), bhi(w.y));
          }
          float mean, rstd;
          ln_stats(v, sb + GS_RED + wk * 512, cw, lane, 1 + wk, mean, rstd);
          if (type == T_F2) store_img<4, 2048>(xn_row_group(1, rg) + lane, v, cw, mean, rstd);
          else store_img<3, 4096>(g_xa + (size_t)(blk * 10 * 4096 + n0 * 256) + lane, v, cw, mean, rstd);
        }
      } else {
        float acc[64];
#pragma unroll
        for (int j = 0; j < 64; j++) acc[j] = 0.f;
        if (waited != seen) { mbar_wait(sb + GB_ORD + 8 * (wk ^ 1), waited & 1); waited++; }
        const uint32_t hand = (t.e & E_HAND) ? sb + GB_ORD + 8 * wk : 0;
        if (!t.valid) { mbar_arrive_if(hand && lane == 0, hand); continue; }
        if (cw == 0) GLOG(t.id_(prm.pend), 3, gtime());
        const uint32_t ph = pos0 >= G_NST, st = pos0 - ph * G_NST, early = (t.e & E_EXCL) ? 0 : hand;
        const bool idle = (t.e & E_HALF) && ((t.e >> 8) & 1) != (cw >> 2);
        if (idle) {
          uint32_t s2 = st, p2 = ph;
#pragma unroll 1
          for (uint32_t kb = 0; kb < t.nkb; kb++) {
            mbar_wait(sb + GB_FULL + 8 * s2, p2);
            mbar_arrive_if(lane == 0, sb + GB_EMPTY + 8 * s2);
            if (++s2 == G_NST) { s2 = 0; p2 ^= 1; }
          }
          mbar_arrive_if(early && lane == 0, early);
        } else if (type == T_A) g_mainloop<1>(acc, sb, early, sb + GB_GATE + 8 * (wk ^ 1), t.nkb, cw, lane, st, ph);
        else g_mainloop<0>(acc, sb, early, sb + GB_GATE + 8 * (wk ^ 1), t.nkb, cw, lane, st, ph);
        if (cw == 0) GLOG(t.id_(prm.pend), 4, gtime());
        if (idle) {
        } else if (type == T_U) {
          uint32_t* dst = g_h + (size_t)((blk * 24 + n0) * 4096 + cw * 512) + lane;
#pragma unroll
          for (int j = 0; j < 8; j++) {
            float h[4];
#pragma unroll
            for (int e = 0; e < 4; e++) {
              float th;
              asm("tanh.approx.f32 %0, %1;" : "=f"(th) : "f"(0.5f * acc[4 * j + e]));
              h[e] = acc[32 + 4 * j + e] * fmaf(th, 0.5f, 0.5f);
            }
            dst[j * 32] = pack2(h[0], h[1]);
            dst[j * 32 + 256] = pack2(h[2], h[3]);
          }
        } else {
          uint2* dst = acc_planes(t.lb, type == T_D) + (size_t)((1 + (n0 >> 3)) * PLANE + (2 * cw * 40 + (n0 & 7) * 8) * 32) + lane;
#pragma unroll
          for (int j = 0; j < 16; j++) {
            const float* a = acc + (j >> 1) * 8 + (j & 1) * 2;
            dst[(j >> 1) * 32 + (j & 1) * 1280] = make_uint2(pack2(a[0], a[1]), pack2(a[4], a[5]));
          }
        }
        mbar_arrive_if(hand != early && lane == 0, hand);
      }
      if (cw == 0) GLOG(t.id_(prm.pend), 5, gtime());
      if (cw == 0) GLOG(t.id_(prm.pend), 6, gtime());
      if (type == T_F2 && layer == 1) mbar_arrive_if((t.e & E_EXCL) && cw == 0 && lane == 0, sb + GB_GATE + 8 * wk);
      else
        signal((type != T_F2 ? c_phase(type + 1, t.lb) | (1 << 16) : (C_XN + NBLK + blk) | ((XN_TARGET / NF) << 16)) | (t.gemm ? 0 : t.e & E_EXCL));
    }
    signal(0);
  }
}

typedef CUresult (*EncodeFn)(CUtensorMap*, CUtensorMapDataType, cuuint32_t, void*, const cuuint64_t*, const cuuint64_t*, const cuuint32_t*,
                             const cuuint32_t*, CUtensorMapInterleave, CUtensorMapSwizzle, CUtensorMapL2promotion, CUtensorMapFloatOOBfill);
static CUtensorMap make_map(EncodeFn fn, const void* p, uint64_t inner, uint64_t outer, uint32_t bi, uint32_t bo) {
  CUtensorMap m;
  cuuint64_t dims[2] = {inner, outer}, str[1] = {inner * 2};
  cuuint32_t box[2] = {bi, bo}, es[2] = {1, 1};
  fn(&m, CU_TENSOR_MAP_DATA_TYPE_BFLOAT16, 2, (void*)p, dims, str, box, es, CU_TENSOR_MAP_INTERLEAVE_NONE, CU_TENSOR_MAP_SWIZZLE_128B,
     CU_TENSOR_MAP_L2_PROMOTION_L2_256B, CU_TENSOR_MAP_FLOAT_OOB_FILL_NONE);
  return m;
}
struct Tune {
  int lag = 11, excl = 7, gonly = 0, xl = 1, ronly = 0, pn = 30;
  int da = 100, db = 350, dc = 650, dd = 650, d2 = 2000, p1 = 400, p2 = 800;
  int ea = 60, eb = 310, ec = 550, ed = 550, e2 = 2200, q1 = 200, q2 = 400, d3 = 60, moff = 192, ds = 400, dh = 60, pa = 0, pb = 0, pc = 0, pd = 0, pe = 0, pf = 0, pg = 0, ph = 0, hold = 1, wpf = 4, gd = 22000, dq = 600, sl = 18;
};
static void fill_r(RParams& p, const Tune& t, int lag, int n0, int n1) {
  r_fill_desc(p);
  p.nslots = 0; p.d3 = t.d3; p.pn = t.pn; p.moff = t.moff; p.ds = t.ds; p.dh = t.dh; p.dq = t.dq;
  for (int c = 0; c < 5; c++) { p.d2[c] = t.d2 + (c == 0 ? 0 : c < 3 ? t.p1 : t.p2); p.d2[5 + c] = t.e2 + (c == 0 ? 0 : c < 3 ? t.q1 : t.q2); }
  const int d1[8] = {t.da, t.db, t.dc, t.dd, t.ea, t.eb, t.ec, t.ed};
  for (int i = 0; i < 8; i++) p.d1[i] = d1[i];
  int last[2] = {0, 0}, n = 0;
  for (int s0 = 0; s0 < NSEG + lag; s0++)
    for (int l = 0; l < 2; l++) {
      const int s = l ? s0 - lag : s0;
      if (s < 0 || s >= NSEG) continue;
      if (n >= n0 && n < n1) { p.slot[p.nslots] = s | (l << 6) | (last[l] << 8) | (((s & 3) == 3 ? C_O + l * NBLK + s / 4 : s == (l ? 61 : 1) ? C_HALF + l * NBLK + s / 4 : 0) << 16); last[l] = ++p.nslots; }
      n++;
    }
  for (int i = 0; i + 1 < p.nslots; i++) if (((p.slot[i] ^ p.slot[i + 1]) >> 6) & 1) p.slot[i] |= 128;
}
static uint32_t g_entry(int grp, int type, int layer, int blk, int i, int ks) {
  int n0 = i, kb0 = 0, kb1 = type == T_U ? 10 : 0;
  if (type == T_F1 || type == T_F2) kb0 = kb1 = ks + 1;
  if (type == T_A || type == T_D) {
    const int KB = type == T_A ? 96 : 24, sp = i / 5;
    n0 = i % 5 | (sp << 3); kb0 = sp * KB / ks; kb1 = (sp + 1) * KB / ks;
  }
  return type | (layer << 3) | (blk << 4) | (n0 << 9) | (kb0 << 16) | ((kb1 - kb0) << 23) | (grp ? E_GRP : 0);
}
static bool g_is_gemm(uint32_t e) { return (e & 7) == T_A || (e & 7) == T_U || (e & 7) == T_D; }
static void g_handover(uint32_t* e, int len) {
  uint32_t next = 0;
  for (int i = len - 1; i >= 0; i--)
    if (g_is_gemm(e[i])) { if ((e[i] & E_GRP) != next) e[i] |= E_HAND; next = e[i] & E_GRP; }
}
struct GList {
  GParams& g; uint32_t* tab; int ncol, stride, len, n[G_LATE], load[G_LATE], grp[G_LATE];
  GList(GParams& g_, uint32_t* t, int nc, int st, int l) : g(g_), tab(t), ncol(nc), stride(st), len(l) { for (int c = 0; c < nc; c++) { n[c] = load[c] = 0; grp[c] = 1; } }
  void add(int type, int lb, int ks, int c0, int c1, uint32_t flags = 0, int i0 = 0, int i1 = 999, int step = 1) {
    const int half = (flags & E_HALF) != 0, ln = type == T_F1 || type == T_F2;
    const int cnt = (type == T_U ? 24 : ln ? NF : 5 * ks) << half;
    if (type < T_F2) g.need[type + 1][lb] = cnt;
    int used[G_LATE] = {0};
    for (int i = i0; i < cnt && i < i1; i += step) {
      int best = c0;
      for (int c = c0; c < c1; c++) if (used[c] < used[best] || (used[c] == used[best] && load[c] < load[best])) best = c;
      used[best]++;
      if (!ln) grp[best] ^= 1;
      const uint32_t e = g_entry(grp[best], type, lb >> 4, lb & 15, i >> half, ks) | flags | (ln ? E_EXCL : 0) | ((i & half) ? E_UP : 0);
      if (n[best] >= len) abort();
      tab[best * stride + n[best]++] = e;
      load[best] += (((e >> 23) & 31) >> half) + 2;
    }
  }
  void put(int c, uint32_t e) { if (n[c] >= len) abort(); tab[c * stride + n[c]++] = e; if (g_is_gemm(e)) grp[c] = (e & E_GRP) != 0; }
  void finish() { for (int c = 0; c < ncol; c++) g_handover(tab + c * stride, len); }
};
static void fill_g(GParams& g, const Tune& t, void* out) {
  g.out = (__nv_bfloat16*)out;  g.pend = NBLK - 2;
  for (int b = 0; b < 2 * NBLK; b++) {
    g.need[T_A][b] = 96; g.need[T_F1][b] = 20; g.need[T_U][b] = NF; g.need[T_D][b] = 32; g.need[T_F2][b] = 15;
  }
  {
    const uint8_t perm[G_EARLY] = {0, 1, 2, 3, 16, 17, 18, 19, 34, 35, 4, 20, 21, 15, 22, 23, 5, 6, 7, 8, 9, 24, 25, 26, 10, 11, 12, 13, 14, 27, 28, 29, 30, 31, 32, 33};
    const uint8_t first[9] = {0, 10, 13, 16, 20, 24, 28, 32, 36};
    const int* pk = &t.pa;
    for (int i = 0; i < G_EARLY; i++) g.perm[i] = t.pa ? (pk[i / 5] >> (6 * (i % 5))) & 63 : perm[i];
    for (int i = 0; i < 9; i++) g.first[i] = first[i];
  }
  for (uint32_t& e : g.tab) e = T_NONE;
  GList pr(g, g.tab, G_EARLY, EL, PL);
  pr.add(T_A, 0, 7, 1, 36, E_HALF, 0, 999, 2); pr.add(T_A, 0, 7, 1, 36, E_HALF, 1, 999, 2); pr.add(T_F1, 0, 7, 20, 36); pr.add(T_U, 0, 0, 12, 36);
  pr.add(T_D, 0, 3, 20, 36); pr.add(T_F2, 0, 3, 20, 36);
  pr.finish();
  const int d = 3;
  const uint32_t xa = (t.excl & 1) ? E_EXCL : 0, xu = (t.excl & 2) ? E_EXCL : 0, xd = (t.excl & 4) ? E_EXCL : 0;
  for (int c = 0; c < G_EARLY; c++) {
    uint32_t* e = g.tab + c * EL + PL;
    if (c < 20) {
      *e++ = g_entry(0, T_A, 0, 0, c, 4) | xa;
      if (c < NF) *e++ = g_entry(0, T_F1, 0, 0, c, 4) | ((t.xl & 1) ? E_EXCL : 0);
      *e++ = g_entry(1, T_A, 1, d, c, 4);
      if (c >= 20 - NF) *e++ = g_entry(1, T_F1, 1, d, c - (20 - NF), 4);
    } else {
      const int j = c - 20;
      const uint32_t hf = E_HALF | ((j & 1) ? E_UP : 0);
      *e++ = g_entry(0, T_U, 0, 0, j, 0);
      *e++ = g_entry(1, T_U, 0, 0, 16 + j / 2, 0) | hf | xu;
      *e++ = g_entry(0, T_U, 1, d + 1, 16 + j / 2, 0) | hf;
      if (j < 15) *e++ = g_entry(1, T_D, 0, 0, j, 3) | xd;
      *e++ = g_entry(1, T_F2, 0, 0, j, 3) | ((t.xl & 2) ? E_EXCL : 0);
      if (j < 15) *e++ = g_entry(0, T_D, 1, d + 2, j, 3);
      *e++ = g_entry(0, T_U, 1, d + 1, j, 0);
      *e++ = g_entry(1, T_F2, 1, d + 2, j, 3);
    }
    g_handover(g.tab + c * EL + PL, ML);
  }
  GList dr(g, g.tab + PL + ML, G_EARLY, EL, DL);
  GList tl(g, g.tab + TAB_TAIL, G_LATE, TL, TL);
  const int L1 = NBLK;
  auto ufull = [&](int lb) { dr.add(T_U, lb, 0, 20, 36, 0, 0, 16); g.need[T_D][lb] = 32; };
  auto uhalf = [&](int lb) { dr.add(T_U, lb, 0, 20, 36, E_HALF, 32); g.need[T_D][lb] = 32; };
  for (int c = 0; c < G_EARLY; c++)
    for (int i = 0; i < ML; i++) {
      uint32_t e = g.tab[c * EL + PL + i] & ~E_HAND;
      const uint32_t ty = e & 7;
      if (ty == T_NONE || ((e & 8) && (ty == T_F2 || (ty == T_U && !(e & E_HALF))))) continue;
      e = (e & ~0xf0u) | (14 - ((e >> 4) & 15)) << 4;
      dr.put(c, e | (ty == T_F2 ? E_EXCL : 0));
    }
  dr.add(T_A, 15, 4, 0, 20, E_EXCL);
  dr.add(T_F1, 15, 4, 0, 16);
  dr.add(T_U, 15, 0, 12, 36, E_EXCL);
  for (int c = 0; c < 20; c++) {
    const int tile = c % 5, sp = c / 5, len = tile < 2 ? (96 - t.sl) / 3 : 48 - t.sl, nl = tile < 2 ? 3 : 2;
    const int k0 = sp <= nl ? sp * len : nl * len + t.sl, nk = sp < nl ? len : sp == 3 ? 96 - k0 : t.sl;
    dr.put(c, (g_entry(dr.grp[c] ^ 1, T_A, 1, 12, c, 4) & ~0x0fff0000u) | k0 << 16 | nk << 23);
  }
  dr.add(T_F1, L1 + 12, 4, 0, 16);
  uhalf(L1 + 11);
  dr.add(T_D, 15, 3, 20, 36, E_EXCL); dr.add(T_F2, 15, 3, 20, 36);
  dr.add(T_A, L1 + 13, 4, 0, 20); dr.add(T_F1, L1 + 13, 4, 0, 20);
  ufull(L1 + 10); ufull(L1 + 11);
  dr.add(T_D, L1 + 10, 3, 20, 36);
  ufull(L1 + 12); uhalf(L1 + 12);
  dr.add(T_A, L1 + 14, 4, 0, 20);
  dr.add(T_A, L1 + 15, 7, 0, 35, E_HALF, 0, 999, 2); dr.add(T_A, L1 + 15, 7, 0, 35, E_HALF | E_EXCL, 1, 999, 2);
  dr.add(T_F1, L1 + 14, 4, 0, 16);
  dr.add(T_F1, L1 + 15, 7, 20, 36);
  dr.add(T_F2, L1 + 9, 3, 4, 20);
  dr.add(T_F2, L1 + 10, 3, 0, 16); dr.add(T_F2, L1 + 11, 3, 4, 20);  dr.add(T_F2, L1 + 12, 3, 0, 20);
  dr.add(T_D, L1 + 13, 3, 20, 36, (t.hold & 1) ? E_UP : 0); dr.add(T_F2, L1 + 13, 3, 20, 36);
  dr.finish();
  tl.add(T_D, L1 + 11, 3, 0, 24); tl.add(T_D, L1 + 12, 3, 72, G_LATE);
  tl.add(T_U, L1 + 14, 0, 0, 24); tl.add(T_U, L1 + 13, 0, 24, 48);
  tl.add(T_D, L1 + 14, 4, 0, 48, E_HALF);
  tl.add(T_F2, L1 + 14, 4, 0, 48);
  tl.add(T_U, L1 + 15, 0, 48, G_LATE, E_HALF);
  tl.add(T_D, L1 + 15, 4, 48, G_LATE, E_HALF);
  tl.add(T_F2, L1 + 15, 4, 48, G_LATE);
  tl.finish();
}
static void launch_all(void* const* d_in, void* d_out, const Tune& t, cudaStream_t st) {
  static EncodeFn fn = nullptr;
  if (!fn) {
    void* f = nullptr;
    cudaDriverEntryPointQueryResult qr;
    cudaGetDriverEntryPoint("cuTensorMapEncodeTiled", &f, cudaEnableDefault, &qr);
    fn = (EncodeFn)f;
    cudaFuncSetAttribute(r_kernel, cudaFuncAttributeMaxDynamicSharedMemorySize, R_SMEM);
    cudaFuncSetAttribute(g_kernel, cudaFuncAttributeMaxDynamicSharedMemorySize, G_SMEM);
  }
  const CUtensorMap mq = make_map(fn, d_in[2], HD, DM, 64, 128), mk = make_map(fn, d_in[3], HD, DM, 64, 128), mv = make_map(fn, d_in[4], HD, DM, 64, 128),
                    mo = make_map(fn, d_in[5], DM, HD, 64, 64), mg = make_map(fn, d_in[8], FF, DM, 64, 64), mu = make_map(fn, d_in[9], FF, DM, 64, 64),
                    md = make_map(fn, d_in[10], DM, FF, 64, 64);
  auto launch_r = [&](int lag, int n0, int n1) {
    RParams p;
    fill_r(p, t, lag, n0, n1);
    for (int i = 0; i < 4; i++) p.w[i] = (const char*)d_in[2 + i];
    p.mem0 = (const uint4*)d_in[1]; p.x = (const uint32_t*)d_in[0]; p.pf = t.wpf;
    cudaLaunchConfig_t cfg = {};
    cfg.gridDim = dim3(3, NH); cfg.blockDim = dim3(512); cfg.dynamicSmemBytes = R_SMEM; cfg.stream = st;
    cudaLaunchAttribute at[1];
    at[0].id = cudaLaunchAttributeClusterDimension; at[0].val.clusterDim.x = 3; at[0].val.clusterDim.y = 1; at[0].val.clusterDim.z = 1;
    cfg.attrs = at; cfg.numAttrs = 1;
    cudaLaunchKernelEx(&cfg, r_kernel, mq, mk, mv, mo, p);
  };
  auto launch_g = [&](const GParams& g, bool pdl) {
    cudaLaunchConfig_t cfg = {};
    cfg.gridDim = dim3(132); cfg.blockDim = dim3(640); cfg.dynamicSmemBytes = G_SMEM; cfg.stream = st;
    cudaLaunchAttribute at[2];
    at[0].id = cudaLaunchAttributeProgrammaticStreamSerialization; at[0].val.programmaticStreamSerializationAllowed = 1;
    cfg.attrs = at; cfg.numAttrs = pdl ? 1 : 0;
    cudaLaunchKernelEx(&cfg, g_kernel, mo, mg, mu, md, g);
  };
  GParams g;
  fill_g(g, t, d_out);
  g.moff = t.moff; g.gd = t.gd; g.x = (const uint32_t*)d_in[0];
  launch_r(t.lag, 0, 2 * NSEG);
  launch_g(g, true);
}

extern "C" void kernel_launch(void* const* d_in, const int* in_sizes, int n_in, void* d_out, int out_size) {
  launch_all(d_in, d_out, Tune(), cudaStreamPerThread);
}
```

```cpp
#include <cuda_runtime.h>
#include <cuda_bf16.h>
#include <cuda.h>
#include <stdint.h>
#include <stdlib.h>

constexpr int SEQ = 2048, DM = 640, NH = 32, DH = 192, HD = NH * DH, FF = 1536;
constexpr int NSEG = 64, SEGL = 32, NMEM = 8;
constexpr int NBLK = 16;

#define DI __device__ __forceinline__

DI uint32_t smem_base() {
  extern __shared__ __align__(1024) unsigned char smem_raw[];
  uint32_t a;
  asm volatile("{.reg .u64 t; cvta.to.shared.u64 t, %1; cvt.u32.u64 %0, t;}" : "=r"(a) : "l"(smem_raw));
  return a;
}
DI uint32_t mapa(uint32_t a, uint32_t r) {
  uint32_t o;
  asm("mapa.shared::cluster.u32 %0, %1, %2;" : "=r"(o) : "r"(a), "r"(r));
  return o;
}
DI void mbar_init(uint32_t bar, uint32_t cnt) { asm volatile("mbarrier.init.shared::cta.b64 [%0], %1;" ::"r"(bar), "r"(cnt) : "memory"); }
DI void mbar_arrive(uint32_t bar) { asm volatile("mbarrier.arrive.shared::cta.b64 _, [%0];" ::"r"(bar) : "memory"); }
DI void mbar_arrive_remote(uint32_t bar) { asm volatile("mbarrier.arrive.release.cluster.shared::cluster.b64 _, [%0];" ::"r"(bar) : "memory"); }
DI void mbar_expect(uint32_t bar, uint32_t tx) { asm volatile("mbarrier.arrive.expect_tx.shared::cta.b64 _, [%0], %1;" ::"r"(bar), "r"(tx) : "memory"); }
DI void mbar_arrive_if(bool p, uint32_t bar) { asm volatile("{.reg .pred p; setp.ne.b32 p, %1, 0; @p mbarrier.arrive.shared::cta.b64 _, [%0];}" ::"r"(bar), "r"((int)p) : "memory"); }
DI void mbar_arrive_if(bool p, uint32_t bar, uint32_t cnt) {
  asm volatile("{.reg .pred p; setp.ne.b32 p, %1, 0; @p mbarrier.arrive.shared::cta.b64 _, [%0], %2;}" ::"r"(bar), "r"((int)p), "r"(cnt) : "memory");
}
DI void mbar_expect_if(bool p, uint32_t bar, uint32_t tx) {
  asm volatile("{.reg .pred p; setp.ne.b32 p, %2, 0; @p mbarrier.arrive.expect_tx.shared::cta.b64 _, [%0], %1;}" ::"r"(bar), "r"(tx), "r"((int)p) : "memory");
}
DI bool mbar_test(uint32_t bar, uint32_t par) {
  uint32_t ok;
  asm volatile("{.reg .pred p; mbarrier.test_wait.parity.shared::cta.b64 p, [%1], %2; selp.u32 %0, 1, 0, p;}" : "=r"(ok) : "r"(bar), "r"(par) : "memory");
  return ok;
}
DI void mbar_wait(uint32_t bar, uint32_t par) {
  asm volatile(
      "{.reg .pred p;\n"
      "LOOP:\n"
      "mbarrier.try_wait.parity.shared::cta.b64 p, [%0], %1;\n"
      "@!p bra LOOP;\n}" ::"r"(bar), "r"(par) : "memory");
}
DI void mbar_wait_wd(uint32_t bar, uint32_t par) {
  asm volatile(
      "{.reg .pred p; .reg .u32 c;\n"
      "mov.u32 c, 0;\n"
      "LOOP:\n"
      "mbarrier.try_wait.parity.shared::cta.b64 p, [%0], %1;\n"
      "@p bra DONE;\n"
      "add.u32 c, c, 1;\n"
      "setp.lt.u32 p, c, 4000000;\n"
      "@p bra LOOP;\n"
      "trap;\n"
      "DONE:\n}" ::"r"(bar), "r"(par) : "memory");
}
DI void fence_async_smem() { asm volatile("fence.proxy.async.shared::cta;" ::: "memory"); }
DI void fence_async_global() { asm volatile("fence.proxy.async.global;" ::: "memory"); }
DI void bar_sync(int id, int n) { asm volatile("bar.sync %0, %1;" ::"r"(id), "r"(n) : "memory"); }
DI void bar_arrive(int id, int n) { asm volatile("bar.arrive %0, %1;" ::"r"(id), "r"(n) : "memory"); }
DI void cluster_sync() { asm volatile("barrier.cluster.arrive.release.aligned; barrier.cluster.wait.acquire.aligned;" ::: "memory"); }
DI bool elect_one() {
  uint32_t p;
  asm volatile("{.reg .pred p; elect.sync _|p, 0xffffffff; selp.u32 %0, 1, 0, p;}" : "=r"(p));
  return p;
}
DI void bulk_g2s(uint32_t dst, const void* src, uint32_t bytes, uint32_t bar) {
  asm volatile("cp.async.bulk.shared::cluster.global.mbarrier::complete_tx::bytes [%0], [%1], %2, [%3];" ::"r"(dst), "l"(src), "r"(bytes), "r"(bar) : "memory");
}
DI void bulk_g2s_mc(uint32_t dst, const void* src, uint32_t bytes, uint32_t bar, uint16_t mask) {
  asm volatile("cp.async.bulk.shared::cluster.global.mbarrier::complete_tx::bytes.multicast::cluster [%0], [%1], %2, [%3], %4;" ::"r"(dst), "l"(src), "r"(bytes), "r"(bar), "h"(mask) : "memory");
}
DI void bulk_s2s(uint32_t dst, uint32_t src, uint32_t bytes, uint32_t bar) {
  asm volatile("cp.async.bulk.shared::cluster.shared::cta.mbarrier::complete_tx::bytes [%0], [%1], %2, [%3];" ::"r"(dst), "r"(src), "r"(bytes), "r"(bar) : "memory");
}
DI void tma_2d(uint32_t dst, const CUtensorMap* map, int c0, int c1, uint32_t bar) {
  asm volatile("cp.async.bulk.tensor.2d.shared::cluster.global.mbarrier::complete_tx::bytes [%0], [%1, {%3, %4}], [%2];" ::"r"(dst), "l"(map), "r"(bar), "r"(c0), "r"(c1) : "memory");
}
DI void tma_pf(const CUtensorMap* map, int c0, int c1) {
  asm volatile("cp.async.bulk.prefetch.tensor.2d.L2.global [%0, {%1, %2}];" ::"l"(map), "r"(c0), "r"(c1) : "memory");
}
DI void st_async4(uint32_t a, uint32_t x, uint32_t y, uint32_t z, uint32_t w, uint32_t bar) {
  asm volatile("st.async.shared::cluster.mbarrier::complete_tx::bytes.v4.b32 [%0], {%1,%2,%3,%4}, [%5];" ::"r"(a), "r"(x), "r"(y), "r"(z), "r"(w), "r"(bar) : "memory");
}
DI void st_async2(uint32_t a, uint32_t x, uint32_t y, uint32_t bar) {
  asm volatile("st.async.shared::cluster.mbarrier::complete_tx::bytes.v2.b32 [%0], {%1,%2}, [%3];" ::"r"(a), "r"(x), "r"(y), "r"(bar) : "memory");
}
DI void st_async1(uint32_t a, uint32_t x, uint32_t bar) {
  asm volatile("st.async.shared::cluster.mbarrier::complete_tx::bytes.b32 [%0], %1, [%2];" ::"r"(a), "r"(x), "r"(bar) : "memory");
}
DI void sts32(uint32_t a, uint32_t x) { asm volatile("st.shared.b32 [%0], %1;" ::"r"(a), "r"(x) : "memory"); }
DI void sts128(uint32_t a, uint4 v) { asm volatile("st.shared.v4.b32 [%0], {%1,%2,%3,%4};" ::"r"(a), "r"(v.x), "r"(v.y), "r"(v.z), "r"(v.w) : "memory"); }
DI uint32_t lds32(uint32_t a) { uint32_t v; asm volatile("ld.shared.b32 %0, [%1];" : "=r"(v) : "r"(a) : "memory"); return v; }
DI uint2 lds64(uint32_t a) { uint2 v; asm volatile("ld.shared.v2.b32 {%0,%1}, [%2];" : "=r"(v.x), "=r"(v.y) : "r"(a) : "memory"); return v; }
DI uint4 lds128(uint32_t a) { uint4 v; asm volatile("ld.shared.v4.b32 {%0,%1,%2,%3}, [%4];" : "=r"(v.x), "=r"(v.y), "=r"(v.z), "=r"(v.w) : "r"(a) : "memory"); return v; }
DI void stsm4(uint32_t a, uint32_t r0, uint32_t r1, uint32_t r2, uint32_t r3) {
  asm volatile("stmatrix.sync.aligned.m8n8.x4.shared.b16 [%0], {%1,%2,%3,%4};" ::"r"(a), "r"(r0), "r"(r1), "r"(r2), "r"(r3) : "memory");
}
DI void stsm2(uint32_t a, uint32_t r0, uint32_t r1) {
  asm volatile("stmatrix.sync.aligned.m8n8.x2.shared.b16 [%0], {%1,%2};" ::"r"(a), "r"(r0), "r"(r1) : "memory");
}
DI uint32_t movm(uint32_t a) { uint32_t d; asm volatile("movmatrix.sync.aligned.m8n8.trans.b16 %0, %1;" : "=r"(d) : "r"(a)); return d; }
DI uint32_t pack2(float lo, float hi) { uint32_t d; asm("cvt.rn.bf16x2.f32 %0, %1, %2;" : "=r"(d) : "f"(hi), "f"(lo)); return d; }
DI uint4 ld_rlx4(const void* p) {
  uint4 v;
  asm volatile("ld.relaxed.gpu.global.v4.u32 {%0,%1,%2,%3}, [%4];" : "=r"(v.x), "=r"(v.y), "=r"(v.z), "=r"(v.w) : "l"(p) : "memory");
  return v;
}
DI void st_rlx4(void* p, uint32_t x, uint32_t y, uint32_t z, uint32_t w) {
  asm volatile("st.relaxed.gpu.global.v4.u32 [%0], {%1,%2,%3,%4};" ::"l"(p), "r"(x), "r"(y), "r"(z), "r"(w) : "memory");
}
DI void st_rlx1(void* p, uint32_t x) { asm volatile("st.relaxed.gpu.global.u32 [%0], %1;" ::"l"(p), "r"(x) : "memory"); }
DI uint32_t ld_acq(const uint32_t* p) { uint32_t v; asm volatile("ld.acquire.gpu.global.u32 %0, [%1];" : "=r"(v) : "l"(p) : "memory"); return v; }
DI uint32_t ld_rlx(const uint32_t* p) { uint32_t v; asm volatile("ld.relaxed.gpu.global.u32 %0, [%1];" : "=r"(v) : "l"(p) : "memory"); return v; }
DI void red_rel(uint32_t* p, uint32_t v) { asm volatile("red.release.gpu.global.add.u32 [%0], %1;" ::"l"(p), "r"(v) : "memory"); }
DI void guard(uint32_t& g) { asm volatile("{.reg .pred p; add.u32 %0, %0, 1; setp.gt.u32 p, %0, 8000000; @p trap;}" : "+r"(g)); }
DI void poll_ge(const uint32_t* p, uint32_t target) {
  asm volatile(
      "{.reg .pred p; .reg .u32 v;\n"
      "LOOP:\n"
      "ld.acquire.gpu.global.u32 v, [%0];\n"
      "setp.lt.u32 p, v, %1;\n"
      "vote.sync.any.pred p, p, 0xffffffff;\n"
      "@p bra.uni LOOP;\n}" ::"l"(p), "r"(target) : "memory");
}
DI float ex2(float x) { float y; asm("ex2.approx.ftz.f32 %0, %1;" : "=f"(y) : "f"(x)); return y; }

DI void wg_fence() { asm volatile("wgmma.fence.sync.aligned;" ::: "memory"); }
DI void wg_commit() { asm volatile("wgmma.commit_group.sync.aligned;" ::: "memory"); }
template <int N> DI void wg_wait() { asm volatile("wgmma.wait_group.sync.aligned %0;" ::"n"(N) : "memory"); }
template <int N> DI void reg_fence(float* d) {
#pragma unroll
  for (int i = 0; i < N; i++) asm volatile("" : "+f"(d[i])::"memory");
}
__host__ __device__ constexpr uint64_t mkdesc(uint32_t addr, uint32_t lbo, uint32_t sbo, uint32_t sw) {
  return (uint64_t)((addr & 0x3FFFF) >> 4) | ((uint64_t)(lbo >> 4) << 16) | ((uint64_t)(sbo >> 4) << 32) | ((uint64_t)sw << 62);
}

#define ACC4(d, o) "+f"(d[o]), "+f"(d[o + 1]), "+f"(d[o + 2]), "+f"(d[o + 3])
#define ACC16(d, o) ACC4(d, o), ACC4(d, o + 4), ACC4(d, o + 8), ACC4(d, o + 12)
#define ACC20(d) ACC16(d, 0), ACC4(d, 16)

template <int TA, int TB> DI void wg_ss40(float* d, uint64_t da, uint64_t db, int sc) {
  asm volatile("{.reg .pred p; setp.ne.b32 p, %22, 0;\n"
               "wgmma.mma_async.sync.aligned.m64n40k16.f32.bf16.bf16 {%0,%1,%2,%3,%4,%5,%6,%7,%8,%9,%10,%11,%12,%13,%14,%15,%16,%17,%18,%19}, %20, %21, p, 1, 1, %23, %24;}"
               : ACC20(d) : "l"(da), "l"(db), "r"(sc), "n"(TA), "n"(TB));
}
DI void wg_rs40(float* d, uint32_t a0, uint32_t a1, uint32_t a2, uint32_t a3, uint64_t db, int sc) {
  asm volatile("{.reg .pred p; setp.ne.b32 p, %25, 0;\n"
               "wgmma.mma_async.sync.aligned.m64n40k16.f32.bf16.bf16 {%0,%1,%2,%3,%4,%5,%6,%7,%8,%9,%10,%11,%12,%13,%14,%15,%16,%17,%18,%19}, {%20,%21,%22,%23}, %24, p, 1, 1, 0;}"
               : ACC20(d) : "r"(a0), "r"(a1), "r"(a2), "r"(a3), "l"(db), "r"(sc));
}
DI void wg_rs32(float* d, uint32_t a0, uint32_t a1, uint32_t a2, uint32_t a3, uint64_t db, int sc) {
  asm volatile("{.reg .pred p; setp.ne.b32 p, %21, 0;\n"
               "wgmma.mma_async.sync.aligned.m64n32k16.f32.bf16.bf16 {%0,%1,%2,%3,%4,%5,%6,%7,%8,%9,%10,%11,%12,%13,%14,%15}, {%16,%17,%18,%19}, %20, p, 1, 1, 0;}"
               : ACC16(d, 0) : "r"(a0), "r"(a1), "r"(a2), "r"(a3), "l"(db), "r"(sc));
}
DI void wg_rs8(float* d, uint32_t a0, uint32_t a1, uint32_t a2, uint32_t a3, uint64_t db, int sc) {
  asm volatile("{.reg .pred p; setp.ne.b32 p, %9, 0;\n"
               "wgmma.mma_async.sync.aligned.m64n8k16.f32.bf16.bf16 {%0,%1,%2,%3}, {%4,%5,%6,%7}, %8, p, 1, 1, 0;}"
               : ACC4(d, 0) : "r"(a0), "r"(a1), "r"(a2), "r"(a3), "l"(db), "r"(sc));
}
DI void mma16816(float* c, const uint32_t* a, uint32_t b0, uint32_t b1) {
  asm volatile("mma.sync.aligned.m16n8k16.row.col.f32.bf16.bf16.f32 {%0,%1,%2,%3}, {%4,%5,%6,%7}, {%8,%9}, {%0,%1,%2,%3};"
               : ACC4(c, 0) : "r"(a[0]), "r"(a[1]), "r"(a[2]), "r"(a[3]), "r"(b0), "r"(b1));
}
DI void wg_ss8(float* d, uint64_t da, uint64_t db, int sc) {
  asm volatile("{.reg .pred p; setp.ne.b32 p, %6, 0;\n"
               "wgmma.mma_async.sync.aligned.m64n8k16.f32.bf16.bf16 {%0,%1,%2,%3}, %4, %5, p, 1, 1, 1, 1;}"
               : ACC4(d, 0) : "l"(da), "l"(db), "r"(sc));
}
DI void wg_rs16(float* d, uint32_t a0, uint32_t a1, uint32_t a2, uint32_t a3, uint64_t db, int sc) {
  asm volatile("{.reg .pred p; setp.ne.b32 p, %13, 0;\n"
               "wgmma.mma_async.sync.aligned.m64n16k16.f32.bf16.bf16 {%0,%1,%2,%3,%4,%5,%6,%7}, {%8,%9,%10,%11}, %12, p, 1, 1, 0;}"
               : ACC4(d, 0), ACC4(d, 4) : "r"(a0), "r"(a1), "r"(a2), "r"(a3), "l"(db), "r"(sc));
}
__device__ uint4 g_xn[2 * NSEG * 10 * 256];
__device__ uint4 g_oT[2 * NBLK * 96 * 1024];
constexpr int PART_RING = 96 * 256;
__device__ uint4 g_part[4 * PART_RING];
constexpr int MEM_OFF = 192;
#define P4 ~0u, ~0u, ~0u, ~0u
#define P16 P4, P4, P4, P4
#define P256 P16, P16, P16, P16, P16, P16, P16, P16, P16, P16, P16, P16, P16, P16, P16, P16
#define P2K P256, P256, P256, P256, P256, P256, P256, P256
#define P8K P2K, P2K, P2K, P2K
__device__ __align__(8192) uint32_t g_mem32[5 * 2 * 2 * 2048] = {P8K, P8K, P8K, P8K, P8K};
#define g_mem ((uint4*)g_mem32)
constexpr int C_XN = 0;
constexpr int C_O = C_XN + 2 * NBLK;
constexpr int C_HALF = C_O + 6 * 2 * NBLK;
constexpr int C_TOTAL = 512;
constexpr int CSTRIDE = 32;
__device__ uint32_t g_cnt[C_TOTAL * CSTRIDE];
constexpr uint32_t XN_TARGET = 128;

#define TRACE(c, n, i, v)
#define SLOG(i)
#define PROF(i)
#define PROFA(c)
#define PROFV(i, v)

constexpr uint32_t SMEM0 = 1024;
constexpr uint32_t SM_WK = 0, SM_WO = 81920, SM_H = 163840, SM_QT = 215040, QSTR = 1056  , SM_KT = SM_QT + 5 * QSTR + 1024,
                   SM_SR = SM_KT + 5120  , SM_PROF = SM_SR + 5760, R_SMEM = 232448,
                   SM_RED = SM_QT + 1024, SM_BAR = SM_RED + 768;
constexpr uint32_t SM_P = SM_KT, SM_OB = SM_QT + 3200;
constexpr uint32_t B_HFULL = SM_BAR, B_HEMPTY = SM_BAR + 40, B_MTRY = SM_BAR + 80, B_W = SM_BAR + 112, B_SR = B_W + 32,
                   B_PMEM = B_SR + 24, B_PTOK = B_SR + 32, B_OB = B_SR + 40, B_OPD = B_SR + 48, B_RFREE = B_SR + 56,
                   B_GATE = B_SR + 64, B_PSUM = B_SR + 72, B_END = B_SR + 80, B_PVI = B_SR + 88,
                   B_OPI = B_SR + 96, B_OTOK = B_SR + 112, SM_TOPI = B_SR + 128, B_PACE = SM_TOPI + 8,
                   SM_RS = SM_QT + 2 * QSTR + 1024;
static_assert(B_PACE + 32 <= SM_QT + 2 * QSTR, "barriers must fit the unused q row group");

struct RParams {
  uint64_t dH, dHt, dWK, dWO, dQT, dKT, dP, dOB[6];
  const char* w[4];
  const uint4* mem0;
  const uint32_t* x;
  int pf;
  int nslots, d3, pn, moff, ds, dh, dq;
  int d2[10], d1[8];
  uint32_t slot[2 * NSEG];
};
static void r_fill_desc(RParams& p) {
  p.dH = mkdesc(SMEM0 + SM_H, 128, 2048, 0);
  p.dHt = mkdesc(SMEM0 + SM_H + 2048, 128, 2048, 0);
  p.dWK = mkdesc(SMEM0 + SM_WK, 1024, 1024, 1);
  p.dWO = mkdesc(SMEM0 + SM_WO, 1024, 1024, 1);
  for (int i = 0; i < 6; i++) p.dOB[i] = mkdesc(SMEM0 + SM_OB + (i < 3 ? 0 : (i - 3) * 1024), 128, 128, 0);
  p.dQT = mkdesc(SMEM0 + SM_QT, 128, QSTR, 0);
  p.dKT = mkdesc(SMEM0 + SM_KT, 128, 1024, 0);
  p.dP = mkdesc(SMEM0 + SM_P, 128, 640, 0);
}
DI uint64_t dadd(uint64_t d, int bytes) {
  uint64_t r;
  asm volatile("add.u64 %0, %1, %2;" : "=l"(r) : "l"(d), "l"((long long)(bytes / 16)));
  return r;
}
template <int BYTES> DI void dstep(uint64_t& d) { asm volatile("add.u64 %0, %0, %1;" : "+l"(d) : "n"((long long)(BYTES / 16))); }
__host__ __device__ constexpr int hoff(int ks) { return (ks >> 3) * 10240 + (ks & 7) * 256; }

DI int opaque(int v) { asm volatile("" : "+r"(v)); return v; }
DI uint32_t pin(uint32_t v, int lane) { return __shfl_sync(~0u, v + (lane >> 5), lane); }
DI char* pin(char* p, int lane) { return (char*)__shfl_sync(~0u, (unsigned long long)p, lane); }
DI float blo(uint32_t w) { return __uint_as_float(w << 16); }
DI float bhi(uint32_t w) { return __uint_as_float(w & 0xffff0000u); }
#define R_FB 1
#define PIN_DST 1
#define RG0 232
#define RG1 216
#define RG2 40
#define RG3 24
DI void ldsm4t(uint32_t* r, uint32_t a) {
  asm volatile("ldmatrix.sync.aligned.m8n8.x4.trans.shared.b16 {%0,%1,%2,%3}, [%4];" : "=r"(r[0]), "=r"(r[1]), "=r"(r[2]), "=r"(r[3]) : "r"(a) : "memory");
}
DI void st_tagged(void* p, float a, float b, uint32_t keep, uint32_t tagbit) {
  asm volatile("{.reg .b32 t; cvt.rn.bf16x2.f32 t, %2, %1; lop3.b32 t, t, %3, %4, 0xea; st.relaxed.gpu.global.b32 [%0], t;}" ::"l"(p), "f"(a), "f"(b),
               "r"(keep), "r"(tagbit) : "memory");
}
DI uint32_t lop_bad(uint32_t a, uint32_t b, uint32_t m) { uint32_t d; asm("lop3.b32 %0, %1, %2, %3, 0x7e;" : "=r"(d) : "r"(a), "r"(b), "r"(m)); return d; }
DI uint32_t lop_or3(uint32_t a, uint32_t b, uint32_t c) { uint32_t d; asm("lop3.b32 %0, %1, %2, %3, 0xfe;" : "=r"(d) : "r"(a), "r"(b), "r"(c)); return d; }
DI uint32_t clk() { uint32_t t; asm volatile("mov.u32 %0, %%clock;" : "=r"(t)); return t; }
DI void spin(uint32_t cyc) { const uint32_t t0 = clk(); while (__any_sync(~0u, clk() - t0 < cyc)) {} }
template <int NL> DI float2 poll_sum(const uint32_t* src, uint32_t tag, uint32_t even, uint32_t& g) {
  uint32_t r[NL];
  while (true) {
#pragma unroll
    for (int i = 0; i < NL; i++) r[i] = ld_rlx(src + i * 32);
    uint32_t bad = lop_or3(lop_bad(r[0], r[1], tag), lop_bad(r[2], r[3], tag), lop_bad(r[4], r[5], tag));
    if (NL == 12) bad = lop_or3(bad, lop_bad(r[6], r[7], tag), lop_bad(r[8], r[9], tag));
    asm volatile("lop3.b32 %0, %0, %1, %2, 0xa8;" : "+r"(bad) : "r"(lop_bad(r[NL - 2], r[NL - 1], tag)), "r"(even));
    if (!__any_sync(~0u, bad)) break;
    g++;
  }
  float x[NL / 2], y[NL / 2];
#pragma unroll
  for (int i = 0; i < NL / 2; i++) { x[i] = blo(r[2 * i]) + blo(r[2 * i + 1]); y[i] = bhi(r[2 * i]) + bhi(r[2 * i + 1]); }
  float2 u = make_float2((x[0] + x[1]) + (x[2] + x[3]), (y[0] + y[1]) + (y[2] + y[3]));
  if (NL == 12) { u.x += x[4] + x[5]; u.y += y[4] + y[5]; }
  return u;
}

constexpr int PLANE = 16 * 40 * 32, MAXPL = 13;
__device__ uint2 g_acc[(size_t)2 * NBLK * 2 * MAXPL * PLANE];
DI uint2* acc_planes(int lb, int d) { return g_acc + (size_t)((lb * 2 + d) * MAXPL) * PLANE; }
DI void ln_stats(const float4* v, uint32_t red, int warp, int lane, int bar, float& mean, float& rstd) {
  float s = 0.f;
#pragma unroll
  for (int i = 0; i < 5; i++) s += (v[i].x + v[i].y) + (v[i].z + v[i].w);
  s += __shfl_xor_sync(~0u, s, 1);
  s += __shfl_xor_sync(~0u, s, 2);
  s *= 1.f / 80;
  float q = 0.f;
#pragma unroll
  for (int i = 0; i < 5; i++) q += ((v[i].x - s) * (v[i].x - s) + (v[i].y - s) * (v[i].y - s)) + ((v[i].z - s) * (v[i].z - s) + (v[i].w - s) * (v[i].w - s));
  q += __shfl_xor_sync(~0u, q, 1);
  q += __shfl_xor_sync(~0u, q, 2);
  if ((lane & 3) == 0) asm volatile("st.shared.v2.f32 [%0], {%1,%2};" ::"r"(red + lane * 16 + warp * 8), "f"(s), "f"(q) : "memory");
  bar_sync(bar, 256);
  const uint4 t = lds128(red + lane * 16);
  const float m0 = __uint_as_float(t.x), m1 = __uint_as_float(t.z);
  mean = m0 + m1;
  mean += __shfl_xor_sync(~0u, mean, 1);
  mean += __shfl_xor_sync(~0u, mean, 2);
  mean *= 0.125f;
  q = __uint_as_float(t.y) + __uint_as_float(t.w) + 80.f * ((m0 - mean) * (m0 - mean) + (m1 - mean) * (m1 - mean));
  q += __shfl_xor_sync(~0u, q, 1);
  q += __shfl_xor_sync(~0u, q, 2);
  rstd = rsqrtf(q * (1.f / DM) + 1e-5f);
}
template <int SH, int STR> DI void store_img(uint32_t* dst, const float4* v, int warp, float mean, float rstd) {
#pragma unroll
  for (int i = 0; i < 5; i++) {
    const int U = 10 * warp + 2 * i;
    uint32_t* p = dst + (U >> SH) * STR + (U & ((1 << SH) - 1)) * 32;
    p[0] = pack2((v[i].x - mean) * rstd, (v[i].y - mean) * rstd);
    p[32] = pack2((v[i].z - mean) * rstd, (v[i].w - mean) * rstd);
  }
}
DI uint32_t* xn_row_group(int layer, int rg) { return (uint32_t*)(g_xn + (size_t)((layer * NSEG + (rg >> 2)) * 2560 + (rg & 3) * 128)); }

DI void first_ln(const uint32_t* a, int rg, uint32_t red, int warp, int lane, int bar) {
  float4 v[5];
#pragma unroll
  for (int i = 0; i < 5; i++) {
    v[i] = make_float4(blo(a[2 * i]), bhi(a[2 * i]), blo(a[2 * i + 1]), bhi(a[2 * i + 1]));
    acc_planes(rg >> 4, 0)[((rg & 15) * 40 + warp * 5 + i) * 32 + lane] = make_uint2(a[2 * i], a[2 * i + 1]);
  }
  float mean, rstd;
  ln_stats(v, red, warp, lane, bar, mean, rstd);
  store_img<4, 2048>(xn_row_group(0, rg) + lane, v, warp, mean, rstd);
}
#define SOLO 1
#define QK_P0 32
#define QK_KB 0
struct QKOrder { int op[76]; };
__host__ __device__ constexpr QKOrder qk_order() {
  QKOrder o = {};
  int n = 0, k = 0, q = 0;
  for (; k < QK_P0; k++, q++) { o.op[n++] = 64 | k; o.op[n++] = q; }
  for (int i = 0; i < QK_KB; i++) o.op[n++] = 64 | k++;
  for (int i = 0; i < -QK_KB; i++) o.op[n++] = q++;
  const int nk = 40 - k, nq = 36 - q;
  for (int i = 0, dk = 0, dq = 0; i < nk + nq; i++) {
    if (dq * nk <= dk * nq + (QK_KB ? 0 : -nq) && dq < nq) { o.op[n++] = q++; dq++; } else if (dk < nk) { o.op[n++] = 64 | k++; dk++; } else { o.op[n++] = q++; dq++; }
  }
  return o;
}
__global__ void __launch_bounds__(512, 1)
r_kernel(const __grid_constant__ CUtensorMap mapWq, const __grid_constant__ CUtensorMap mapWk, const __grid_constant__ CUtensorMap mapWv,
         const __grid_constant__ CUtensorMap mapWo, const __grid_constant__ RParams prm) {
  const uint32_t sb = smem_base();
  const int wid = __shfl_sync(~0u, threadIdx.x >> 5, 0);
  const int lane0 = __shfl_sync(~0u, threadIdx.x & 31, threadIdx.x & 31);
  const int lane = lane0;
  const int warp = wid & 3, wg = wid >> 2;
  const uint32_t rank = blockIdx.x, head = blockIdx.y, cta = head * 3 + rank;
  const uint32_t peer1 = mapa(sb, rank == 2 ? 0 : rank + 1), peer2 = mapa(sb, rank == 0 ? 2 : rank - 1);
  const int nslots = prm.nslots;

  SLOG(0);
  if (threadIdx.x == 384) {
    if ((sb & 0x3FFFF) != SMEM0) __trap();
    for (int c = 0; c < 5; c++) { mbar_init(sb + B_HFULL + 8 * c, 2); mbar_init(sb + B_HEMPTY + 8 * c, c == 4 ? 8 : 4); }
    for (int c = 0; c < 11; c++) mbar_init(sb + B_MTRY + 8 * c, 1);
    mbar_init(sb + B_PTOK, rank == 0 ? 3 : 2); mbar_init(sb + B_OB, 5); mbar_init(sb + B_OPD, 4);
    mbar_init(sb + B_OPI, 1); mbar_init(sb + B_OPI + 8, 1); mbar_init(sb + B_RFREE, 1); mbar_init(sb + B_GATE, 1); mbar_init(sb + B_PMEM, 2); mbar_init(sb + B_PSUM, 2); mbar_init(sb + B_PVI, 5); mbar_init(sb + B_OTOK, 4); mbar_init(sb + B_OTOK + 8, 4); mbar_init(sb + B_END, 15);
    for (int c = 0; c < 4; c++) mbar_init(sb + B_PACE + 8 * c, 1);
    asm volatile("fence.mbarrier_init.release.cluster;" ::: "memory");
    fence_async_smem();
  }
  asm volatile("griddepcontrol.launch_dependents;");
  asm volatile("barrier.cluster.arrive.release.aligned;" ::: "memory");

  if (wg < 2) {
  {
    uint32_t xa[10];
    const uint32_t* src = prm.x + (size_t)(cta * 8 + (lane >> 2)) * (DM / 2) + wid * 40 + (lane & 3);
#pragma unroll
    for (int i = 0; i < 10; i++) xa[i] = __ldg(src + i * 4);
    asm volatile("barrier.cluster.wait.acquire.aligned;" ::: "memory");
    first_ln(xa, cta, sb + SM_SR, wid, lane, 8);
    bar_arrive(10, 288);
  }
  if (wg == 0) {
    asm volatile("setmaxnreg.inc.sync.aligned.u32 %0;" ::"n"(RG0));
    uint32_t wq[160];
    SLOG(1);
    mbar_wait(sb + B_W, 0);
    SLOG(2);
    {
      const uint32_t ld_off = ((lane >> 4) * 8 + (lane & 7)) * 128 + (((2 * warp + ((lane >> 3) & 1)) ^ (lane & 7)) << 4);
#pragma unroll
      for (int ks = 0; ks < 40; ks++) ldsm4t(wq + 4 * ks, sb + SM_WO + ks * 2048 + ld_off);
    }
    fence_async_smem();
    bar_arrive(5, 160);
    mbar_wait(sb + B_W + 16, 0);
    SLOG(3);
    const uint32_t st_addr = pin(sb + SM_QT + (lane >> 4) * 1024 + (2 * warp + ((lane >> 3) & 1)) * 128 + (lane & 7) * 16, lane);
    const uint32_t sq_addr = pin(sb + SM_QT + (2 + (lane & 3)) * QSTR + warp * 256 + (lane >> 2) * 16, lane);
    const uint32_t to_lo = warp == 0 ? peer1 : mapa(sb, warp == 2 ? 2 : 0), to_hi = warp == 0 ? peer2 : mapa(sb, warp == 1 ? 1 : 0);
    const uint32_t sr_off = SM_SR + warp * 1920 + rank * 640, sr_bar = B_SR + warp * 8;
    const uint32_t sa0 = pin(to_lo + sr_off + lane * 16, lane), sb0 = pin(to_lo + sr_bar, lane), sa1 = pin(to_lo + sr_off + 512 + lane * 4, lane), sb1 = pin(sb0, lane);
    const uint32_t sa2 = pin(to_hi + sr_off + lane * 16, lane), sb2 = pin(to_hi + sr_bar, lane), sa3 = pin(to_hi + sr_off + 512 + lane * 4, lane), sb3 = pin(sb2, lane);
    uint32_t nsolo = 0;
#pragma unroll 1
    for (int n = 0; n < nslots; n++) {
      const uint32_t par = n & 1;
      PROFA(warp == PW);
      const bool alt = prm.slot[n] & 128;
      auto next = [&](uint64_t& d, int ks) { if ((ks & 7) == 7) dstep<10240 - 7 * 256>(d); else dstep<256>(d); };
      auto store_k = [&](const float* ka) {
        stsm2(st_addr + (SM_KT - SM_QT), pack2(ka[0], ka[1]), pack2(ka[2], ka[3]));
        stsm4(st_addr + (SM_KT - SM_QT) + 1024, pack2(ka[4], ka[5]), pack2(ka[6], ka[7]), pack2(ka[8], ka[9]), pack2(ka[10], ka[11]));
        stsm4(st_addr + (SM_KT - SM_QT) + 3072, pack2(ka[12], ka[13]), pack2(ka[14], ka[15]), pack2(ka[16], ka[17]), pack2(ka[18], ka[19]));
      };
      auto store_qt = [&](const float* q) {
        sts128(sq_addr, make_uint4(pack2(q[0], q[1]), pack2(q[4], q[5]), pack2(q[8], q[9]), pack2(q[12], q[13])));
        sts128(sq_addr + 128, make_uint4(pack2(q[2], q[3]), pack2(q[6], q[7]), pack2(q[10], q[11]), pack2(q[14], q[15])));
      };
      if (SOLO && n > 0 && ((prm.slot[n] >> 8) & 255) == n) {
        {
          float qt[16];
          uint64_t rh = prm.dHt;
          mbar_wait(sb + B_OPD, par ^ 1);
          spin(prm.dq);
          mbar_wait(sb + B_PVI, nsolo++ & 1);
          wg_fence();
#pragma unroll
          for (int ks = 0; ks < 40; ks++) { wg_rs32(qt, wq[4 * ks], wq[4 * ks + 1], wq[4 * ks + 2], wq[4 * ks + 3], rh, ks != 0); if (ks < 39) next(rh, ks); }
          wg_commit();
          wg_wait<0>();
          reg_fence<16>(qt);
          store_qt(qt);
        }
        float qm[4], ka[20];
        uint64_t rk = prm.dWK, rh = prm.dH, rq;
        bool ok = false;
#pragma unroll
        for (int g = 0; g < 18; g++) {
          if ((g & 3) == 0 && !ok) mbar_wait(sb + B_HFULL + 2 * g, par);
          if (g == 0) PROF(0);
          if ((g & 3) == 3) ok = mbar_test(sb + B_HFULL + 2 * (g + 1), par);
          if ((g & 3) == 0) wg_fence();
#pragma unroll
          for (int ks = 2 * g; ks < 2 * g + 2; ks++) {
            wg_ss40<1, 0>(ka, rk, rh, ks != 0);
            wg_rs8(qm, wq[4 * ks], wq[4 * ks + 1], wq[4 * ks + 2], wq[4 * ks + 3], rh, ks != 0);
            dstep<2048>(rk); next(rh, ks);
          }
        }
        wg_commit();
        rq = rh;
#pragma unroll
        for (int ks = 36; ks < 40; ks++) { wg_ss40<1, 0>(ka, rk, rh, 1); if (ks < 39) { dstep<2048>(rk); dstep<256>(rh); } }
        wg_commit();
#pragma unroll
        for (int ks = 36; ks < 40; ks++) { wg_rs8(qm, wq[4 * ks], wq[4 * ks + 1], wq[4 * ks + 2], wq[4 * ks + 3], rq, 1); if (ks < 39) dstep<256>(rq); }
        wg_commit();
        wg_wait<2>();
        if (alt) bar_arrive(2, 256);
        wg_wait<1>();
        if (!alt) bar_arrive(2, 256);
        reg_fence<20>(ka);
        store_k(ka);
        wg_wait<0>();
        reg_fence<4>(qm);
        PROF(9);
        stsm2(st_addr, pack2(qm[0], qm[1]), pack2(qm[2], qm[3]));
      } else {
      float qa[20], ka[20];
      uint64_t rk = prm.dWK, rh = prm.dH, rq;
      auto K = [&](int ks) { wg_ss40<1, 0>(ka, rk, rh, ks != 0); };
      auto Q = [&](int ks, uint64_t db) { wg_rs40(qa, wq[4 * ks], wq[4 * ks + 1], wq[4 * ks + 2], wq[4 * ks + 3], db, ks != 0); };
      constexpr QKOrder ord = qk_order();
      auto first = [&](int g, int c) { for (int i = 0; i < 76; i++) if ((ord.op[i] & 63) >> 3 == c) return i >> 2 == g; return false; };
      bool ok = true;
      mbar_wait(sb + B_HFULL, par);
#pragma unroll
      for (int g = 0; g < 19; g++) {
        if (!ok) {
#pragma unroll
          for (int c = 1; c < 5; c++) if (first(g, c)) mbar_wait(sb + B_HFULL + 8 * c, par);
          mbar_wait(sb + B_GATE, 1);
        }
        if (g == 0) PROF(0);
        if (g < 18) ok = mbar_test(sb + B_GATE, 1);
#pragma unroll
        for (int c = 1; c < 5; c++) if (first(g + 1, c)) ok &= mbar_test(sb + B_HFULL + 8 * c, par);
        wg_fence();
#pragma unroll
        for (int i = 4 * g; i < 4 * g + 4; i++) {
          const int ks = ord.op[i] & 63;
          if (i < 2 * QK_P0) {
            if (ord.op[i] & 64) K(ks);
            else { Q(ks, rh); dstep<2048>(rk); next(rh, ks); if (i == 2 * QK_P0 - 1) rq = rh; }
          } else if (ord.op[i] & 64) { K(ks); if (ks < 39) { dstep<2048>(rk); next(rh, ks); } }
          else { Q(ks, rq); next(rq, ks); }
        }
        if (g == 17) wg_commit();
      }
      wg_commit();
#pragma unroll
      for (int ks = 36; ks < 40; ks++) { Q(ks, rq); if (ks < 39) dstep<256>(rq); }
      wg_commit();
      wg_wait<2>();
      if (alt) bar_arrive(2, 256);
      mbar_wait(sb + B_OPD, par ^ 1);
      wg_wait<1>();
      if (!alt) bar_arrive(2, 256);
      reg_fence<20>(ka);
      store_k(ka);
      wg_wait<0>();
      reg_fence<20>(qa);
      PROF(9);
      stsm2(st_addr, pack2(qa[0], qa[1]), pack2(qa[2], qa[3]));
      store_qt(qa + 4);
      }
      mbar_arrive_if(lane == 0, sb + B_HEMPTY + 32);
      fence_async_smem();
      bar_sync(1, 128);
      PROF(1);
      float qa[20];
      wg_fence();
#pragma unroll
      for (int k = 0; k < 4; k++) wg_ss40<1, 1>(qa, dadd(prm.dQT, k * 256), dadd(prm.dKT, k * 256), k != 0);
      wg_commit();
      bar_arrive(7, 256);
      wg_wait<0>();
      reg_fence<20>(qa);
      PROF(3);
      if (warp < 3) {
        uint32_t p[5];
#pragma unroll
        for (int j = 0; j < 5; j++) p[j] = pack2(qa[4 * j], qa[4 * j + 1]);
        if (warp == 0) {
          st_async4(sa0, p[0], p[1], p[2], p[3], sb0);
          st_async4(sa2, p[0], p[1], p[2], p[3], sb2);
          st_async1(sa1, p[4], sb1);
          st_async1(sa3, p[4], sb3);
          sts128(sb + sr_off + lane * 16, make_uint4(p[0], p[1], p[2], p[3]));
          sts32(sb + sr_off + 512 + lane * 4, p[4]);
          __syncwarp();
          mbar_expect_if(lane == 0, sb + B_SR, 1280);
        } else {
          uint32_t h[5];
#pragma unroll
          for (int j = 0; j < 5; j++) h[j] = pack2(qa[4 * j + 2], qa[4 * j + 3]);
          spin(prm.d3);
          st_async4(sa0, p[0], p[1], p[2], p[3], sb0);
          st_async4(sa2, h[0], h[1], h[2], h[3], sb2);
          st_async1(sa1, p[4], sb1);
          st_async1(sa3, h[4], sb3);
        }
      }
    }
  } else {
    asm volatile("setmaxnreg.inc.sync.aligned.u32 %0;" ::"n"(RG1));
    uint32_t wv[160];
    mbar_wait(sb + B_W + 8, 0);
    SLOG(4);
    {
      const uint32_t ld_off = ((lane >> 4) * 8 + (lane & 7)) * 128 + (((2 * warp + ((lane >> 3) & 1)) ^ (lane & 7)) << 4);
#pragma unroll
      for (int ks = 0; ks < 40; ks++) ldsm4t(wv + 4 * ks, sb + SM_WO + ks * 2048 + ld_off);
    }
    fence_async_smem();
    bar_arrive(6, 160);
    const uint64_t dH = prm.dH;
    uint32_t op[8];
    const uint32_t ob_off = SM_OB + (4 * rank + warp) * 256 + lane * 4;
    const uint32_t oa0 = pin(peer1 + ob_off, lane), ob0 = pin(peer1 + B_OB, lane), oa1 = pin(peer2 + ob_off, lane), ob1 = pin(peer2 + B_OB, lane);
    const uint32_t oa2 = pin(oa0 + 128, lane), ob2 = pin(ob0, lane), oa3 = pin(oa1 + 128, lane), ob3 = pin(ob1, lane);
    const uint32_t o_loc = pin(sb + ob_off, lane), rs_addr = pin(sb + SM_RS + (lane & 3) * 8, lane);
    const uint32_t tok_off = pin((cta * 1024 + 64 * warp + (lane ^ (lane >> 3))) * 16, lane), keep = pin((lane & 1) ? ~0u : ~1u, lane);
    const uint32_t pb_off = pin((8 * rank + 2 * warp) * 4096 + head * 128 + lane * 4, lane);
    const uint32_t ph_off = pin(72 * 4096 + 2 * warp * 12288 + cta * 64 + (lane & 2) * 3072 + (lane >> 2) * 8 + (lane & 1) * 4, lane);
    auto store_tok = [&](int m, int lane) {
      const uint32_t ls = prm.slot[m] & 127, sig = prm.slot[m] >> 16;
      uint4* dst = (uint4*)((char*)(g_oT + (size_t)((ls >> 2) * (96 * 1024) + (ls & 3) * 256)) + tok_off);
      dst[0] = make_uint4(op[0], op[1], op[2], op[3]);
      dst[32] = make_uint4(op[4], op[5], op[6], op[7]);
      __syncwarp();
      mbar_arrive_if(sig && lane == 0, sb + B_OTOK + (ls >> 6) * 8);
    };
#pragma unroll 1
    for (int n = 0; n < nslots; n++) {
      const uint32_t par = n & 1;
      const int lane = opaque(lane0);
      PROFA(warp == PW);
      float va[20];
      const bool alt = prm.slot[n] & 128;
      mbar_expect_if(warp == 0 && lane == 0, sb + B_PTOK, rank == 0 ? 1280 : 1920);
      bar_sync(2, 256);
#pragma unroll
      for (int g = 0; g < 10; g++) {
        wg_fence();
#pragma unroll
        for (int ks = 4 * g; ks < 4 * g + 4; ks++) { wg_rs40(va, wv[4 * ks], wv[4 * ks + 1], wv[4 * ks + 2], wv[4 * ks + 3], dadd(dH, hoff(ks)), ks != 0); }
        wg_commit();
        if (g >= 2 && !(g & 1)) {
          wg_wait<1>();
          if (lane == 0) mbar_arrive(sb + B_HEMPTY + 8 * (g / 2 - 1));
        }
        if (g == 1 ? !alt : g == 2 && alt) bar_sync(7, 256);
      }
      wg_wait<0>();
      reg_fence<20>(va);
      if (lane == 0) mbar_arrive(sb + B_HEMPTY + 32);
      PROF(10);
      uint32_t vf[10];
#pragma unroll
      for (int j = 0; j < 10; j++) {
        const int i = (j + 4) % 10;
        asm volatile("cvt.rn.bf16x2.f32 %0, %1, %2;" : "=r"(vf[i]) : "f"(va[2 * i + 1]), "f"(va[2 * i]));
        if (j == 5) mbar_wait(sb + B_W + 8, 0);
      }
      uint32_t z0, z1;
      asm volatile("shr.u32 %0, %2, 5; shr.u32 %1, %2, 6;" : "=r"(z0), "=r"(z1) : "r"(lane));
      const uint32_t info = prm.slot[n];
      const uint32_t tagbit = ~(info >> 1) & ~keep;
      char* const ring = (char*)(g_part + (size_t)((((info >> 5) & 2) + (info & 1)) * PART_RING));
      char* const pb = pin(ring + pb_off, lane);
      char* const ph = ring + ph_off;
      mbar_wait(sb + B_PMEM, par);
      float om[4];
      wg_fence();
      wg_rs8(om, vf[0], vf[1], vf[2], vf[3], prm.dP, 0);
      wg_rs8(om, vf[4], vf[5], vf[6], vf[7], dadd(prm.dP, 256), 1);
      wg_rs8(om, vf[8], vf[9], z0, z1, dadd(prm.dP, 512 - (128 << 16)), 1);
      wg_commit();
      {
        wg_wait<0>();
        reg_fence<4>(om);
        const uint32_t b0 = pack2(om[0], om[1]), b1 = pack2(om[2], om[3]);
        st_async1(oa0, b0, ob0);
        st_async1(oa1, b0, ob1);
        st_async1(oa2, b1, ob2);
        st_async1(oa3, b1, ob3);
        sts32(o_loc, b0);
        sts32(o_loc + 128, b1);
        fence_async_smem();
        __syncwarp();
        mbar_arrive_if(lane == 0, sb + B_OB);
      }
      PROF(11);
      {
        float c[8];
        mbar_wait(sb + B_PSUM, par);
        const uint2 rs = lds64(rs_addr);
        const float r0 = __uint_as_float(rs.x), r1 = __uint_as_float(rs.y);
        if (n == 0) { SLOG(5); mbar_wait(sb + B_W + 24, 0); SLOG(6); }
        mbar_wait(sb + B_OB, par);
        asm volatile("fence.proxy.async::generic.acquire.sync_restrict::shared::cluster.cluster;" ::: "memory");
        PROF(16);
        if ((info & 63) == NSEG - 1) {
          mbar_wait(sb + B_OPI + par * 8, (n >> 1) & 1);
          mbar_arrive_if(warp == 3 && lane == 0, sb + B_GATE);
#pragma unroll
          for (int p = 0; p < 6; p++) st_rlx1(pb + (p >> 1) * 98304 + (p & 1) * 4096, tagbit);
          st_rlx1(ph, tagbit);
          st_rlx1(ph + 12288, tagbit);
        } else {
#pragma unroll
        for (int p = 0; p < 4; p++) {
          float* const cur = c + 4 * (p & 1);
          float* const prv = c + 4 * (~p & 1);
          if (p == 2) mbar_wait(sb + B_OPI + par * 8, (n >> 1) & 1);
          wg_fence();
#pragma unroll
          for (int ks = 0; ks < (p < 3 ? 12 : 4); ks++) {
            wg_ss8(cur, dadd(prm.dWO, p * 24576 + ks * 2048), dadd(prm.dOB[p < 3 ? p : 3 + rank], ks * 256), ks != 0);
            if (p == 3 && ks == 3) mbar_arrive_if(warp == 3 && lane == 0, sb + B_GATE);
            if (p > 0 && ks == 3) {
              wg_commit();
              wg_wait<1>();
              reg_fence<4>(prv);
              st_tagged(pb + (p - 1) * 98304, prv[0] * r0, prv[1] * r1, keep, tagbit);
              st_tagged(pb + (p - 1) * 98304 + 4096, prv[2] * r0, prv[3] * r1, keep, tagbit);
            }
          }
          if (p < 3) wg_commit();
        }
        wg_wait<0>();
        reg_fence<4>(c + 4);
        st_tagged(ph, c[4] * r0, c[5] * r1, keep, tagbit);
        st_tagged(ph + 12288, c[6] * r0, c[7] * r1, keep, tagbit);
        }
        PROF(17);
      }
      mbar_wait(sb + B_PTOK, par);
      PROF(12);
      {
        float ot[16];
        wg_fence();
        wg_rs32(ot, vf[0], vf[1], vf[2], vf[3], dadd(prm.dP, 640), 0);
        wg_rs32(ot, vf[4], vf[5], vf[6], vf[7], dadd(prm.dP, 640 + 256), 1);
        wg_rs32(ot, vf[8], vf[9], z0, z1, dadd(prm.dP, 640 + 512 - (128 << 16)), 1);
        wg_commit();
        wg_wait<0>();
        reg_fence<16>(ot);
#pragma unroll
        for (int i = 0; i < 8; i++) op[(i & 1) * 4 + (i >> 1)] = pack2(ot[2 * i], ot[2 * i + 1]);
      }
      if (lane == 0) mbar_arrive(sb + B_OPD);
      PROF(13);
      if (info & 128) spin(prm.ds);
      store_tok(n, lane);
    }
  }
  } else if (wg == 2) {
    asm volatile("setmaxnreg.dec.sync.aligned.u32 %0;" ::"n"(RG2));
    asm volatile("barrier.cluster.wait.acquire.aligned;" ::: "memory");
    if (warp == 1) {
      const uint32_t depth = prm.pf & 7;
#pragma unroll 1
      for (uint32_t i = 0; i < 20 + depth; i++) {
        if (i >= depth) {
          const uint32_t j = i - depth;
          mbar_wait_wd(sb + B_PACE + 8 * (j & 3), (j >> 2) & 1);
          if (j % 5 == 4) mbar_arrive_if(lane == 0 && (j != 14 || depth == 1), sb + B_W + (j == 4 ? 0 : j == 9 ? 16 : j == 14 ? 8 : 24));
        }
        if (i >= 20) continue;
        const uint32_t m = i / 5, k = i % 5, bar = sb + B_PACE + 8 * (i & 3);
        if (i == 10) bar_sync(5, 160);
        if (i == 15) {
          if ((prm.pf & 8) && elect_one())
            for (int q = 0; q < 4; q++) tma_pf(&mapWo, (q / 3 * 3 + rank) * 64, head * DH + q % 3 * 64);
#pragma unroll 1
          for (uint32_t j = 16 - depth; j < 15; j++) mbar_wait_wd(sb + B_PACE + 8 * (j & 3), (j >> 2) & 1);
          mbar_arrive_if(lane == 0 && depth > 1, sb + B_W + 8);
          bar_sync(6, 160);
        }
        if (elect_one()) {
          mbar_expect(bar, 16384);
          if (m < 3) tma_2d(sb + (m == 1 ? SM_WK : SM_WO) + k * 16384, m == 0 ? &mapWq : m == 1 ? &mapWk : &mapWv, cta * 64, k * 128, bar);
          else
            for (uint32_t q = 2 * k; q < 2 * k + 2; q++)
              tma_2d(sb + SM_WO + q * 8192, &mapWo, q < 9 ? (q / 3 * 3 + rank) * 64 : 576, head * DH + (q < 9 ? q % 3 : rank) * 64, bar);
        }
      }
    }
    if (warp == 2 && cta < 80 && lane < 16)
      g_mem[(cta >> 4) * 2048 + (lane >> 3) * 1024 + prm.moff + (cta & 15) * 8 + (lane & 7)] = prm.mem0[(lane & 7) * 80 + cta];
    if (warp == 3) {
      bar_sync(10, 288);
      if (lane == 0) red_rel(&g_cnt[(C_XN + (cta >> 4)) * CSTRIDE], 8);
    }
    const uint32_t grp = warp == 1 ? 1 + rank : 4 - (rank >> 1);
    constexpr float SC = 0.07216878364870322f * 1.4426950408889634f;
    const bool split = cta >= 72;
    const uint32_t wd = split ? 72 * 16 + cta * 16 : cta * 32;
    const uint32_t src_off = pin(split ? 72 * 4096 + (cta - 72) * 6144 + warp * 1536 + (lane & 2) * 32 + (lane >> 2) * 8 + (lane & 1) * 4 : cta * 4096 + warp * 1024 + lane * 4, lane);
    const uint32_t dst_off = pin(((wd >> 9) * 8192 + prm.moff * 4 + (wd & 511) + lane) * 4, lane);
    const uint32_t red = pin(sb + SM_RED + (warp < 2 ? 0 : (warp - 1) * 256) + lane * 8, lane);
    const uint32_t fl = (warp & 2) * 8 + (lane >> 3) * 4 + (lane & 3), hf = lane & 4;
    const uint32_t s0 = pin(sb + SM_SR + fl * 16 + hf * 2, lane), s1 = pin(sb + fl * 4, lane), pd = pin(s1 + hf * 64, lane);
    const uint32_t even = pin(~lane & 1, lane);
    uint32_t nred = 0;
    const uint32_t arm = pin(warp == 0 && (lane == 5 || ((lane == 1 || lane == 2) && lane + rank != 3)) ? sb + B_SR + lane * 8 : 0, lane);
#pragma unroll 1
    for (int n = 0; n < nslots; n++) {
      const uint32_t par = n & 1;
      const int lane = opaque(lane0);
      PROFA(warp == PW2);
      const uint32_t info = prm.slot[n], s = info & 63, l = (info >> 6) & 1;
      {
        mbar_expect_if(arm, arm, lane == 5 ? 2048 : 1920);
        if (warp == 0 || warp == 3) {
          mbar_wait(sb + B_SR, par);
          PROF(4);
          const uint2 a0 = lds64(s0), a1 = lds64(s0 + 640), a2 = lds64(s0 + 1280);
          const uint32_t b0 = lds32(s1 + SM_SR + 512), b1 = lds32(s1 + SM_SR + 1152), b2 = lds32(s1 + SM_SR + 1792);
          float v[6];
          v[0] = blo(a0.x) + blo(a1.x) + blo(a2.x); v[1] = bhi(a0.x) + bhi(a1.x) + bhi(a2.x);
          v[2] = blo(a0.y) + blo(a1.y) + blo(a2.y); v[3] = bhi(a0.y) + bhi(a1.y) + bhi(a2.y);
          v[4] = blo(b0) + blo(b1) + blo(b2); v[5] = bhi(b0) + bhi(b1) + bhi(b2);
          float m = fmaxf(fmaxf(v[0], v[1]), fmaxf(v[2], v[3]));
          m = fmaxf(fmaxf(m, __shfl_xor_sync(~0u, m, 4)), fmaxf(v[4], v[5]));
          {
            const float m1 = __shfl_xor_sync(~0u, m, 1), m2 = __shfl_xor_sync(~0u, m, 2), m3 = __shfl_xor_sync(~0u, m, 3);
            m = fmaxf(fmaxf(m, m1), fmaxf(m2, m3));
          }
          const float ms = -m * SC;
#pragma unroll
          for (int i = 0; i < 6; i++) v[i] = ex2(fmaf(v[i], SC, ms));
          float sum = (v[0] + v[1]) + (v[2] + v[3]);
          const float so = __shfl_xor_sync(~0u, sum, 4);
          sts32(pd + SM_P, pack2(v[0], v[1]));
          sts32(pd + SM_P + 128, pack2(v[2], v[3]));
          sts32(s1 + SM_P + 512, pack2(v[4], v[5]));
          fence_async_smem();
          __syncwarp();
          mbar_arrive_if(lane == 0, sb + B_PMEM);
          PROF(5);
          sum += so + (v[4] + v[5]);
          {
            const float t1 = __shfl_xor_sync(~0u, sum, 1), t2 = __shfl_xor_sync(~0u, sum, 2), t3 = __shfl_xor_sync(~0u, sum, 3);
            sum = (sum + t1) + (t2 + t3);
          }
          float r;
          asm("rcp.approx.ftz.f32 %0, %1;" : "=f"(r) : "f"(sum));
          sts32(sb + SM_RS + (warp & 2) * 8 + (lane >> 3) * 4, __float_as_uint(r));
          __syncwarp();
          mbar_arrive_if(lane == 0, sb + B_PSUM);
        } else {
          if (warp + rank != 3) {
            const uint32_t src = sb + SM_SR + warp * 1920;
            mbar_wait(sb + B_SR + warp * 8, par);
            const uint4 a0 = lds128(src + lane * 16), a1 = lds128(src + 640 + lane * 16), a2 = lds128(src + 1280 + lane * 16);
            const uint32_t b0 = lds32(src + 512 + lane * 4), b1 = lds32(src + 1152 + lane * 4), b2 = lds32(src + 1792 + lane * 4);
            float v[10];
            v[0] = blo(a0.x) + blo(a1.x) + blo(a2.x); v[1] = bhi(a0.x) + bhi(a1.x) + bhi(a2.x);
            v[2] = blo(a0.y) + blo(a1.y) + blo(a2.y); v[3] = bhi(a0.y) + bhi(a1.y) + bhi(a2.y);
            v[4] = blo(a0.z) + blo(a1.z) + blo(a2.z); v[5] = bhi(a0.z) + bhi(a1.z) + bhi(a2.z);
            v[6] = blo(a0.w) + blo(a1.w) + blo(a2.w); v[7] = bhi(a0.w) + bhi(a1.w) + bhi(a2.w);
            v[8] = blo(b0) + blo(b1) + blo(b2); v[9] = bhi(b0) + bhi(b1) + bhi(b2);
            {
              const int lim = 6 + 2 * grp + (lane & 24) + ((lane >> 2) & 1) - 2 * (lane & 3);
#pragma unroll
              for (int i = 2; i < 10; i++) if ((i >> 1) * 8 + (i & 1) > lim) v[i] = -INFINITY;
            }
            float m = fmaxf(fmaxf(fmaxf(v[0], v[1]), fmaxf(v[2], v[3])), fmaxf(fmaxf(v[4], v[5]), fmaxf(v[6], v[7])));
            m = fmaxf(m, fmaxf(v[8], v[9]));
            {
              const float m1 = __shfl_xor_sync(~0u, m, 1), m2 = __shfl_xor_sync(~0u, m, 2), m3 = __shfl_xor_sync(~0u, m, 3);
              m = fmaxf(fmaxf(m, m1), fmaxf(m2, m3));
            }
            const float ms = -m * SC;
#pragma unroll
            for (int i = 0; i < 10; i++) v[i] = ex2(fmaf(v[i], SC, ms));
            float sum = ((v[0] + v[1]) + (v[2] + v[3])) + ((v[4] + v[5]) + (v[6] + v[7])) + (v[8] + v[9]);
            {
              const float s1 = __shfl_xor_sync(~0u, sum, 1), s2 = __shfl_xor_sync(~0u, sum, 2), s3 = __shfl_xor_sync(~0u, sum, 3);
              sum = (sum + s1) + (s2 + s3);
            }
            float r;
            asm("rcp.approx.ftz.f32 %0, %1;" : "=f"(r) : "f"(sum));
            {
              const uint32_t row = SM_P + grp * 640;
#pragma unroll
              for (int j = 0; j < 5; j++) sts32(sb + row + j * 128 + lane * 4, pack2(v[2 * j] * r, v[2 * j + 1] * r));
              fence_async_smem();
              __syncwarp();
              mbar_arrive_if(lane == 0, sb + B_PTOK);
              if (elect_one()) {
                bulk_s2s(peer1 + row, sb + row, 640, peer1 + B_PTOK);
                bulk_s2s(peer2 + row, sb + row, 640, peer2 + B_PTOK);
              }
            }
          }
        }
      }
      const uint32_t* const src = (const uint32_t*)((char*)(g_part + (size_t)((l * 2 + (s & 1)) * PART_RING)) + src_off);
      uint32_t* const dst = (uint32_t*)pin((char*)(g_mem + l * 1024 + (~s & 1) * 512) + dst_off, lane);
      {
        const uint32_t d1 = prm.d1[cta / 24 + ((info >> 5) & 4)];
        if (warp == 3) {
          mbar_wait(sb + B_OB, par);
          mbar_arrive_if(lane == 0, sb + B_GATE);
          sts32(sb + SM_TOPI + par * 4, clk());
          __syncwarp();
          mbar_arrive_if(lane == 0, sb + B_OPI + par * 8);
          TRACE(true, n, 0, gtl());
        }
        const bool reduce = cta < 88 && s != NSEG - 1;
        if (reduce || warp == 0) mbar_wait(sb + B_OPI + par * 8, (n >> 1) & 1);
        if (!reduce) continue;
        mbar_wait(sb + B_RFREE, (nred++ & 1) ^ 1);
        mbar_wait(sb + B_GATE, 1);
        if (d1) spin(d1);
      }
      {
        uint32_t g = 0;
        float2 u;
        PROF(14);
        if (!split) {
          u = poll_sum<8>(src, ~(s >> 1), even, g);
        } else {
          u = poll_sum<12>(src, ~(s >> 1), even, g);
          u.x += __shfl_xor_sync(~0u, u.x, 2);
          u.y += __shfl_xor_sync(~0u, u.y, 2);
        }
        PROF(18);
        if (warp != 1) {
          asm volatile("st.shared.v2.f32 [%0], {%1,%2};" ::"r"(red), "f"(u.x), "f"(u.y) : "memory");
          bar_arrive(3, 128);
        } else {
          bar_sync(3, 128);
          const uint2 o0 = lds64(red), o1 = lds64(red + 256), o2 = lds64(red + 512);
          const uint32_t w = movm(pack2((u.x + __uint_as_float(o0.x)) + (__uint_as_float(o1.x) + __uint_as_float(o2.x)),
                                        (u.y + __uint_as_float(o0.y)) + (__uint_as_float(o1.y) + __uint_as_float(o2.y))));
          if (!split || lane < 16) {
            st_rlx1(dst, w);
            st_rlx1(dst + ((s & 1) ? 2048 : -2048), ~0u);
          }
          mbar_arrive_if(lane == 0, sb + B_RFREE);
        }
        PROF(19);
        PROFV(2, g);
        TRACE(warp == 1, n, 1, gtl());
        TRACE(g, n, 2, g);
      }
    }
  } else {
    asm volatile("setmaxnreg.dec.sync.aligned.u32 %0;" ::"n"(RG3));
    asm volatile("barrier.cluster.wait.acquire.aligned;" ::: "memory");
    const uint32_t chk = lane * 32 + ((lane >> 2) << 2);
    const uint32_t bar = sb + B_MTRY + 8 * warp;
    uint32_t mph = 0, waited = 0, pub = 0, pph = 0, nsolo = 0;
    auto publish = [&](uint32_t upto) {
#pragma unroll 1
      for (; pub < upto; pub++) {
        const uint32_t e = prm.slot[pub], l = (e >> 6) & 1;
        if (warp == 3 && (e >> 16)) {
          mbar_wait_wd(sb + B_OTOK + l * 8, (pph >> l) & 1);
          pph ^= 1 << l;
          if (elect_one()) red_rel(&g_cnt[(e >> 16) * CSTRIDE], 1);
        }
      }
    };
#pragma unroll 1
    for (int m = 0; m < nslots; m++) {
      const uint32_t info = prm.slot[m], prod = (info >> 8) & 255, ls = info & 127;
      uint32_t g = 0;
#pragma unroll 1
      for (; waited < prod && waited + 1 < m; waited++) mbar_wait_wd(sb + B_OPI + (waited & 1) * 8, (waited >> 1) & 1);
      uint32_t t0 = lds32(sb + SM_TOPI + (~waited & 1) * 4);
      publish(waited);
      if ((ls & 3) == 0) {
        while (__any_sync(~0u, ld_acq(&g_cnt[(C_XN + (ls >> 2)) * CSTRIDE]) < XN_TARGET)) guard(g);
        fence_async_global();
      }
#pragma unroll 1
      for (uint32_t c = warp; c < 5; c += 4) {
        const uint32_t dst = sb + SM_H + c * 10240, full = sb + B_HFULL + 8 * c;
        const uint4* src = g_mem + (c * 2048 + (ls >> 6) * 1024 + (ls & 1) * 512 + prm.moff);
        const uint32_t d = prod ? prm.d2[(m - prod) * 5 + c] : 0;
        const uint4* tok = g_xn + (size_t)(ls * 2560 + c * 512);
        const uint32_t pp = (m & 1) ^ 1;
        const bool single = waited < prod;
        mbar_wait_wd(full, pp);
        const bool solo = SOLO && m > 0 && prod == m;
        const uint32_t tokb = solo ? sb + B_PVI : full;
        if (solo && c < 4) mbar_wait_wd(tokb, (nsolo++ & 1) ^ 1);
        mbar_expect_if(lane < 2 && !(solo && c == 4 && lane == 0), lane ? bar : tokb, lane ? 2048 : 8192);
        if (!single) while (__any_sync(~0u, clk() - t0 < d)) {}
        if (c >= 2) mbar_wait_wd(sb + B_HEMPTY + 8 * c, pp);
        mbar_wait_wd(sb + (c < 2 ? B_HEMPTY + 8 * c : c == 2 && !single ? B_PMEM : B_OB), pp);
        if ((c != 2 || single) && !(solo && c == 4)) { if (elect_one()) bulk_g2s(dst + 2048, tok, 8192, tokb); }
        if (single) {
          mbar_wait_wd(sb + B_OPI + (waited & 1) * 8, (waited >> 1) & 1);
          waited++;
          t0 = lds32(sb + SM_TOPI + (~waited & 1) * 4);
          if (solo && c == 0 && elect_one()) {
            mbar_expect(tokb, 8192);
            bulk_g2s(dst + 4 * 10240 + 2048, tok + 2048, 8192, tokb);
          }
          publish(waited);
          while (__any_sync(~0u, clk() - t0 < d)) {}
        }
        else if (c < 2) spin(prm.dh);
        if (elect_one()) bulk_g2s(dst, src, 2048, bar);
        if (c == 2 && !single) {
          mbar_wait_wd(sb + B_OB, pp);
          if (elect_one()) bulk_g2s(dst + 2048, tok, 8192, full);
        }
        g = 0;
        while (true) {
          mbar_wait_wd(bar, mph);
          mph ^= 1;
          const uint32_t v0 = lds32(dst + chk), v1 = lds32(dst + chk + 1024);
          if (__all_sync(~0u, v0 != ~0u && v1 != ~0u)) break;
          if (elect_one()) {
            mbar_expect(bar, 2048);
            bulk_g2s(dst, src, 2048, bar);
          }
          guard(g);
        }
        mbar_arrive_if(lane == 0, full, solo ? 2 : 1);
        TRACE(c < 2, m, 3 + 2 * c, gtl());
        TRACE(c < 2, m, 4 + 2 * c, g);
      }
    }
    publish(nslots);
    if (warp == 0) mbar_wait_wd(sb + B_END, 0);
  }
  __syncwarp();
  if (wid != 12 && lane0 == 0) mbar_arrive(sb + B_END);
  cluster_sync();
}
__device__ uint32_t g_xa[NBLK * 10 * 4096];
__device__ uint32_t g_h[NBLK * 24 * 4096];

enum { T_A = 0, T_F1 = 1, T_U = 2, T_D = 3, T_F2 = 4, T_NONE = 7 };
__host__ __device__ constexpr int c_phase(int type, int lb) { return C_O + type * 32 + lb; }
constexpr int C_TICKET = c_phase(5, 0), C_EXIT = C_TICKET + 1, C_USED = C_HALF + 2 * NBLK;
constexpr int G_NST = 7;
constexpr uint32_t GS_RED = G_NST * 32768, GS_BAR = GS_RED + 1088, G_SMEM = GS_BAR + 224;
constexpr uint32_t GB_FULL = GS_BAR, GB_EMPTY = GS_BAR + 64, GB_ORD = GS_BAR + 128, GB_READY = GS_BAR + 144, GB_ACK = GS_BAR + 152, GB_GATE = GS_BAR + 160, GB_SIG = GS_BAR + 176, GB_SACK = GS_BAR + 192,
                   GS_SIG = GS_BAR + 208, GS_COL = GS_BAR + 216;
#define FPL 6
constexpr int NF = 16;
constexpr int G_EARLY = 36;
constexpr int G_LATE = 96, PL = 6, ML = 8, DL = 30, TL = 10;
constexpr int GRC = 112, GRP = 32;
constexpr uint32_t E_UP = 1u << 8, E_HALF = 1u << 28, E_GRP = 1u << 29, E_HAND = 1u << 30, E_EXCL = 1u << 31;

struct GParams {
  __nv_bfloat16* out;
  const uint32_t* x;
  int moff, gd;
  int pend;
  uint8_t perm[G_EARLY], first[9];
  uint8_t need[5][2 * NBLK];
  uint32_t tab[G_EARLY * (PL + ML + DL) + G_LATE * TL];
};
constexpr int EL = PL + ML + DL, TAB_TAIL = G_EARLY * EL;
struct GIter {
  int p, left, period;
  uint32_t e, type, lb, n0, kb0, nkb;
  bool gemm, valid;
  DI GIter(const GParams& prm, int col) {
    if (col < G_EARLY) { p = col * EL; left = PL; period = 0; }
    else { p = TAB_TAIL + (col - G_EARLY) * TL; left = TL; period = prm.pend; }
  }
  DI bool next(const GParams& prm, int col) {
    do {
      if (left == 0) {
        if (++period > prm.pend) return false;
        left = period < prm.pend ? ML : DL;
        if (period > 1 && period < prm.pend) p -= ML;
      }
      e = prm.tab[p++]; left--;
    } while ((e & 7) == T_NONE);
    const int b = (e >> 4) & 15, blk = period < prm.pend ? period - b : b;
    type = e & 7; valid = blk >= 0; lb = (e & 8) * 2 + (blk & 15); n0 = (e >> 9) & 127; kb0 = (e >> 16) & 127;
    gemm = type != T_F1 && type != T_F2;
    nkb = valid ? (e >> 23) & 31 : 0;
    return true;
  }
  DI int id_(int pend) const { return period < pend ? period * 10 + ML - left : 160 + DL - left; }
};

#define GLOG(nt, i, v)
template <int TA> DI void wg_ss128(float* d, uint64_t da, uint64_t db, int sc) {
  asm volatile("{.reg .pred p; setp.ne.b32 p, %66, 0;\n"
               "wgmma.mma_async.sync.aligned.m64n128k16.f32.bf16.bf16 "
               "{%0,%1,%2,%3,%4,%5,%6,%7,%8,%9,%10,%11,%12,%13,%14,%15,%16,%17,%18,%19,%20,%21,%22,%23,%24,%25,%26,%27,%28,%29,%30,%31,"
               "%32,%33,%34,%35,%36,%37,%38,%39,%40,%41,%42,%43,%44,%45,%46,%47,%48,%49,%50,%51,%52,%53,%54,%55,%56,%57,%58,%59,%60,%61,%62,%63}, "
               "%64, %65, p, 1, 1, %67, 1;}"
               : ACC16(d, 0), ACC16(d, 16), ACC16(d, 32), ACC16(d, 48) : "l"(da), "l"(db), "r"(sc), "n"(TA));
}

template <int TA> DI void g_mainloop(float* acc, uint32_t sb, uint32_t hand, uint32_t gate, int nkb, int cw, int lane, uint32_t st, uint32_t ph) {
  const uint64_t da0 = (TA ? mkdesc(SMEM0, 4096, 512, 2) : mkdesc(SMEM0, 128, 1024, 0)) + (cw >> 2) * 512;
  const uint64_t db0 = mkdesc(SMEM0 + 16384, 8192, 1024, 1);
  uint32_t prev = 0;
#pragma unroll 1
  for (int kb = 0; kb < nkb; kb++) {
    mbar_wait(sb + GB_FULL + 8 * st, ph);
    mbar_wait(gate, 1);
    const uint64_t da = da0 + st * 2048, db = db0 + st * 2048;
    wg_fence();
#pragma unroll
    for (int k = 0; k < 4; k++) wg_ss128<TA>(acc, da + k * (TA ? 64 : 16), db + k * 128, 1);
    wg_commit();
    mbar_arrive_if(hand && kb == nkb - 1 && lane == 0, hand);
    wg_wait<1>();
    mbar_arrive_if(kb > 0 && lane == 0, sb + GB_EMPTY + 8 * prev);
    prev = st;
    if (++st == G_NST) { st = 0; ph ^= 1; }
  }
  wg_wait<0>();
  reg_fence<64>(acc);
  mbar_arrive_if(lane == 0, sb + GB_EMPTY + 8 * prev);
}

__global__ void __launch_bounds__(640, 1)
g_kernel(const __grid_constant__ CUtensorMap mapWo, const __grid_constant__ CUtensorMap mapWg, const __grid_constant__ CUtensorMap mapWu,
         const __grid_constant__ CUtensorMap mapWd, const __grid_constant__ GParams prm) {
  const uint32_t sb = smem_base();
  const int wid = __shfl_sync(~0u, threadIdx.x >> 5, 0), lane = threadIdx.x & 31;
  if (threadIdx.x == 0) {
    if ((sb & 0x3FFFF) != SMEM0) __trap();
    {
      uint32_t sm; asm volatile("mov.u32 %0, %%smid;" : "=r"(sm));
      uint32_t* const tk = &g_cnt[C_TICKET * CSTRIDE];
      uint32_t c = atomicAdd(tk, 1);
      if (c < G_EARLY) {
        const uint32_t k = sm < 64 ? (sm >> 1) & 7 : sm < 120 ? 1 + ((sm - 64) >> 1) % 7 : sm < 124 ? 1 + ((sm >> 1) & 1) : 0;
        const uint32_t t = atomicAdd(tk + 1 + k, 1);
        atomicAdd(tk + 9, 1);
        if (t < prm.first[k + 1] - prm.first[k]) c = prm.perm[prm.first[k] + t];
        else {
          uint32_t o = atomicAdd(tk + 10, 1), g = 0;
          while (ld_acq(tk + 9) < G_EARLY) guard(g);
          for (int j = 0; j < 8; j++)
            for (uint32_t i = prm.first[j] + ld_acq(tk + 1 + j); i < prm.first[j + 1]; i++) if (o-- == 0) c = prm.perm[i];
        }
      }
      sts32(sb + GS_COL, c);
    }
    for (int i = 0; i < G_NST; i++) { mbar_init(sb + GB_FULL + 8 * i, 1); mbar_init(sb + GB_EMPTY + 8 * i, 8); }
    mbar_init(sb + GB_ORD, 8); mbar_init(sb + GB_ORD + 8, 8); mbar_init(sb + GB_READY, 1); mbar_init(sb + GB_ACK, 1);
    mbar_init(sb + GB_GATE, 1); mbar_init(sb + GB_GATE + 8, 1);
    mbar_init(sb + GB_SIG, 8); mbar_init(sb + GB_SIG + 8, 8); mbar_init(sb + GB_SACK, 1); mbar_init(sb + GB_SACK + 8, 1);
    fence_async_smem();
  }
  __syncthreads();
  const int col = __shfl_sync(~0u, lds32(sb + GS_COL), 0);

  if (wid >= 16) {
    GIter t(prm, col);
    asm volatile("setmaxnreg.dec.sync.aligned.u32 %0;" ::"n"(GRP));
    uint32_t st = 0, ph = 1, k = 0;
    if (wid == 16) {
      while (t.next(prm, col)) {
        const CUtensorMap* m0 = t.type == T_A ? &mapWo : t.type == T_U ? &mapWg : &mapWd;
        const CUtensorMap* m1 = t.type == T_U ? &mapWu : m0;
        const int c0 = t.type == T_U ? t.n0 * 64 : (t.n0 & 7) * 128, c1 = t.type == T_U ? c0 : c0 + 64;
        if ((t.e & (E_HALF | E_UP)) == E_UP) poll_ge(&g_cnt[c_phase(t.type, t.lb) * CSTRIDE], prm.need[t.type][t.lb]);
#pragma unroll 1
        for (uint32_t kb = t.kb0; kb < t.kb0 + t.nkb; kb++) {
          mbar_wait(sb + GB_EMPTY + 8 * st, ph);
          if (elect_one()) {
            const uint32_t full = sb + GB_FULL + 8 * st, dst = sb + st * 32768;
            mbar_expect(full, (t.e & E_HALF) ? 24576 : 32768);
            tma_2d(dst + 16384, m0, c0, kb * 64, full);
            tma_2d(dst + 24576, m1, c1, kb * 64, full);
          }
          if (++st == G_NST) { st = 0; ph ^= 1; }
        }
      }
    } else if (wid == 17) {
      while (t.next(prm, col)) {
        if (!t.nkb) continue;
        const char* asrc = t.type == T_A ? (const char*)g_oT + (size_t)t.lb * (96 * 16384)
                         : t.type == T_U ? (const char*)g_xa + (size_t)(t.lb & 15) * (10 * 16384) : (const char*)g_h + (size_t)(t.lb & 15) * (24 * 16384);
        const uint32_t up = (t.e & E_HALF) ? (t.e & E_UP) * 32 : 0;
        GLOG(t.id_(prm.pend), 1, gtime());
        mbar_wait(sb + GB_READY, k & 1);
        mbar_arrive_if(lane == 0, sb + GB_ACK);
        k++;
#pragma unroll 1
        for (uint32_t kb = t.kb0; kb < t.kb0 + t.nkb; kb++) {
          mbar_wait(sb + GB_EMPTY + 8 * st, ph);
          if (elect_one()) bulk_g2s(sb + st * 32768 + up, asrc + (size_t)kb * 16384 + up, (t.e & E_HALF) ? 8192 : 16384, sb + GB_FULL + 8 * st);
          if (++st == G_NST) { st = 0; ph ^= 1; }
        }
      }
    } else if (wid == 18) {
      while (t.next(prm, col)) {
        if (!t.nkb) continue;
        const bool lower = t.type == T_A && (t.e & (E_HALF | E_UP)) == E_HALF;
        poll_ge(&g_cnt[(lower ? C_HALF + t.lb : c_phase(t.type, t.lb)) * CSTRIDE], prm.need[t.type][t.lb]);
        fence_async_global();
        GLOG(t.id_(prm.pend), 2, gtime());
        mbar_wait(sb + GB_ACK, (k & 1) ^ 1);
        mbar_arrive_if(lane == 0, sb + GB_READY);
        k++;
      }
    } else {
      uint32_t live = 3, par = 0, g = 0;
      while (live) {
        const bool ev = lane < 2 && ((live >> lane) & 1) && mbar_test(sb + GB_SIG + 8 * lane, (par >> lane) & 1);
        const uint32_t evs = __ballot_sync(~0u, ev);
        if (!evs) { guard(g); __nanosleep(20); continue; }
        const uint32_t msg = ev ? lds32(sb + GS_SIG + 4 * lane) : 0;
        mbar_arrive_if(ev, sb + GB_SACK + 8 * lane);
        mbar_arrive_if(msg >> 31, sb + GB_GATE + 8 * lane);
        if (msg) red_rel(&g_cnt[(msg & 0xffff) * CSTRIDE], (msg >> 16) & 255);
        par ^= evs;
        live &= ~__ballot_sync(~0u, ev && !msg);
        g = 0;
      }
      asm volatile("griddepcontrol.wait;" ::: "memory");
      if (col < 80 && lane < 16) g_mem[(col >> 4) * 2048 + (lane >> 3) * 1024 + 512 + prm.moff + (col & 15) * 8 + (lane & 7)] = make_uint4(~0u, ~0u, ~0u, ~0u);
      uint32_t last = 0;
      if (lane == 0) last = atomicAdd(&g_cnt[C_EXIT * CSTRIDE], 1) == gridDim.x - 1;
      if (__shfl_sync(~0u, last, 0)) {
        g_cnt[C_TICKET * CSTRIDE + lane] = 0;
        for (int i = lane; i < C_USED; i += 32) g_cnt[i * CSTRIDE] = 0;
      }
    }
  } else {
    asm volatile("setmaxnreg.inc.sync.aligned.u32 %0;" ::"n"(GRC));
    const int cw = wid & 7, wk = wid >> 3;
    GIter t(prm, col);
    uint32_t pos = 0, seen = 0, waited = 0;
    uint32_t nsig = 0;
    auto signal = [&](uint32_t msg) {
      mbar_wait(sb + GB_SACK + 8 * wk, (nsig++ & 1) ^ 1);
      if (cw == 0) sts32(sb + GS_SIG + 4 * wk, msg);
      __syncwarp();
      mbar_arrive_if(lane == 0, sb + GB_SIG + 8 * wk);
    };
    if (col < G_EARLY) {
      spin(prm.gd);
#pragma unroll 1
      for (int rg = 96 + col * 2 + wk; rg < 256; rg += 2 * G_EARLY) {
        uint32_t a[10];
        const uint32_t* src = prm.x + (size_t)(rg * 8 + (lane >> 2)) * (DM / 2) + cw * 40 + (lane & 3);
#pragma unroll
        for (int i = 0; i < 10; i++) a[i] = __ldg(src + i * 4);
        first_ln(a, rg, sb + GS_RED + wk * 512, cw, lane, 1 + wk);
        signal((C_XN + (rg >> 4)) | ((XN_TARGET / NF) << 16));
        bar_sync(1 + wk, 256);
      }
    }
    while (t.next(prm, col)) {
      const uint32_t pos0 = pos;
      pos = (pos + t.nkb) % (2 * G_NST);
      if (((t.e >> 29) & 1) != wk) { seen += (t.e >> 30) & 1; continue; }
      const uint32_t type = t.type, blk = t.lb & 15, layer = t.lb >> 4, n0 = t.n0;
      if (cw == 0 && t.valid) GLOG(t.id_(prm.pend), 0, 0x80000000u | type | (t.lb << 3) | (n0 << 8) | (t.nkb << 16));
      if (!t.gemm) {
        if (!t.valid) continue;
        const int rg = blk * 16 + n0;
        float4 v[5];
        const int off = (n0 * 40 + cw * 5) * 32 + lane, npl = t.kb0;
        const uint2* src = acc_planes(t.lb, type == T_F2) + off;
        if (cw == 0) {
          poll_ge(&g_cnt[c_phase(type, t.lb) * CSTRIDE], prm.need[type][t.lb]);
          mbar_arrive_if((t.e & E_EXCL) && lane == 0, sb + GB_GATE + 8 * wk);
          GLOG(t.id_(prm.pend), 2, gtime()); GLOG(t.id_(prm.pend), 3, gtime());
        }
        bar_sync(1 + wk, 256);
        {
          const uint32_t eye = (lane >> 3) == (lane & 3) ? ((lane & 4) ? 0x3f800000u : 0x00003f80u) : 0u;
#pragma unroll
          for (int i = 0; i < 5; i++) v[i] = make_float4(0.f, 0.f, 0.f, 0.f);
#pragma unroll 1
          for (int p0 = 0; p0 < npl; p0 += FPL) {
            uint32_t r[FPL / 2][5][4];
#pragma unroll
            for (int p = 0; p < FPL; p++)
#pragma unroll
              for (int i = 0; i < 5; i++) {
                const uint2 w = p0 + p < npl ? __ldcg(src + (size_t)(p0 + p) * PLANE + i * 32) : make_uint2(0, 0);
                r[p >> 1][i][(p & 1) * 2] = w.x; r[p >> 1][i][(p & 1) * 2 + 1] = w.y;
              }
#pragma unroll
            for (int p = 0; p < FPL / 2; p++) {
              if (p0 + 2 * p >= npl) break;
              if (t.e & E_EXCL) {
#pragma unroll
                for (int i = 0; i < 5; i++) mma16816(&v[i].x, r[p][i], eye, eye);
              } else {
#pragma unroll
                for (int i = 0; i < 5; i++) {
                  const uint32_t* w = r[p][i];
                  v[i].x += blo(w[0]) + blo(w[2]); v[i].y += bhi(w[0]) + bhi(w[2]); v[i].z += blo(w[1]) + blo(w[3]); v[i].w += bhi(w[1]) + bhi(w[3]);
                }
              }
            }
          }
        }
        if (type == T_F2 && layer == 1) {
          uint2* dst = (uint2*)prm.out + (size_t)(rg * 8 + (lane >> 2)) * (DM / 4) + cw * 20 + (lane & 1) * 2 + ((lane >> 1) & 1);
#pragma unroll
          for (int i = 0; i < 5; i++) {
            const uint32_t a = pack2(v[i].x, v[i].y), b = pack2(v[i].z, v[i].w);
            const uint32_t o = __shfl_xor_sync(~0u, (lane & 1) ? a : b, 1);
            dst[i * 4] = (lane & 1) ? make_uint2(o, b) : make_uint2(a, o);
          }
        } else {
          uint2* nx = (type == T_F1 ? acc_planes(t.lb, 1) : acc_planes(NBLK + blk, 0)) + off;
#pragma unroll
          for (int i = 0; i < 5; i++) {
            const uint2 w = make_uint2(pack2(v[i].x, v[i].y), pack2(v[i].z, v[i].w));
            nx[i * 32] = w;
            v[i] = make_float4(blo(w.x), bhi(w.x), blo(w.y), bhi(w.y));
          }
          float mean, rstd;
          ln_stats(v, sb + GS_RED + wk * 512, cw, lane, 1 + wk, mean, rstd);
          if (type == T_F2) store_img<4, 2048>(xn_row_group(1, rg) + lane, v, cw, mean, rstd);
          else store_img<3, 4096>(g_xa + (size_t)(blk * 10 * 4096 + n0 * 256) + lane, v, cw, mean, rstd);
        }
      } else {
        float acc[64];
#pragma unroll
        for (int j = 0; j < 64; j++) acc[j] = 0.f;
        if (waited != seen) { mbar_wait(sb + GB_ORD + 8 * (wk ^ 1), waited & 1); waited++; }
        const uint32_t hand = (t.e & E_HAND) ? sb + GB_ORD + 8 * wk : 0;
        if (!t.valid) { mbar_arrive_if(hand && lane == 0, hand); continue; }
        if (cw == 0) GLOG(t.id_(prm.pend), 3, gtime());
        const uint32_t ph = pos0 >= G_NST, st = pos0 - ph * G_NST, early = (t.e & E_EXCL) ? 0 : hand;
        const bool idle = (t.e & E_HALF) && ((t.e >> 8) & 1) != (cw >> 2);
        if (idle) {
          uint32_t s2 = st, p2 = ph;
#pragma unroll 1
          for (uint32_t kb = 0; kb < t.nkb; kb++) {
            mbar_wait(sb + GB_FULL + 8 * s2, p2);
            mbar_arrive_if(lane == 0, sb + GB_EMPTY + 8 * s2);
            if (++s2 == G_NST) { s2 = 0; p2 ^= 1; }
          }
          mbar_arrive_if(early && lane == 0, early);
        } else if (type == T_A) g_mainloop<1>(acc, sb, early, sb + GB_GATE + 8 * (wk ^ 1), t.nkb, cw, lane, st, ph);
        else g_mainloop<0>(acc, sb, early, sb + GB_GATE + 8 * (wk ^ 1), t.nkb, cw, lane, st, ph);
        if (cw == 0) GLOG(t.id_(prm.pend), 4, gtime());
        if (idle) {
        } else if (type == T_U) {
          uint32_t* dst = g_h + (size_t)((blk * 24 + n0) * 4096 + cw * 512) + lane;
#pragma unroll
          for (int j = 0; j < 8; j++) {
            float h[4];
#pragma unroll
            for (int e = 0; e < 4; e++) {
              float th;
              asm("tanh.approx.f32 %0, %1;" : "=f"(th) : "f"(0.5f * acc[4 * j + e]));
              h[e] = acc[32 + 4 * j + e] * fmaf(th, 0.5f, 0.5f);
            }
            dst[j * 32] = pack2(h[0], h[1]);
            dst[j * 32 + 256] = pack2(h[2], h[3]);
          }
        } else {
          uint2* dst = acc_planes(t.lb, type == T_D) + (size_t)((1 + (n0 >> 3)) * PLANE + (2 * cw * 40 + (n0 & 7) * 8) * 32) + lane;
#pragma unroll
          for (int j = 0; j < 16; j++) {
            const float* a = acc + (j >> 1) * 8 + (j & 1) * 2;
            dst[(j >> 1) * 32 + (j & 1) * 1280] = make_uint2(pack2(a[0], a[1]), pack2(a[4], a[5]));
          }
        }
        mbar_arrive_if(hand != early && lane == 0, hand);
      }
      if (cw == 0) GLOG(t.id_(prm.pend), 5, gtime());
      if (cw == 0) GLOG(t.id_(prm.pend), 6, gtime());
      if (type == T_F2 && layer == 1) mbar_arrive_if((t.e & E_EXCL) && cw == 0 && lane == 0, sb + GB_GATE + 8 * wk);
      else
        signal((type != T_F2 ? c_phase(type + 1, t.lb) | (1 << 16) : (C_XN + NBLK + blk) | ((XN_TARGET / NF) << 16)) | (t.gemm ? 0 : t.e & E_EXCL));
    }
    signal(0);
  }
}

typedef CUresult (*EncodeFn)(CUtensorMap*, CUtensorMapDataType, cuuint32_t, void*, const cuuint64_t*, const cuuint64_t*, const cuuint32_t*,
                             const cuuint32_t*, CUtensorMapInterleave, CUtensorMapSwizzle, CUtensorMapL2promotion, CUtensorMapFloatOOBfill);
static CUtensorMap make_map(EncodeFn fn, const void* p, uint64_t inner, uint64_t outer, uint32_t bi, uint32_t bo) {
  CUtensorMap m;
  cuuint64_t dims[2] = {inner, outer}, str[1] = {inner * 2};
  cuuint32_t box[2] = {bi, bo}, es[2] = {1, 1};
  fn(&m, CU_TENSOR_MAP_DATA_TYPE_BFLOAT16, 2, (void*)p, dims, str, box, es, CU_TENSOR_MAP_INTERLEAVE_NONE, CU_TENSOR_MAP_SWIZZLE_128B,
     CU_TENSOR_MAP_L2_PROMOTION_L2_256B, CU_TENSOR_MAP_FLOAT_OOB_FILL_NONE);
  return m;
}
struct Tune {
  int lag = 11, excl = 7, gonly = 0, xl = 1, ronly = 0, pn = 30;
  int da = 100, db = 350, dc = 650, dd = 650, d2 = 2000, p1 = 400, p2 = 800;
  int ea = 60, eb = 310, ec = 550, ed = 550, e2 = 2200, q1 = 200, q2 = 400, d3 = 60, moff = 192, ds = 400, dh = 60, pa = 0, pb = 0, pc = 0, pd = 0, pe = 0, pf = 0, pg = 0, ph = 0, hold = 1, wpf = 4, gd = 22000, dq = 600, sl = 18;
};
static void fill_r(RParams& p, const Tune& t, int lag, int n0, int n1) {
  r_fill_desc(p);
  p.nslots = 0; p.d3 = t.d3; p.pn = t.pn; p.moff = t.moff; p.ds = t.ds; p.dh = t.dh; p.dq = t.dq;
  for (int c = 0; c < 5; c++) { p.d2[c] = t.d2 + (c == 0 ? 0 : c < 3 ? t.p1 : t.p2); p.d2[5 + c] = t.e2 + (c == 0 ? 0 : c < 3 ? t.q1 : t.q2); }
  const int d1[8] = {t.da, t.db, t.dc, t.dd, t.ea, t.eb, t.ec, t.ed};
  for (int i = 0; i < 8; i++) p.d1[i] = d1[i];
  int last[2] = {0, 0}, n = 0;
  for (int s0 = 0; s0 < NSEG + lag; s0++)
    for (int l = 0; l < 2; l++) {
      const int s = l ? s0 - lag : s0;
      if (s < 0 || s >= NSEG) continue;
      if (n >= n0 && n < n1) { p.slot[p.nslots] = s | (l << 6) | (last[l] << 8) | (((s & 3) == 3 ? C_O + l * NBLK + s / 4 : s == (l ? 61 : 1) ? C_HALF + l * NBLK + s / 4 : 0) << 16); last[l] = ++p.nslots; }
      n++;
    }
  for (int i = 0; i + 1 < p.nslots; i++) if (((p.slot[i] ^ p.slot[i + 1]) >> 6) & 1) p.slot[i] |= 128;
}
static uint32_t g_entry(int grp, int type, int layer, int blk, int i, int ks) {
  int n0 = i, kb0 = 0, kb1 = type == T_U ? 10 : 0;
  if (type == T_F1 || type == T_F2) kb0 = kb1 = ks + 1;
  if (type == T_A || type == T_D) {
    const int KB = type == T_A ? 96 : 24, sp = i / 5;
    n0 = i % 5 | (sp << 3); kb0 = sp * KB / ks; kb1 = (sp + 1) * KB / ks;
  }
  return type | (layer << 3) | (blk << 4) | (n0 << 9) | (kb0 << 16) | ((kb1 - kb0) << 23) | (grp ? E_GRP : 0);
}
static bool g_is_gemm(uint32_t e) { return (e & 7) == T_A || (e & 7) == T_U || (e & 7) == T_D; }
static void g_handover(uint32_t* e, int len) {
  uint32_t next = 0;
  for (int i = len - 1; i >= 0; i--)
    if (g_is_gemm(e[i])) { if ((e[i] & E_GRP) != next) e[i] |= E_HAND; next = e[i] & E_GRP; }
}
struct GList {
  GParams& g; uint32_t* tab; int ncol, stride, len, n[G_LATE], load[G_LATE], grp[G_LATE];
  GList(GParams& g_, uint32_t* t, int nc, int st, int l) : g(g_), tab(t), ncol(nc), stride(st), len(l) { for (int c = 0; c < nc; c++) { n[c] = load[c] = 0; grp[c] = 1; } }
  void add(int type, int lb, int ks, int c0, int c1, uint32_t flags = 0, int i0 = 0, int i1 = 999, int step = 1) {
    const int half = (flags & E_HALF) != 0, ln = type == T_F1 || type == T_F2;
    const int cnt = (type == T_U ? 24 : ln ? NF : 5 * ks) << half;
    if (type < T_F2) g.need[type + 1][lb] = cnt;
    int used[G_LATE] = {0};
    for (int i = i0; i < cnt && i < i1; i += step) {
      int best = c0;
      for (int c = c0; c < c1; c++) if (used[c] < used[best] || (used[c] == used[best] && load[c] < load[best])) best = c;
      used[best]++;
      if (!ln) grp[best] ^= 1;
      const uint32_t e = g_entry(grp[best], type, lb >> 4, lb & 15, i >> half, ks) | flags | (ln ? E_EXCL : 0) | ((i & half) ? E_UP : 0);
      if (n[best] >= len) abort();
      tab[best * stride + n[best]++] = e;
      load[best] += (((e >> 23) & 31) >> half) + 2;
    }
  }
  void put(int c, uint32_t e) { if (n[c] >= len) abort(); tab[c * stride + n[c]++] = e; if (g_is_gemm(e)) grp[c] = (e & E_GRP) != 0; }
  void finish() { for (int c = 0; c < ncol; c++) g_handover(tab + c * stride, len); }
};
static void fill_g(GParams& g, const Tune& t, void* out) {
  g.out = (__nv_bfloat16*)out;  g.pend = NBLK - 2;
  for (int b = 0; b < 2 * NBLK; b++) {
    g.need[T_A][b] = 96; g.need[T_F1][b] = 20; g.need[T_U][b] = NF; g.need[T_D][b] = 32; g.need[T_F2][b] = 15;
  }
  {
    const uint8_t perm[G_EARLY] = {0, 1, 2, 3, 16, 17, 18, 19, 34, 35, 4, 20, 21, 15, 22, 23, 5, 6, 7, 8, 9, 24, 25, 26, 10, 11, 12, 13, 14, 27, 28, 29, 30, 31, 32, 33};
    const uint8_t first[9] = {0, 10, 13, 16, 20, 24, 28, 32, 36};
    const int* pk = &t.pa;
    for (int i = 0; i < G_EARLY; i++) g.perm[i] = t.pa ? (pk[i / 5] >> (6 * (i % 5))) & 63 : perm[i];
    for (int i = 0; i < 9; i++) g.first[i] = first[i];
  }
  for (uint32_t& e : g.tab) e = T_NONE;
  GList pr(g, g.tab, G_EARLY, EL, PL);
  pr.add(T_A, 0, 7, 1, 36, E_HALF, 0, 999, 2); pr.add(T_A, 0, 7, 1, 36, E_HALF, 1, 999, 2); pr.add(T_F1, 0, 7, 20, 36); pr.add(T_U, 0, 0, 12, 36);
  pr.add(T_D, 0, 3, 20, 36); pr.add(T_F2, 0, 3, 20, 36);
  pr.finish();
  const int d = 3;
  const uint32_t xa = (t.excl & 1) ? E_EXCL : 0, xu = (t.excl & 2) ? E_EXCL : 0, xd = (t.excl & 4) ? E_EXCL : 0;
  for (int c = 0; c < G_EARLY; c++) {
    uint32_t* e = g.tab + c * EL + PL;
    if (c < 20) {
      *e++ = g_entry(0, T_A, 0, 0, c, 4) | xa;
      if (c < NF) *e++ = g_entry(0, T_F1, 0, 0, c, 4) | ((t.xl & 1) ? E_EXCL : 0);
      *e++ = g_entry(1, T_A, 1, d, c, 4);
      if (c >= 20 - NF) *e++ = g_entry(1, T_F1, 1, d, c - (20 - NF), 4);
    } else {
      const int j = c - 20;
      const uint32_t hf = E_HALF | ((j & 1) ? E_UP : 0);
      *e++ = g_entry(0, T_U, 0, 0, j, 0);
      *e++ = g_entry(1, T_U, 0, 0, 16 + j / 2, 0) | hf | xu;
      *e++ = g_entry(0, T_U, 1, d + 1, 16 + j / 2, 0) | hf;
      if (j < 15) *e++ = g_entry(1, T_D, 0, 0, j, 3) | xd;
      *e++ = g_entry(1, T_F2, 0, 0, j, 3) | ((t.xl & 2) ? E_EXCL : 0);
      if (j < 15) *e++ = g_entry(0, T_D, 1, d + 1, j, 3);
      *e++ = g_entry(0, T_U, 1, d, j, 0);
      *e++ = g_entry(1, T_F2, 1, d + 1, j, 3);
    }
    g_handover(g.tab + c * EL + PL, ML);
  }
  GList dr(g, g.tab + PL + ML, G_EARLY, EL, DL);
  GList tl(g, g.tab + TAB_TAIL, G_LATE, TL, TL);
  const int L1 = NBLK;
  auto ufull = [&](int lb) { dr.add(T_U, lb, 0, 20, 36, 0, 0, 16); g.need[T_D][lb] = 32; };
  auto uhalf = [&](int lb) { dr.add(T_U, lb, 0, 20, 36, E_HALF, 32); g.need[T_D][lb] = 32; };
  for (int c = 0; c < G_EARLY; c++)
    for (int i = 0; i < ML; i++) {
      uint32_t e = g.tab[c * EL + PL + i] & ~E_HAND;
      const uint32_t ty = e & 7;
      if (ty == T_NONE || ((e & 8) && (ty == T_F2 || (ty == T_U && !(e & E_HALF))))) continue;
      e = (e & ~0xf0u) | (14 - ((e >> 4) & 15)) << 4;
      dr.put(c, e | (ty == T_F2 ? E_EXCL : 0));
    }
  dr.add(T_A, 15, 4, 0, 20, E_EXCL);
  dr.add(T_F1, 15, 4, 0, 16);
  dr.add(T_U, 15, 0, 12, 36, E_EXCL);
  for (int c = 0; c < 20; c++) {
    const int tile = c % 5, sp = c / 5, len = tile < 2 ? (96 - t.sl) / 3 : 48 - t.sl, nl = tile < 2 ? 3 : 2;
    const int k0 = sp <= nl ? sp * len : nl * len + t.sl, nk = sp < nl ? len : sp == 3 ? 96 - k0 : t.sl;
    dr.put(c, (g_entry(dr.grp[c] ^ 1, T_A, 1, 12, c, 4) & ~0x0fff0000u) | k0 << 16 | nk << 23);
  }
  dr.add(T_F1, L1 + 12, 4, 0, 16);
  uhalf(L1 + 11);
  dr.add(T_D, 15, 3, 20, 36, E_EXCL); dr.add(T_F2, 15, 3, 20, 36);
  dr.add(T_A, L1 + 13, 4, 0, 20); dr.add(T_F1, L1 + 13, 4, 0, 20);
  ufull(L1 + 11);
  dr.add(T_D, L1 + 11, 3, 20, 36);
  ufull(L1 + 12); uhalf(L1 + 12);
  dr.add(T_A, L1 + 14, 4, 0, 20);
  dr.add(T_A, L1 + 15, 7, 0, 35, E_HALF, 0, 999, 2); dr.add(T_A, L1 + 15, 7, 0, 35, E_HALF | E_EXCL, 1, 999, 2);
  dr.add(T_F1, L1 + 14, 4, 0, 16);
  dr.add(T_F1, L1 + 15, 7, 20, 36);
  dr.add(T_F2, L1 + 10, 3, 0, 16); dr.add(T_F2, L1 + 11, 3, 4, 20);  dr.add(T_F2, L1 + 12, 3, 0, 20);
  dr.add(T_D, L1 + 13, 3, 20, 36, (t.hold & 1) ? E_UP : 0); dr.add(T_F2, L1 + 13, 3, 20, 36);
  dr.finish();
  tl.add(T_D, L1 + 12, 3, 72, G_LATE);
  tl.add(T_U, L1 + 14, 0, 0, 24); tl.add(T_U, L1 + 13, 0, 24, 48);
  tl.add(T_D, L1 + 14, 4, 0, 48, E_HALF);
  tl.add(T_F2, L1 + 14, 4, 0, 48);
  tl.add(T_U, L1 + 15, 0, 48, G_LATE, E_HALF);
  tl.add(T_D, L1 + 15, 4, 48, G_LATE, E_HALF);
  tl.add(T_F2, L1 + 15, 4, 48, G_LATE);
  tl.finish();
}
static void launch_all(void* const* d_in, void* d_out, const Tune& t, cudaStream_t st) {
  static EncodeFn fn = nullptr;
  if (!fn) {
    void* f = nullptr;
    cudaDriverEntryPointQueryResult qr;
    cudaGetDriverEntryPoint("cuTensorMapEncodeTiled", &f, cudaEnableDefault, &qr);
    fn = (EncodeFn)f;
    cudaFuncSetAttribute(r_kernel, cudaFuncAttributeMaxDynamicSharedMemorySize, R_SMEM);
    cudaFuncSetAttribute(g_kernel, cudaFuncAttributeMaxDynamicSharedMemorySize, G_SMEM);
  }
  const CUtensorMap mq = make_map(fn, d_in[2], HD, DM, 64, 128), mk = make_map(fn, d_in[3], HD, DM, 64, 128), mv = make_map(fn, d_in[4], HD, DM, 64, 128),
                    mo = make_map(fn, d_in[5], DM, HD, 64, 64), mg = make_map(fn, d_in[8], FF, DM, 64, 64), mu = make_map(fn, d_in[9], FF, DM, 64, 64),
                    md = make_map(fn, d_in[10], DM, FF, 64, 64);
  auto launch_r = [&](int lag, int n0, int n1) {
    RParams p;
    fill_r(p, t, lag, n0, n1);
    for (int i = 0; i < 4; i++) p.w[i] = (const char*)d_in[2 + i];
    p.mem0 = (const uint4*)d_in[1]; p.x = (const uint32_t*)d_in[0]; p.pf = t.wpf;
    cudaLaunchConfig_t cfg = {};
    cfg.gridDim = dim3(3, NH); cfg.blockDim = dim3(512); cfg.dynamicSmemBytes = R_SMEM; cfg.stream = st;
    cudaLaunchAttribute at[1];
    at[0].id = cudaLaunchAttributeClusterDimension; at[0].val.clusterDim.x = 3; at[0].val.clusterDim.y = 1; at[0].val.clusterDim.z = 1;
    cfg.attrs = at; cfg.numAttrs = 1;
    cudaLaunchKernelEx(&cfg, r_kernel, mq, mk, mv, mo, p);
  };
  auto launch_g = [&](const GParams& g, bool pdl) {
    cudaLaunchConfig_t cfg = {};
    cfg.gridDim = dim3(132); cfg.blockDim = dim3(640); cfg.dynamicSmemBytes = G_SMEM; cfg.stream = st;
    cudaLaunchAttribute at[2];
    at[0].id = cudaLaunchAttributeProgrammaticStreamSerialization; at[0].val.programmaticStreamSerializationAllowed = 1;
    cfg.attrs = at; cfg.numAttrs = pdl ? 1 : 0;
    cudaLaunchKernelEx(&cfg, g_kernel, mo, mg, mu, md, g);
  };
  GParams g;
  fill_g(g, t, d_out);
  g.moff = t.moff; g.gd = t.gd; g.x = (const uint32_t*)d_in[0];
  launch_r(t.lag, 0, 2 * NSEG);
  launch_g(g, true);
}

extern "C" void kernel_launch(void* const* d_in, const int* in_sizes, int n_in, void* d_out, int out_size) {
  launch_all(d_in, d_out, Tune(), cudaStreamPerThread);
}
```

```cpp
#include <cuda_runtime.h>
#include <cuda_bf16.h>
#include <cuda.h>
#include <stdint.h>
#include <stdlib.h>

constexpr int SEQ = 2048, DM = 640, NH = 32, DH = 192, HD = NH * DH, FF = 1536;
constexpr int NSEG = 64, SEGL = 32, NMEM = 8;
constexpr int NBLK = 16;

#define DI __device__ __forceinline__

DI uint32_t smem_base() {
  extern __shared__ __align__(1024) unsigned char smem_raw[];
  uint32_t a;
  asm volatile("{.reg .u64 t; cvta.to.shared.u64 t, %1; cvt.u32.u64 %0, t;}" : "=r"(a) : "l"(smem_raw));
  return a;
}
DI uint32_t mapa(uint32_t a, uint32_t r) {
  uint32_t o;
  asm("mapa.shared::cluster.u32 %0, %1, %2;" : "=r"(o) : "r"(a), "r"(r));
  return o;
}
DI void mbar_init(uint32_t bar, uint32_t cnt) { asm volatile("mbarrier.init.shared::cta.b64 [%0], %1;" ::"r"(bar), "r"(cnt) : "memory"); }
DI void mbar_arrive(uint32_t bar) { asm volatile("mbarrier.arrive.shared::cta.b64 _, [%0];" ::"r"(bar) : "memory"); }
DI void mbar_arrive_remote(uint32_t bar) { asm volatile("mbarrier.arrive.release.cluster.shared::cluster.b64 _, [%0];" ::"r"(bar) : "memory"); }
DI void mbar_expect(uint32_t bar, uint32_t tx) { asm volatile("mbarrier.arrive.expect_tx.shared::cta.b64 _, [%0], %1;" ::"r"(bar), "r"(tx) : "memory"); }
DI void mbar_arrive_if(bool p, uint32_t bar) { asm volatile("{.reg .pred p; setp.ne.b32 p, %1, 0; @p mbarrier.arrive.shared::cta.b64 _, [%0];}" ::"r"(bar), "r"((int)p) : "memory"); }
DI void mbar_arrive_if(bool p, uint32_t bar, uint32_t cnt) {
  asm volatile("{.reg .pred p; setp.ne.b32 p, %1, 0; @p mbarrier.arrive.shared::cta.b64 _, [%0], %2;}" ::"r"(bar), "r"((int)p), "r"(cnt) : "memory");
}
DI void mbar_expect_if(bool p, uint32_t bar, uint32_t tx) {
  asm volatile("{.reg .pred p; setp.ne.b32 p, %2, 0; @p mbarrier.arrive.expect_tx.shared::cta.b64 _, [%0], %1;}" ::"r"(bar), "r"(tx), "r"((int)p) : "memory");
}
DI bool mbar_test(uint32_t bar, uint32_t par) {
  uint32_t ok;
  asm volatile("{.reg .pred p; mbarrier.test_wait.parity.shared::cta.b64 p, [%1], %2; selp.u32 %0, 1, 0, p;}" : "=r"(ok) : "r"(bar), "r"(par) : "memory");
  return ok;
}
DI void mbar_wait(uint32_t bar, uint32_t par) {
  asm volatile(
      "{.reg .pred p;\n"
      "LOOP:\n"
      "mbarrier.try_wait.parity.shared::cta.b64 p, [%0], %1;\n"
      "@!p bra LOOP;\n}" ::"r"(bar), "r"(par) : "memory");
}
DI void mbar_wait_wd(uint32_t bar, uint32_t par) {
  asm volatile(
      "{.reg .pred p; .reg .u32 c;\n"
      "mov.u32 c, 0;\n"
      "LOOP:\n"
      "mbarrier.try_wait.parity.shared::cta.b64 p, [%0], %1;\n"
      "@p bra DONE;\n"
      "add.u32 c, c, 1;\n"
      "setp.lt.u32 p, c, 4000000;\n"
      "@p bra LOOP;\n"
      "trap;\n"
      "DONE:\n}" ::"r"(bar), "r"(par) : "memory");
}
DI void fence_async_smem() { asm volatile("fence.proxy.async.shared::cta;" ::: "memory"); }
DI void fence_async_global() { asm volatile("fence.proxy.async.global;" ::: "memory"); }
DI void bar_sync(int id, int n) { asm volatile("bar.sync %0, %1;" ::"r"(id), "r"(n) : "memory"); }
DI void bar_arrive(int id, int n) { asm volatile("bar.arrive %0, %1;" ::"r"(id), "r"(n) : "memory"); }
DI void cluster_sync() { asm volatile("barrier.cluster.arrive.release.aligned; barrier.cluster.wait.acquire.aligned;" ::: "memory"); }
DI bool elect_one() {
  uint32_t p;
  asm volatile("{.reg .pred p; elect.sync _|p, 0xffffffff; selp.u32 %0, 1, 0, p;}" : "=r"(p));
  return p;
}
DI void bulk_g2s(uint32_t dst, const void* src, uint32_t bytes, uint32_t bar) {
  asm volatile("cp.async.bulk.shared::cluster.global.mbarrier::complete_tx::bytes [%0], [%1], %2, [%3];" ::"r"(dst), "l"(src), "r"(bytes), "r"(bar) : "memory");
}
DI void bulk_g2s_mc(uint32_t dst, const void* src, uint32_t bytes, uint32_t bar, uint16_t mask) {
  asm volatile("cp.async.bulk.shared::cluster.global.mbarrier::complete_tx::bytes.multicast::cluster [%0], [%1], %2, [%3], %4;" ::"r"(dst), "l"(src), "r"(bytes), "r"(bar), "h"(mask) : "memory");
}
DI void bulk_s2s(uint32_t dst, uint32_t src, uint32_t bytes, uint32_t bar) {
  asm volatile("cp.async.bulk.shared::cluster.shared::cta.mbarrier::complete_tx::bytes [%0], [%1], %2, [%3];" ::"r"(dst), "r"(src), "r"(bytes), "r"(bar) : "memory");
}
DI void tma_2d(uint32_t dst, const CUtensorMap* map, int c0, int c1, uint32_t bar) {
  asm volatile("cp.async.bulk.tensor.2d.shared::cluster.global.mbarrier::complete_tx::bytes [%0], [%1, {%3, %4}], [%2];" ::"r"(dst), "l"(map), "r"(bar), "r"(c0), "r"(c1) : "memory");
}
DI void tma_pf(const CUtensorMap* map, int c0, int c1) {
  asm volatile("cp.async.bulk.prefetch.tensor.2d.L2.global [%0, {%1, %2}];" ::"l"(map), "r"(c0), "r"(c1) : "memory");
}
DI void st_async4(uint32_t a, uint32_t x, uint32_t y, uint32_t z, uint32_t w, uint32_t bar) {
  asm volatile("st.async.shared::cluster.mbarrier::complete_tx::bytes.v4.b32 [%0], {%1,%2,%3,%4}, [%5];" ::"r"(a), "r"(x), "r"(y), "r"(z), "r"(w), "r"(bar) : "memory");
}
DI void st_async2(uint32_t a, uint32_t x, uint32_t y, uint32_t bar) {
  asm volatile("st.async.shared::cluster.mbarrier::complete_tx::bytes.v2.b32 [%0], {%1,%2}, [%3];" ::"r"(a), "r"(x), "r"(y), "r"(bar) : "memory");
}
DI void st_async1(uint32_t a, uint32_t x, uint32_t bar) {
  asm volatile("st.async.shared::cluster.mbarrier::complete_tx::bytes.b32 [%0], %1, [%2];" ::"r"(a), "r"(x), "r"(bar) : "memory");
}
DI void sts32(uint32_t a, uint32_t x) { asm volatile("st.shared.b32 [%0], %1;" ::"r"(a), "r"(x) : "memory"); }
DI void sts128(uint32_t a, uint4 v) { asm volatile("st.shared.v4.b32 [%0], {%1,%2,%3,%4};" ::"r"(a), "r"(v.x), "r"(v.y), "r"(v.z), "r"(v.w) : "memory"); }
DI uint32_t lds32(uint32_t a) { uint32_t v; asm volatile("ld.shared.b32 %0, [%1];" : "=r"(v) : "r"(a) : "memory"); return v; }
DI uint2 lds64(uint32_t a) { uint2 v; asm volatile("ld.shared.v2.b32 {%0,%1}, [%2];" : "=r"(v.x), "=r"(v.y) : "r"(a) : "memory"); return v; }
DI uint4 lds128(uint32_t a) { uint4 v; asm volatile("ld.shared.v4.b32 {%0,%1,%2,%3}, [%4];" : "=r"(v.x), "=r"(v.y), "=r"(v.z), "=r"(v.w) : "r"(a) : "memory"); return v; }
DI void stsm4(uint32_t a, uint32_t r0, uint32_t r1, uint32_t r2, uint32_t r3) {
  asm volatile("stmatrix.sync.aligned.m8n8.x4.shared.b16 [%0], {%1,%2,%3,%4};" ::"r"(a), "r"(r0), "r"(r1), "r"(r2), "r"(r3) : "memory");
}
DI void stsm2(uint32_t a, uint32_t r0, uint32_t r1) {
  asm volatile("stmatrix.sync.aligned.m8n8.x2.shared.b16 [%0], {%1,%2};" ::"r"(a), "r"(r0), "r"(r1) : "memory");
}
DI uint32_t movm(uint32_t a) { uint32_t d; asm volatile("movmatrix.sync.aligned.m8n8.trans.b16 %0, %1;" : "=r"(d) : "r"(a)); return d; }
DI uint32_t pack2(float lo, float hi) { uint32_t d; asm("cvt.rn.bf16x2.f32 %0, %1, %2;" : "=r"(d) : "f"(hi), "f"(lo)); return d; }
DI uint4 ld_rlx4(const void* p) {
  uint4 v;
  asm volatile("ld.relaxed.gpu.global.v4.u32 {%0,%1,%2,%3}, [%4];" : "=r"(v.x), "=r"(v.y), "=r"(v.z), "=r"(v.w) : "l"(p) : "memory");
  return v;
}
DI void st_rlx4(void* p, uint32_t x, uint32_t y, uint32_t z, uint32_t w) {
  asm volatile("st.relaxed.gpu.global.v4.u32 [%0], {%1,%2,%3,%4};" ::"l"(p), "r"(x), "r"(y), "r"(z), "r"(w) : "memory");
}
DI void st_rlx1(void* p, uint32_t x) { asm volatile("st.relaxed.gpu.global.u32 [%0], %1;" ::"l"(p), "r"(x) : "memory"); }
DI uint32_t ld_acq(const uint32_t* p) { uint32_t v; asm volatile("ld.acquire.gpu.global.u32 %0, [%1];" : "=r"(v) : "l"(p) : "memory"); return v; }
DI uint32_t ld_rlx(const uint32_t* p) { uint32_t v; asm volatile("ld.relaxed.gpu.global.u32 %0, [%1];" : "=r"(v) : "l"(p) : "memory"); return v; }
DI void red_rel(uint32_t* p, uint32_t v) { asm volatile("red.release.gpu.global.add.u32 [%0], %1;" ::"l"(p), "r"(v) : "memory"); }
DI void guard(uint32_t& g) { asm volatile("{.reg .pred p; add.u32 %0, %0, 1; setp.gt.u32 p, %0, 8000000; @p trap;}" : "+r"(g)); }
DI void poll_ge(const uint32_t* p, uint32_t target) {
  asm volatile(
      "{.reg .pred p; .reg .u32 v;\n"
      "LOOP:\n"
      "ld.acquire.gpu.global.u32 v, [%0];\n"
      "setp.lt.u32 p, v, %1;\n"
      "vote.sync.any.pred p, p, 0xffffffff;\n"
      "@p bra.uni LOOP;\n}" ::"l"(p), "r"(target) : "memory");
}
DI float ex2(float x) { float y; asm("ex2.approx.ftz.f32 %0, %1;" : "=f"(y) : "f"(x)); return y; }

DI void wg_fence() { asm volatile("wgmma.fence.sync.aligned;" ::: "memory"); }
DI void wg_commit() { asm volatile("wgmma.commit_group.sync.aligned;" ::: "memory"); }
template <int N> DI void wg_wait() { asm volatile("wgmma.wait_group.sync.aligned %0;" ::"n"(N) : "memory"); }
template <int N> DI void reg_fence(float* d) {
#pragma unroll
  for (int i = 0; i < N; i++) asm volatile("" : "+f"(d[i])::"memory");
}
__host__ __device__ constexpr uint64_t mkdesc(uint32_t addr, uint32_t lbo, uint32_t sbo, uint32_t sw) {
  return (uint64_t)((addr & 0x3FFFF) >> 4) | ((uint64_t)(lbo >> 4) << 16) | ((uint64_t)(sbo >> 4) << 32) | ((uint64_t)sw << 62);
}

#define ACC4(d, o) "+f"(d[o]), "+f"(d[o + 1]), "+f"(d[o + 2]), "+f"(d[o + 3])
#define ACC16(d, o) ACC4(d, o), ACC4(d, o + 4), ACC4(d, o + 8), ACC4(d, o + 12)
#define ACC20(d) ACC16(d, 0), ACC4(d, 16)

template <int TA, int TB> DI void wg_ss40(float* d, uint64_t da, uint64_t db, int sc) {
  asm volatile("{.reg .pred p; setp.ne.b32 p, %22, 0;\n"
               "wgmma.mma_async.sync.aligned.m64n40k16.f32.bf16.bf16 {%0,%1,%2,%3,%4,%5,%6,%7,%8,%9,%10,%11,%12,%13,%14,%15,%16,%17,%18,%19}, %20, %21, p, 1, 1, %23, %24;}"
               : ACC20(d) : "l"(da), "l"(db), "r"(sc), "n"(TA), "n"(TB));
}
DI void wg_rs40(float* d, uint32_t a0, uint32_t a1, uint32_t a2, uint32_t a3, uint64_t db, int sc) {
  asm volatile("{.reg .pred p; setp.ne.b32 p, %25, 0;\n"
               "wgmma.mma_async.sync.aligned.m64n40k16.f32.bf16.bf16 {%0,%1,%2,%3,%4,%5,%6,%7,%8,%9,%10,%11,%12,%13,%14,%15,%16,%17,%18,%19}, {%20,%21,%22,%23}, %24, p, 1, 1, 0;}"
               : ACC20(d) : "r"(a0), "r"(a1), "r"(a2), "r"(a3), "l"(db), "r"(sc));
}
DI void wg_rs32(float* d, uint32_t a0, uint32_t a1, uint32_t a2, uint32_t a3, uint64_t db, int sc) {
  asm volatile("{.reg .pred p; setp.ne.b32 p, %21, 0;\n"
               "wgmma.mma_async.sync.aligned.m64n32k16.f32.bf16.bf16 {%0,%1,%2,%3,%4,%5,%6,%7,%8,%9,%10,%11,%12,%13,%14,%15}, {%16,%17,%18,%19}, %20, p, 1, 1, 0;}"
               : ACC16(d, 0) : "r"(a0), "r"(a1), "r"(a2), "r"(a3), "l"(db), "r"(sc));
}
DI void wg_rs8(float* d, uint32_t a0, uint32_t a1, uint32_t a2, uint32_t a3, uint64_t db, int sc) {
  asm volatile("{.reg .pred p; setp.ne.b32 p, %9, 0;\n"
               "wgmma.mma_async.sync.aligned.m64n8k16.f32.bf16.bf16 {%0,%1,%2,%3}, {%4,%5,%6,%7}, %8, p, 1, 1, 0;}"
               : ACC4(d, 0) : "r"(a0), "r"(a1), "r"(a2), "r"(a3), "l"(db), "r"(sc));
}
DI void mma16816(float* c, const uint32_t* a, uint32_t b0, uint32_t b1) {
  asm volatile("mma.sync.aligned.m16n8k16.row.col.f32.bf16.bf16.f32 {%0,%1,%2,%3}, {%4,%5,%6,%7}, {%8,%9}, {%0,%1,%2,%3};"
               : ACC4(c, 0) : "r"(a[0]), "r"(a[1]), "r"(a[2]), "r"(a[3]), "r"(b0), "r"(b1));
}
DI void wg_ss8(float* d, uint64_t da, uint64_t db, int sc) {
  asm volatile("{.reg .pred p; setp.ne.b32 p, %6, 0;\n"
               "wgmma.mma_async.sync.aligned.m64n8k16.f32.bf16.bf16 {%0,%1,%2,%3}, %4, %5, p, 1, 1, 1, 1;}"
               : ACC4(d, 0) : "l"(da), "l"(db), "r"(sc));
}
DI void wg_rs16(float* d, uint32_t a0, uint32_t a1, uint32_t a2, uint32_t a3, uint64_t db, int sc) {
  asm volatile("{.reg .pred p; setp.ne.b32 p, %13, 0;\n"
               "wgmma.mma_async.sync.aligned.m64n16k16.f32.bf16.bf16 {%0,%1,%2,%3,%4,%5,%6,%7}, {%8,%9,%10,%11}, %12, p, 1, 1, 0;}"
               : ACC4(d, 0), ACC4(d, 4) : "r"(a0), "r"(a1), "r"(a2), "r"(a3), "l"(db), "r"(sc));
}
__device__ uint4 g_xn[2 * NSEG * 10 * 256];
__device__ uint4 g_oT[2 * NBLK * 96 * 1024];
constexpr int PART_RING = 96 * 256;
__device__ uint4 g_part[4 * PART_RING];
constexpr int MEM_OFF = 192;
#define P4 ~0u, ~0u, ~0u, ~0u
#define P16 P4, P4, P4, P4
#define P256 P16, P16, P16, P16, P16, P16, P16, P16, P16, P16, P16, P16, P16, P16, P16, P16
#define P2K P256, P256, P256, P256, P256, P256, P256, P256
#define P8K P2K, P2K, P2K, P2K
__device__ __align__(8192) uint32_t g_mem32[5 * 2 * 2 * 2048] = {P8K, P8K, P8K, P8K, P8K};
#define g_mem ((uint4*)g_mem32)
constexpr int C_XN = 0;
constexpr int C_O = C_XN + 2 * NBLK;
constexpr int C_HALF = C_O + 6 * 2 * NBLK;
constexpr int C_TOTAL = 512;
constexpr int CSTRIDE = 32;
__device__ uint32_t g_cnt[C_TOTAL * CSTRIDE];
constexpr uint32_t XN_TARGET = 128;

#define TRACE(c, n, i, v)
#define SLOG(i)
#define PROF(i)
#define PROFA(c)
#define PROFV(i, v)

constexpr uint32_t SMEM0 = 1024;
constexpr uint32_t SM_WK = 0, SM_WO = 81920, SM_H = 163840, SM_QT = 215040, QSTR = 1056  , SM_KT = SM_QT + 5 * QSTR + 1024,
                   SM_SR = SM_KT + 5120  , SM_PROF = SM_SR + 5760, R_SMEM = 232448,
                   SM_RED = SM_QT + 1024, SM_BAR = SM_RED + 768;
constexpr uint32_t SM_P = SM_KT, SM_OB = SM_QT + 3200;
constexpr uint32_t B_HFULL = SM_BAR, B_HEMPTY = SM_BAR + 40, B_MTRY = SM_BAR + 80, B_W = SM_BAR + 112, B_SR = B_W + 32,
                   B_PMEM = B_SR + 24, B_PTOK = B_SR + 32, B_OB = B_SR + 40, B_OPD = B_SR + 48, B_RFREE = B_SR + 56,
                   B_GATE = B_SR + 64, B_PSUM = B_SR + 72, B_END = B_SR + 80, B_PVI = B_SR + 88,
                   B_OPI = B_SR + 96, B_OTOK = B_SR + 112, SM_TOPI = B_SR + 128, B_PACE = SM_TOPI + 8,
                   SM_RS = SM_QT + 2 * QSTR + 1024;
static_assert(B_PACE + 32 <= SM_QT + 2 * QSTR, "barriers must fit the unused q row group");

struct RParams {
  uint64_t dH, dHt, dWK, dWO, dQT, dKT, dP, dOB[6];
  const char* w[4];
  const uint4* mem0;
  const uint32_t* x;
  int pf;
  int nslots, d3, pn, moff, ds, dh, dq;
  int d2[10], d1[8];
  uint32_t slot[2 * NSEG];
};
static void r_fill_desc(RParams& p) {
  p.dH = mkdesc(SMEM0 + SM_H, 128, 2048, 0);
  p.dHt = mkdesc(SMEM0 + SM_H + 2048, 128, 2048, 0);
  p.dWK = mkdesc(SMEM0 + SM_WK, 1024, 1024, 1);
  p.dWO = mkdesc(SMEM0 + SM_WO, 1024, 1024, 1);
  for (int i = 0; i < 6; i++) p.dOB[i] = mkdesc(SMEM0 + SM_OB + (i < 3 ? 0 : (i - 3) * 1024), 128, 128, 0);
  p.dQT = mkdesc(SMEM0 + SM_QT, 128, QSTR, 0);
  p.dKT = mkdesc(SMEM0 + SM_KT, 128, 1024, 0);
  p.dP = mkdesc(SMEM0 + SM_P, 128, 640, 0);
}
DI uint64_t dadd(uint64_t d, int bytes) {
  uint64_t r;
  asm volatile("add.u64 %0, %1, %2;" : "=l"(r) : "l"(d), "l"((long long)(bytes / 16)));
  return r;
}
template <int BYTES> DI void dstep(uint64_t& d) { asm volatile("add.u64 %0, %0, %1;" : "+l"(d) : "n"((long long)(BYTES / 16))); }
__host__ __device__ constexpr int hoff(int ks) { return (ks >> 3) * 10240 + (ks & 7) * 256; }

DI int opaque(int v) { asm volatile("" : "+r"(v)); return v; }
DI uint32_t pin(uint32_t v, int lane) { return __shfl_sync(~0u, v + (lane >> 5), lane); }
DI char* pin(char* p, int lane) { return (char*)__shfl_sync(~0u, (unsigned long long)p, lane); }
DI float blo(uint32_t w) { return __uint_as_float(w << 16); }
DI float bhi(uint32_t w) { return __uint_as_float(w & 0xffff0000u); }
#define R_FB 1
#define PIN_DST 1
#define RG0 232
#define RG1 216
#define RG2 40
#define RG3 24
DI void ldsm4t(uint32_t* r, uint32_t a) {
  asm volatile("ldmatrix.sync.aligned.m8n8.x4.trans.shared.b16 {%0,%1,%2,%3}, [%4];" : "=r"(r[0]), "=r"(r[1]), "=r"(r[2]), "=r"(r[3]) : "r"(a) : "memory");
}
DI void st_tagged(void* p, float a, float b, uint32_t keep, uint32_t tagbit) {
  asm volatile("{.reg .b32 t; cvt.rn.bf16x2.f32 t, %2, %1; lop3.b32 t, t, %3, %4, 0xea; st.relaxed.gpu.global.b32 [%0], t;}" ::"l"(p), "f"(a), "f"(b),
               "r"(keep), "r"(tagbit) : "memory");
}
DI uint32_t lop_bad(uint32_t a, uint32_t b, uint32_t m) { uint32_t d; asm("lop3.b32 %0, %1, %2, %3, 0x7e;" : "=r"(d) : "r"(a), "r"(b), "r"(m)); return d; }
DI uint32_t lop_or3(uint32_t a, uint32_t b, uint32_t c) { uint32_t d; asm("lop3.b32 %0, %1, %2, %3, 0xfe;" : "=r"(d) : "r"(a), "r"(b), "r"(c)); return d; }
DI uint32_t clk() { uint32_t t; asm volatile("mov.u32 %0, %%clock;" : "=r"(t)); return t; }
DI void spin(uint32_t cyc) { const uint32_t t0 = clk(); while (__any_sync(~0u, clk() - t0 < cyc)) {} }
template <int NL> DI float2 poll_sum(const uint32_t* src, uint32_t tag, uint32_t even, uint32_t& g) {
  uint32_t r[NL];
  while (true) {
#pragma unroll
    for (int i = 0; i < NL; i++) r[i] = ld_rlx(src + i * 32);
    uint32_t bad = lop_or3(lop_bad(r[0], r[1], tag), lop_bad(r[2], r[3], tag), lop_bad(r[4], r[5], tag));
    if (NL == 12) bad = lop_or3(bad, lop_bad(r[6], r[7], tag), lop_bad(r[8], r[9], tag));
    asm volatile("lop3.b32 %0, %0, %1, %2, 0xa8;" : "+r"(bad) : "r"(lop_bad(r[NL - 2], r[NL - 1], tag)), "r"(even));
    if (!__any_sync(~0u, bad)) break;
    g++;
  }
  float x[NL / 2], y[NL / 2];
#pragma unroll
  for (int i = 0; i < NL / 2; i++) { x[i] = blo(r[2 * i]) + blo(r[2 * i + 1]); y[i] = bhi(r[2 * i]) + bhi(r[2 * i + 1]); }
  float2 u = make_float2((x[0] + x[1]) + (x[2] + x[3]), (y[0] + y[1]) + (y[2] + y[3]));
  if (NL == 12) { u.x += x[4] + x[5]; u.y += y[4] + y[5]; }
  return u;
}

constexpr int PLANE = 16 * 40 * 32, MAXPL = 13;
__device__ uint2 g_acc[(size_t)2 * NBLK * 2 * MAXPL * PLANE];
DI uint2* acc_planes(int lb, int d) { return g_acc + (size_t)((lb * 2 + d) * MAXPL) * PLANE; }
DI void ln_stats(const float4* v, uint32_t red, int warp, int lane, int bar, float& mean, float& rstd) {
  float s = 0.f;
#pragma unroll
  for (int i = 0; i < 5; i++) s += (v[i].x + v[i].y) + (v[i].z + v[i].w);
  s += __shfl_xor_sync(~0u, s, 1);
  s += __shfl_xor_sync(~0u, s, 2);
  s *= 1.f / 80;
  float q = 0.f;
#pragma unroll
  for (int i = 0; i < 5; i++) q += ((v[i].x - s) * (v[i].x - s) + (v[i].y - s) * (v[i].y - s)) + ((v[i].z - s) * (v[i].z - s) + (v[i].w - s) * (v[i].w - s));
  q += __shfl_xor_sync(~0u, q, 1);
  q += __shfl_xor_sync(~0u, q, 2);
  if ((lane & 3) == 0) asm volatile("st.shared.v2.f32 [%0], {%1,%2};" ::"r"(red + lane * 16 + warp * 8), "f"(s), "f"(q) : "memory");
  bar_sync(bar, 256);
  const uint4 t = lds128(red + lane * 16);
  const float m0 = __uint_as_float(t.x), m1 = __uint_as_float(t.z);
  mean = m0 + m1;
  mean += __shfl_xor_sync(~0u, mean, 1);
  mean += __shfl_xor_sync(~0u, mean, 2);
  mean *= 0.125f;
  q = __uint_as_float(t.y) + __uint_as_float(t.w) + 80.f * ((m0 - mean) * (m0 - mean) + (m1 - mean) * (m1 - mean));
  q += __shfl_xor_sync(~0u, q, 1);
  q += __shfl_xor_sync(~0u, q, 2);
  rstd = rsqrtf(q * (1.f / DM) + 1e-5f);
}
template <int SH, int STR> DI void store_img(uint32_t* dst, const float4* v, int warp, float mean, float rstd) {
#pragma unroll
  for (int i = 0; i < 5; i++) {
    const int U = 10 * warp + 2 * i;
    uint32_t* p = dst + (U >> SH) * STR + (U & ((1 << SH) - 1)) * 32;
    p[0] = pack2((v[i].x - mean) * rstd, (v[i].y - mean) * rstd);
    p[32] = pack2((v[i].z - mean) * rstd, (v[i].w - mean) * rstd);
  }
}
DI uint32_t* xn_row_group(int layer, int rg) { return (uint32_t*)(g_xn + (size_t)((layer * NSEG + (rg >> 2)) * 2560 + (rg & 3) * 128)); }

DI void first_ln(const uint32_t* a, int rg, uint32_t red, int warp, int lane, int bar) {
  float4 v[5];
#pragma unroll
  for (int i = 0; i < 5; i++) {
    v[i] = make_float4(blo(a[2 * i]), bhi(a[2 * i]), blo(a[2 * i + 1]), bhi(a[2 * i + 1]));
    acc_planes(rg >> 4, 0)[((rg & 15) * 40 + warp * 5 + i) * 32 + lane] = make_uint2(a[2 * i], a[2 * i + 1]);
  }
  float mean, rstd;
  ln_stats(v, red, warp, lane, bar, mean, rstd);
  store_img<4, 2048>(xn_row_group(0, rg) + lane, v, warp, mean, rstd);
}
#define SOLO 1
#define QK_P0 32
#define QK_KB 0
struct QKOrder { int op[76]; };
__host__ __device__ constexpr QKOrder qk_order() {
  QKOrder o = {};
  int n = 0, k = 0, q = 0;
  for (; k < QK_P0; k++, q++) { o.op[n++] = 64 | k; o.op[n++] = q; }
  for (int i = 0; i < QK_KB; i++) o.op[n++] = 64 | k++;
  for (int i = 0; i < -QK_KB; i++) o.op[n++] = q++;
  const int nk = 40 - k, nq = 36 - q;
  for (int i = 0, dk = 0, dq = 0; i < nk + nq; i++) {
    if (dq * nk <= dk * nq + (QK_KB ? 0 : -nq) && dq < nq) { o.op[n++] = q++; dq++; } else if (dk < nk) { o.op[n++] = 64 | k++; dk++; } else { o.op[n++] = q++; dq++; }
  }
  return o;
}
__global__ void __launch_bounds__(512, 1)
r_kernel(const __grid_constant__ CUtensorMap mapWq, const __grid_constant__ CUtensorMap mapWk, const __grid_constant__ CUtensorMap mapWv,
         const __grid_constant__ CUtensorMap mapWo, const __grid_constant__ RParams prm) {
  const uint32_t sb = smem_base();
  const int wid = __shfl_sync(~0u, threadIdx.x >> 5, 0);
  const int lane0 = __shfl_sync(~0u, threadIdx.x & 31, threadIdx.x & 31);
  const int lane = lane0;
  const int warp = wid & 3, wg = wid >> 2;
  const uint32_t rank = blockIdx.x, head = blockIdx.y, cta = head * 3 + rank;
  const uint32_t peer1 = mapa(sb, rank == 2 ? 0 : rank + 1), peer2 = mapa(sb, rank == 0 ? 2 : rank - 1);
  const int nslots = prm.nslots;

  SLOG(0);
  if (threadIdx.x == 384) {
    if ((sb & 0x3FFFF) != SMEM0) __trap();
    for (int c = 0; c < 5; c++) { mbar_init(sb + B_HFULL + 8 * c, 2); mbar_init(sb + B_HEMPTY + 8 * c, c == 4 ? 8 : 4); }
    for (int c = 0; c < 11; c++) mbar_init(sb + B_MTRY + 8 * c, 1);
    mbar_init(sb + B_PTOK, rank == 0 ? 3 : 2); mbar_init(sb + B_OB, 5); mbar_init(sb + B_OPD, 4);
    mbar_init(sb + B_OPI, 1); mbar_init(sb + B_OPI + 8, 1); mbar_init(sb + B_RFREE, 1); mbar_init(sb + B_GATE, 1); mbar_init(sb + B_PMEM, 2); mbar_init(sb + B_PSUM, 2); mbar_init(sb + B_PVI, 5); mbar_init(sb + B_OTOK, 4); mbar_init(sb + B_OTOK + 8, 4); mbar_init(sb + B_END, 15);
    for (int c = 0; c < 4; c++) mbar_init(sb + B_PACE + 8 * c, 1);
    asm volatile("fence.mbarrier_init.release.cluster;" ::: "memory");
    fence_async_smem();
  }
  asm volatile("griddepcontrol.launch_dependents;");
  asm volatile("barrier.cluster.arrive.release.aligned;" ::: "memory");

  if (wg < 2) {
  {
    uint32_t xa[10];
    const uint32_t* src = prm.x + (size_t)(cta * 8 + (lane >> 2)) * (DM / 2) + wid * 40 + (lane & 3);
#pragma unroll
    for (int i = 0; i < 10; i++) xa[i] = __ldg(src + i * 4);
    asm volatile("barrier.cluster.wait.acquire.aligned;" ::: "memory");
    first_ln(xa, cta, sb + SM_SR, wid, lane, 8);
    bar_arrive(10, 288);
  }
  if (wg == 0) {
    asm volatile("setmaxnreg.inc.sync.aligned.u32 %0;" ::"n"(RG0));
    uint32_t wq[160];
    SLOG(1);
    mbar_wait(sb + B_W, 0);
    SLOG(2);
    {
      const uint32_t ld_off = ((lane >> 4) * 8 + (lane & 7)) * 128 + (((2 * warp + ((lane >> 3) & 1)) ^ (lane & 7)) << 4);
#pragma unroll
      for (int ks = 0; ks < 40; ks++) ldsm4t(wq + 4 * ks, sb + SM_WO + ks * 2048 + ld_off);
    }
    fence_async_smem();
    bar_arrive(5, 160);
    mbar_wait(sb + B_W + 16, 0);
    SLOG(3);
    const uint32_t st_addr = pin(sb + SM_QT + (lane >> 4) * 1024 + (2 * warp + ((lane >> 3) & 1)) * 128 + (lane & 7) * 16, lane);
    const uint32_t sq_addr = pin(sb + SM_QT + (2 + (lane & 3)) * QSTR + warp * 256 + (lane >> 2) * 16, lane);
    const uint32_t to_lo = warp == 0 ? peer1 : mapa(sb, warp == 2 ? 2 : 0), to_hi = warp == 0 ? peer2 : mapa(sb, warp == 1 ? 1 : 0);
    const uint32_t sr_off = SM_SR + warp * 1920 + rank * 640, sr_bar = B_SR + warp * 8;
    const uint32_t sa0 = pin(to_lo + sr_off + lane * 16, lane), sb0 = pin(to_lo + sr_bar, lane), sa1 = pin(to_lo + sr_off + 512 + lane * 4, lane), sb1 = pin(sb0, lane);
    const uint32_t sa2 = pin(to_hi + sr_off + lane * 16, lane), sb2 = pin(to_hi + sr_bar, lane), sa3 = pin(to_hi + sr_off + 512 + lane * 4, lane), sb3 = pin(sb2, lane);
    uint32_t nsolo = 0;
#pragma unroll 1
    for (int n = 0; n < nslots; n++) {
      const uint32_t par = n & 1;
      PROFA(warp == PW);
      const bool alt = prm.slot[n] & 128;
      auto next = [&](uint64_t& d, int ks) { if ((ks & 7) == 7) dstep<10240 - 7 * 256>(d); else dstep<256>(d); };
      auto store_k = [&](const float* ka) {
        stsm2(st_addr + (SM_KT - SM_QT), pack2(ka[0], ka[1]), pack2(ka[2], ka[3]));
        stsm4(st_addr + (SM_KT - SM_QT) + 1024, pack2(ka[4], ka[5]), pack2(ka[6], ka[7]), pack2(ka[8], ka[9]), pack2(ka[10], ka[11]));
        stsm4(st_addr + (SM_KT - SM_QT) + 3072, pack2(ka[12], ka[13]), pack2(ka[14], ka[15]), pack2(ka[16], ka[17]), pack2(ka[18], ka[19]));
      };
      auto store_qt = [&](const float* q) {
        sts128(sq_addr, make_uint4(pack2(q[0], q[1]), pack2(q[4], q[5]), pack2(q[8], q[9]), pack2(q[12], q[13])));
        sts128(sq_addr + 128, make_uint4(pack2(q[2], q[3]), pack2(q[6], q[7]), pack2(q[10], q[11]), pack2(q[14], q[15])));
      };
      if (SOLO && n > 0 && ((prm.slot[n] >> 8) & 255) == n) {
        {
          float qt[16];
          uint64_t rh = prm.dHt;
          mbar_wait(sb + B_OPD, par ^ 1);
          spin(prm.dq);
          mbar_wait(sb + B_PVI, nsolo++ & 1);
          wg_fence();
#pragma unroll
          for (int ks = 0; ks < 40; ks++) { wg_rs32(qt, wq[4 * ks], wq[4 * ks + 1], wq[4 * ks + 2], wq[4 * ks + 3], rh, ks != 0); if (ks < 39) next(rh, ks); }
          wg_commit();
          wg_wait<0>();
          reg_fence<16>(qt);
          store_qt(qt);
        }
        float qm[4], ka[20];
        uint64_t rk = prm.dWK, rh = prm.dH, rq;
        bool ok = false;
#pragma unroll
        for (int g = 0; g < 18; g++) {
          if ((g & 3) == 0 && !ok) mbar_wait(sb + B_HFULL + 2 * g, par);
          if (g == 0) PROF(0);
          if ((g & 3) == 3) ok = mbar_test(sb + B_HFULL + 2 * (g + 1), par);
          if ((g & 3) == 0) wg_fence();
#pragma unroll
          for (int ks = 2 * g; ks < 2 * g + 2; ks++) {
            wg_ss40<1, 0>(ka, rk, rh, ks != 0);
            wg_rs8(qm, wq[4 * ks], wq[4 * ks + 1], wq[4 * ks + 2], wq[4 * ks + 3], rh, ks != 0);
            dstep<2048>(rk); next(rh, ks);
          }
        }
        wg_commit();
        rq = rh;
#pragma unroll
        for (int ks = 36; ks < 40; ks++) { wg_ss40<1, 0>(ka, rk, rh, 1); if (ks < 39) { dstep<2048>(rk); dstep<256>(rh); } }
        wg_commit();
#pragma unroll
        for (int ks = 36; ks < 40; ks++) { wg_rs8(qm, wq[4 * ks], wq[4 * ks + 1], wq[4 * ks + 2], wq[4 * ks + 3], rq, 1); if (ks < 39) dstep<256>(rq); }
        wg_commit();
        wg_wait<2>();
        if (alt) bar_arrive(2, 256);
        wg_wait<1>();
        if (!alt) bar_arrive(2, 256);
        reg_fence<20>(ka);
        store_k(ka);
        wg_wait<0>();
        reg_fence<4>(qm);
        PROF(9);
        stsm2(st_addr, pack2(qm[0], qm[1]), pack2(qm[2], qm[3]));
      } else {
      float qa[20], ka[20];
      uint64_t rk = prm.dWK, rh = prm.dH, rq;
      auto K = [&](int ks) { wg_ss40<1, 0>(ka, rk, rh, ks != 0); };
      auto Q = [&](int ks, uint64_t db) { wg_rs40(qa, wq[4 * ks], wq[4 * ks + 1], wq[4 * ks + 2], wq[4 * ks + 3], db, ks != 0); };
      constexpr QKOrder ord = qk_order();
      auto first = [&](int g, int c) { for (int i = 0; i < 76; i++) if ((ord.op[i] & 63) >> 3 == c) return i >> 2 == g; return false; };
      bool ok = true;
      mbar_wait(sb + B_HFULL, par);
#pragma unroll
      for (int g = 0; g < 19; g++) {
        if (!ok) {
#pragma unroll
          for (int c = 1; c < 5; c++) if (first(g, c)) mbar_wait(sb + B_HFULL + 8 * c, par);
          mbar_wait(sb + B_GATE, 1);
        }
        if (g == 0) PROF(0);
        if (g < 18) ok = mbar_test(sb + B_GATE, 1);
#pragma unroll
        for (int c = 1; c < 5; c++) if (first(g + 1, c)) ok &= mbar_test(sb + B_HFULL + 8 * c, par);
        wg_fence();
#pragma unroll
        for (int i = 4 * g; i < 4 * g + 4; i++) {
          const int ks = ord.op[i] & 63;
          if (i < 2 * QK_P0) {
            if (ord.op[i] & 64) K(ks);
            else { Q(ks, rh); dstep<2048>(rk); next(rh, ks); if (i == 2 * QK_P0 - 1) rq = rh; }
          } else if (ord.op[i] & 64) { K(ks); if (ks < 39) { dstep<2048>(rk); next(rh, ks); } }
          else { Q(ks, rq); next(rq, ks); }
        }
        if (g == 17) wg_commit();
      }
      wg_commit();
#pragma unroll
      for (int ks = 36; ks < 40; ks++) { Q(ks, rq); if (ks < 39) dstep<256>(rq); }
      wg_commit();
      wg_wait<2>();
      if (alt) bar_arrive(2, 256);
      mbar_wait(sb + B_OPD, par ^ 1);
      wg_wait<1>();
      if (!alt) bar_arrive(2, 256);
      reg_fence<20>(ka);
      store_k(ka);
      wg_wait<0>();
      reg_fence<20>(qa);
      PROF(9);
      stsm2(st_addr, pack2(qa[0], qa[1]), pack2(qa[2], qa[3]));
      store_qt(qa + 4);
      }
      mbar_arrive_if(lane == 0, sb + B_HEMPTY + 32);
      fence_async_smem();
      bar_sync(1, 128);
      PROF(1);
      float qa[20];
      wg_fence();
#pragma unroll
      for (int k = 0; k < 4; k++) wg_ss40<1, 1>(qa, dadd(prm.dQT, k * 256), dadd(prm.dKT, k * 256), k != 0);
      wg_commit();
      bar_arrive(7, 256);
      wg_wait<0>();
      reg_fence<20>(qa);
      PROF(3);
      if (warp < 3) {
        uint32_t p[5];
#pragma unroll
        for (int j = 0; j < 5; j++) p[j] = pack2(qa[4 * j], qa[4 * j + 1]);
        if (warp == 0) {
          st_async4(sa0, p[0], p[1], p[2], p[3], sb0);
          st_async4(sa2, p[0], p[1], p[2], p[3], sb2);
          st_async1(sa1, p[4], sb1);
          st_async1(sa3, p[4], sb3);
          sts128(sb + sr_off + lane * 16, make_uint4(p[0], p[1], p[2], p[3]));
          sts32(sb + sr_off + 512 + lane * 4, p[4]);
          __syncwarp();
          mbar_expect_if(lane == 0, sb + B_SR, 1280);
        } else {
          uint32_t h[5];
#pragma unroll
          for (int j = 0; j < 5; j++) h[j] = pack2(qa[4 * j + 2], qa[4 * j + 3]);
          spin(prm.d3);
          st_async4(sa0, p[0], p[1], p[2], p[3], sb0);
          st_async4(sa2, h[0], h[1], h[2], h[3], sb2);
          st_async1(sa1, p[4], sb1);
          st_async1(sa3, h[4], sb3);
        }
      }
    }
  } else {
    asm volatile("setmaxnreg.inc.sync.aligned.u32 %0;" ::"n"(RG1));
    uint32_t wv[160];
    mbar_wait(sb + B_W + 8, 0);
    SLOG(4);
    {
      const uint32_t ld_off = ((lane >> 4) * 8 + (lane & 7)) * 128 + (((2 * warp + ((lane >> 3) & 1)) ^ (lane & 7)) << 4);
#pragma unroll
      for (int ks = 0; ks < 40; ks++) ldsm4t(wv + 4 * ks, sb + SM_WO + ks * 2048 + ld_off);
    }
    fence_async_smem();
    bar_arrive(6, 160);
    const uint64_t dH = prm.dH;
    uint32_t op[8];
    const uint32_t ob_off = SM_OB + (4 * rank + warp) * 256 + lane * 4;
    const uint32_t oa0 = pin(peer1 + ob_off, lane), ob0 = pin(peer1 + B_OB, lane), oa1 = pin(peer2 + ob_off, lane), ob1 = pin(peer2 + B_OB, lane);
    const uint32_t oa2 = pin(oa0 + 128, lane), ob2 = pin(ob0, lane), oa3 = pin(oa1 + 128, lane), ob3 = pin(ob1, lane);
    const uint32_t o_loc = pin(sb + ob_off, lane), rs_addr = pin(sb + SM_RS + (lane & 3) * 8, lane);
    const uint32_t tok_off = pin((cta * 1024 + 64 * warp + (lane ^ (lane >> 3))) * 16, lane), keep = pin((lane & 1) ? ~0u : ~1u, lane);
    const uint32_t pb_off = pin((8 * rank + 2 * warp) * 4096 + head * 128 + lane * 4, lane);
    const uint32_t ph_off = pin(72 * 4096 + 2 * warp * 12288 + cta * 64 + (lane & 2) * 3072 + (lane >> 2) * 8 + (lane & 1) * 4, lane);
    auto store_tok = [&](int m, int lane) {
      const uint32_t ls = prm.slot[m] & 127, sig = prm.slot[m] >> 16;
      uint4* dst = (uint4*)((char*)(g_oT + (size_t)((ls >> 2) * (96 * 1024) + (ls & 3) * 256)) + tok_off);
      dst[0] = make_uint4(op[0], op[1], op[2], op[3]);
      dst[32] = make_uint4(op[4], op[5], op[6], op[7]);
      __syncwarp();
      mbar_arrive_if(sig && lane == 0, sb + B_OTOK + (ls >> 6) * 8);
    };
#pragma unroll 1
    for (int n = 0; n < nslots; n++) {
      const uint32_t par = n & 1;
      const int lane = opaque(lane0);
      PROFA(warp == PW);
      float va[20];
      const bool alt = prm.slot[n] & 128;
      mbar_expect_if(warp == 0 && lane == 0, sb + B_PTOK, rank == 0 ? 1280 : 1920);
      bar_sync(2, 256);
#pragma unroll
      for (int g = 0; g < 10; g++) {
        wg_fence();
#pragma unroll
        for (int ks = 4 * g; ks < 4 * g + 4; ks++) { wg_rs40(va, wv[4 * ks], wv[4 * ks + 1], wv[4 * ks + 2], wv[4 * ks + 3], dadd(dH, hoff(ks)), ks != 0); }
        wg_commit();
        if (g >= 2 && !(g & 1)) {
          wg_wait<1>();
          if (lane == 0) mbar_arrive(sb + B_HEMPTY + 8 * (g / 2 - 1));
        }
        if (g == 1 ? !alt : g == 2 && alt) bar_sync(7, 256);
      }
      wg_wait<0>();
      reg_fence<20>(va);
      if (lane == 0) mbar_arrive(sb + B_HEMPTY + 32);
      PROF(10);
      uint32_t vf[10];
#pragma unroll
      for (int j = 0; j < 10; j++) {
        const int i = (j + 4) % 10;
        asm volatile("cvt.rn.bf16x2.f32 %0, %1, %2;" : "=r"(vf[i]) : "f"(va[2 * i + 1]), "f"(va[2 * i]));
        if (j == 5) mbar_wait(sb + B_W + 8, 0);
      }
      uint32_t z0, z1;
      asm volatile("shr.u32 %0, %2, 5; shr.u32 %1, %2, 6;" : "=r"(z0), "=r"(z1) : "r"(lane));
      const uint32_t info = prm.slot[n];
      const uint32_t tagbit = ~(info >> 1) & ~keep;
      char* const ring = (char*)(g_part + (size_t)((((info >> 5) & 2) + (info & 1)) * PART_RING));
      char* const pb = pin(ring + pb_off, lane);
      char* const ph = ring + ph_off;
      mbar_wait(sb + B_PMEM, par);
      float om[4];
      wg_fence();
      wg_rs8(om, vf[0], vf[1], vf[2], vf[3], prm.dP, 0);
      wg_rs8(om, vf[4], vf[5], vf[6], vf[7], dadd(prm.dP, 256), 1);
      wg_rs8(om, vf[8], vf[9], z0, z1, dadd(prm.dP, 512 - (128 << 16)), 1);
      wg_commit();
      {
        wg_wait<0>();
        reg_fence<4>(om);
        const uint32_t b0 = pack2(om[0], om[1]), b1 = pack2(om[2], om[3]);
        st_async1(oa0, b0, ob0);
        st_async1(oa1, b0, ob1);
        st_async1(oa2, b1, ob2);
        st_async1(oa3, b1, ob3);
        sts32(o_loc, b0);
        sts32(o_loc + 128, b1);
        fence_async_smem();
        __syncwarp();
        mbar_arrive_if(lane == 0, sb + B_OB);
      }
      PROF(11);
      {
        float c[8];
        mbar_wait(sb + B_PSUM, par);
        const uint2 rs = lds64(rs_addr);
        const float r0 = __uint_as_float(rs.x), r1 = __uint_as_float(rs.y);
        if (n == 0) { SLOG(5); mbar_wait(sb + B_W + 24, 0); SLOG(6); }
        mbar_wait(sb + B_OB, par);
        asm volatile("fence.proxy.async::generic.acquire.sync_restrict::shared::cluster.cluster;" ::: "memory");
        PROF(16);
        if ((info & 63) == NSEG - 1) {
          mbar_wait(sb + B_OPI + par * 8, (n >> 1) & 1);
          mbar_arrive_if(warp == 3 && lane == 0, sb + B_GATE);
#pragma unroll
          for (int p = 0; p < 6; p++) st_rlx1(pb + (p >> 1) * 98304 + (p & 1) * 4096, tagbit);
          st_rlx1(ph, tagbit);
          st_rlx1(ph + 12288, tagbit);
        } else {
#pragma unroll
        for (int p = 0; p < 4; p++) {
          float* const cur = c + 4 * (p & 1);
          float* const prv = c + 4 * (~p & 1);
          if (p == 2) mbar_wait(sb + B_OPI + par * 8, (n >> 1) & 1);
          wg_fence();
#pragma unroll
          for (int ks = 0; ks < (p < 3 ? 12 : 4); ks++) {
            wg_ss8(cur, dadd(prm.dWO, p * 24576 + ks * 2048), dadd(prm.dOB[p < 3 ? p : 3 + rank], ks * 256), ks != 0);
            if (p == 3 && ks == 3) mbar_arrive_if(warp == 3 && lane == 0, sb + B_GATE);
            if (p > 0 && ks == 3) {
              wg_commit();
              wg_wait<1>();
              reg_fence<4>(prv);
              st_tagged(pb + (p - 1) * 98304, prv[0] * r0, prv[1] * r1, keep, tagbit);
              st_tagged(pb + (p - 1) * 98304 + 4096, prv[2] * r0, prv[3] * r1, keep, tagbit);
            }
          }
          if (p < 3) wg_commit();
        }
        wg_wait<0>();
        reg_fence<4>(c + 4);
        st_tagged(ph, c[4] * r0, c[5] * r1, keep, tagbit);
        st_tagged(ph + 12288, c[6] * r0, c[7] * r1, keep, tagbit);
        }
        PROF(17);
      }
      mbar_wait(sb + B_PTOK, par);
      PROF(12);
      {
        float ot[16];
        wg_fence();
        wg_rs32(ot, vf[0], vf[1], vf[2], vf[3], dadd(prm.dP, 640), 0);
        wg_rs32(ot, vf[4], vf[5], vf[6], vf[7], dadd(prm.dP, 640 + 256), 1);
        wg_rs32(ot, vf[8], vf[9], z0, z1, dadd(prm.dP, 640 + 512 - (128 << 16)), 1);
        wg_commit();
        wg_wait<0>();
        reg_fence<16>(ot);
#pragma unroll
        for (int i = 0; i < 8; i++) op[(i & 1) * 4 + (i >> 1)] = pack2(ot[2 * i], ot[2 * i + 1]);
      }
      if (lane == 0) mbar_arrive(sb + B_OPD);
      PROF(13);
      if (info & 128) spin(prm.ds);
      store_tok(n, lane);
    }
  }
  } else if (wg == 2) {
    asm volatile("setmaxnreg.dec.sync.aligned.u32 %0;" ::"n"(RG2));
    asm volatile("barrier.cluster.wait.acquire.aligned;" ::: "memory");
    if (warp == 1) {
      const uint32_t depth = prm.pf & 7;
#pragma unroll 1
      for (uint32_t i = 0; i < 20 + depth; i++) {
        if (i >= depth) {
          const uint32_t j = i - depth;
          mbar_wait_wd(sb + B_PACE + 8 * (j & 3), (j >> 2) & 1);
          if (j % 5 == 4) mbar_arrive_if(lane == 0 && (j != 14 || depth == 1), sb + B_W + (j == 4 ? 0 : j == 9 ? 16 : j == 14 ? 8 : 24));
        }
        if (i >= 20) continue;
        const uint32_t m = i / 5, k = i % 5, bar = sb + B_PACE + 8 * (i & 3);
        if (i == 10) bar_sync(5, 160);
        if (i == 15) {
          if ((prm.pf & 8) && elect_one())
            for (int q = 0; q < 4; q++) tma_pf(&mapWo, (q / 3 * 3 + rank) * 64, head * DH + q % 3 * 64);
#pragma unroll 1
          for (uint32_t j = 16 - depth; j < 15; j++) mbar_wait_wd(sb + B_PACE + 8 * (j & 3), (j >> 2) & 1);
          mbar_arrive_if(lane == 0 && depth > 1, sb + B_W + 8);
          bar_sync(6, 160);
        }
        if (elect_one()) {
          mbar_expect(bar, 16384);
          if (m < 3) tma_2d(sb + (m == 1 ? SM_WK : SM_WO) + k * 16384, m == 0 ? &mapWq : m == 1 ? &mapWk : &mapWv, cta * 64, k * 128, bar);
          else
            for (uint32_t q = 2 * k; q < 2 * k + 2; q++)
              tma_2d(sb + SM_WO + q * 8192, &mapWo, q < 9 ? (q / 3 * 3 + rank) * 64 : 576, head * DH + (q < 9 ? q % 3 : rank) * 64, bar);
        }
      }
    }
    if (warp == 2 && cta < 80 && lane < 16)
      g_mem[(cta >> 4) * 2048 + (lane >> 3) * 1024 + prm.moff + (cta & 15) * 8 + (lane & 7)] = prm.mem0[(lane & 7) * 80 + cta];
    if (warp == 3) {
      bar_sync(10, 288);
      if (lane == 0) red_rel(&g_cnt[(C_XN + (cta >> 4)) * CSTRIDE], 8);
    }
    const uint32_t grp = warp == 1 ? 1 + rank : 4 - (rank >> 1);
    constexpr float SC = 0.07216878364870322f * 1.4426950408889634f;
    const bool split = cta >= 72;
    const uint32_t wd = split ? 72 * 16 + cta * 16 : cta * 32;
    const uint32_t src_off = pin(split ? 72 * 4096 + (cta - 72) * 6144 + warp * 1536 + (lane & 2) * 32 + (lane >> 2) * 8 + (lane & 1) * 4 : cta * 4096 + warp * 1024 + lane * 4, lane);
    const uint32_t dst_off = pin(((wd >> 9) * 8192 + prm.moff * 4 + (wd & 511) + lane) * 4, lane);
    const uint32_t red = pin(sb + SM_RED + (warp < 2 ? 0 : (warp - 1) * 256) + lane * 8, lane);
    const uint32_t fl = (warp & 2) * 8 + (lane >> 3) * 4 + (lane & 3), hf = lane & 4;
    const uint32_t s0 = pin(sb + SM_SR + fl * 16 + hf * 2, lane), s1 = pin(sb + fl * 4, lane), pd = pin(s1 + hf * 64, lane);
    const uint32_t even = pin(~lane & 1, lane);
    uint32_t nred = 0;
    const uint32_t arm = pin(warp == 0 && (lane == 5 || ((lane == 1 || lane == 2) && lane + rank != 3)) ? sb + B_SR + lane * 8 : 0, lane);
#pragma unroll 1
    for (int n = 0; n < nslots; n++) {
      const uint32_t par = n & 1;
      const int lane = opaque(lane0);
      PROFA(warp == PW2);
      const uint32_t info = prm.slot[n], s = info & 63, l = (info >> 6) & 1;
      {
        mbar_expect_if(arm, arm, lane == 5 ? 2048 : 1920);
        if (warp == 0 || warp == 3) {
          mbar_wait(sb + B_SR, par);
          PROF(4);
          const uint2 a0 = lds64(s0), a1 = lds64(s0 + 640), a2 = lds64(s0 + 1280);
          const uint32_t b0 = lds32(s1 + SM_SR + 512), b1 = lds32(s1 + SM_SR + 1152), b2 = lds32(s1 + SM_SR + 1792);
          float v[6];
          v[0] = blo(a0.x) + blo(a1.x) + blo(a2.x); v[1] = bhi(a0.x) + bhi(a1.x) + bhi(a2.x);
          v[2] = blo(a0.y) + blo(a1.y) + blo(a2.y); v[3] = bhi(a0.y) + bhi(a1.y) + bhi(a2.y);
          v[4] = blo(b0) + blo(b1) + blo(b2); v[5] = bhi(b0) + bhi(b1) + bhi(b2);
          float m = fmaxf(fmaxf(v[0], v[1]), fmaxf(v[2], v[3]));
          m = fmaxf(fmaxf(m, __shfl_xor_sync(~0u, m, 4)), fmaxf(v[4], v[5]));
          {
            const float m1 = __shfl_xor_sync(~0u, m, 1), m2 = __shfl_xor_sync(~0u, m, 2), m3 = __shfl_xor_sync(~0u, m, 3);
            m = fmaxf(fmaxf(m, m1), fmaxf(m2, m3));
          }
          const float ms = -m * SC;
#pragma unroll
          for (int i = 0; i < 6; i++) v[i] = ex2(fmaf(v[i], SC, ms));
          float sum = (v[0] + v[1]) + (v[2] + v[3]);
          const float so = __shfl_xor_sync(~0u, sum, 4);
          sts32(pd + SM_P, pack2(v[0], v[1]));
          sts32(pd + SM_P + 128, pack2(v[2], v[3]));
          sts32(s1 + SM_P + 512, pack2(v[4], v[5]));
          fence_async_smem();
          __syncwarp();
          mbar_arrive_if(lane == 0, sb + B_PMEM);
          PROF(5);
          sum += so + (v[4] + v[5]);
          {
            const float t1 = __shfl_xor_sync(~0u, sum, 1), t2 = __shfl_xor_sync(~0u, sum, 2), t3 = __shfl_xor_sync(~0u, sum, 3);
            sum = (sum + t1) + (t2 + t3);
          }
          float r;
          asm("rcp.approx.ftz.f32 %0, %1;" : "=f"(r) : "f"(sum));
          sts32(sb + SM_RS + (warp & 2) * 8 + (lane >> 3) * 4, __float_as_uint(r));
          __syncwarp();
          mbar_arrive_if(lane == 0, sb + B_PSUM);
        } else {
          if (warp + rank != 3) {
            const uint32_t src = sb + SM_SR + warp * 1920;
            mbar_wait(sb + B_SR + warp * 8, par);
            const uint4 a0 = lds128(src + lane * 16), a1 = lds128(src + 640 + lane * 16), a2 = lds128(src + 1280 + lane * 16);
            const uint32_t b0 = lds32(src + 512 + lane * 4), b1 = lds32(src + 1152 + lane * 4), b2 = lds32(src + 1792 + lane * 4);
            float v[10];
            v[0] = blo(a0.x) + blo(a1.x) + blo(a2.x); v[1] = bhi(a0.x) + bhi(a1.x) + bhi(a2.x);
            v[2] = blo(a0.y) + blo(a1.y) + blo(a2.y); v[3] = bhi(a0.y) + bhi(a1.y) + bhi(a2.y);
            v[4] = blo(a0.z) + blo(a1.z) + blo(a2.z); v[5] = bhi(a0.z) + bhi(a1.z) + bhi(a2.z);
            v[6] = blo(a0.w) + blo(a1.w) + blo(a2.w); v[7] = bhi(a0.w) + bhi(a1.w) + bhi(a2.w);
            v[8] = blo(b0) + blo(b1) + blo(b2); v[9] = bhi(b0) + bhi(b1) + bhi(b2);
            {
              const int lim = 6 + 2 * grp + (lane & 24) + ((lane >> 2) & 1) - 2 * (lane & 3);
#pragma unroll
              for (int i = 2; i < 10; i++) if ((i >> 1) * 8 + (i & 1) > lim) v[i] = -INFINITY;
            }
            float m = fmaxf(fmaxf(fmaxf(v[0], v[1]), fmaxf(v[2], v[3])), fmaxf(fmaxf(v[4], v[5]), fmaxf(v[6], v[7])));
            m = fmaxf(m, fmaxf(v[8], v[9]));
            {
              const float m1 = __shfl_xor_sync(~0u, m, 1), m2 = __shfl_xor_sync(~0u, m, 2), m3 = __shfl_xor_sync(~0u, m, 3);
              m = fmaxf(fmaxf(m, m1), fmaxf(m2, m3));
            }
            const float ms = -m * SC;
#pragma unroll
            for (int i = 0; i < 10; i++) v[i] = ex2(fmaf(v[i], SC, ms));
            float sum = ((v[0] + v[1]) + (v[2] + v[3])) + ((v[4] + v[5]) + (v[6] + v[7])) + (v[8] + v[9]);
            {
              const float s1 = __shfl_xor_sync(~0u, sum, 1), s2 = __shfl_xor_sync(~0u, sum, 2), s3 = __shfl_xor_sync(~0u, sum, 3);
              sum = (sum + s1) + (s2 + s3);
            }
            float r;
            asm("rcp.approx.ftz.f32 %0, %1;" : "=f"(r) : "f"(sum));
            {
              const uint32_t row = SM_P + grp * 640;
#pragma unroll
              for (int j = 0; j < 5; j++) sts32(sb + row + j * 128 + lane * 4, pack2(v[2 * j] * r, v[2 * j + 1] * r));
              fence_async_smem();
              __syncwarp();
              mbar_arrive_if(lane == 0, sb + B_PTOK);
              if (elect_one()) {
                bulk_s2s(peer1 + row, sb + row, 640, peer1 + B_PTOK);
                bulk_s2s(peer2 + row, sb + row, 640, peer2 + B_PTOK);
              }
            }
          }
        }
      }
      const uint32_t* const src = (const uint32_t*)((char*)(g_part + (size_t)((l * 2 + (s & 1)) * PART_RING)) + src_off);
      uint32_t* const dst = (uint32_t*)pin((char*)(g_mem + l * 1024 + (~s & 1) * 512) + dst_off, lane);
      {
        const uint32_t d1 = prm.d1[cta / 24 + ((info >> 5) & 4)];
        if (warp == 3) {
          mbar_wait(sb + B_OB, par);
          mbar_arrive_if(lane == 0, sb + B_GATE);
          sts32(sb + SM_TOPI + par * 4, clk());
          __syncwarp();
          mbar_arrive_if(lane == 0, sb + B_OPI + par * 8);
          TRACE(true, n, 0, gtl());
        }
        const bool reduce = cta < 88 && s != NSEG - 1;
        if (reduce || warp == 0) mbar_wait(sb + B_OPI + par * 8, (n >> 1) & 1);
        if (!reduce) continue;
        mbar_wait(sb + B_RFREE, (nred++ & 1) ^ 1);
        mbar_wait(sb + B_GATE, 1);
        if (d1) spin(d1);
      }
      {
        uint32_t g = 0;
        float2 u;
        PROF(14);
        if (!split) {
          u = poll_sum<8>(src, ~(s >> 1), even, g);
        } else {
          u = poll_sum<12>(src, ~(s >> 1), even, g);
          u.x += __shfl_xor_sync(~0u, u.x, 2);
          u.y += __shfl_xor_sync(~0u, u.y, 2);
        }
        PROF(18);
        if (warp != 1) {
          asm volatile("st.shared.v2.f32 [%0], {%1,%2};" ::"r"(red), "f"(u.x), "f"(u.y) : "memory");
          bar_arrive(3, 128);
        } else {
          bar_sync(3, 128);
          const uint2 o0 = lds64(red), o1 = lds64(red + 256), o2 = lds64(red + 512);
          const uint32_t w = movm(pack2((u.x + __uint_as_float(o0.x)) + (__uint_as_float(o1.x) + __uint_as_float(o2.x)),
                                        (u.y + __uint_as_float(o0.y)) + (__uint_as_float(o1.y) + __uint_as_float(o2.y))));
          if (!split || lane < 16) {
            st_rlx1(dst, w);
            st_rlx1(dst + ((s & 1) ? 2048 : -2048), ~0u);
          }
          mbar_arrive_if(lane == 0, sb + B_RFREE);
        }
        PROF(19);
        PROFV(2, g);
        TRACE(warp == 1, n, 1, gtl());
        TRACE(g, n, 2, g);
      }
    }
  } else {
    asm volatile("setmaxnreg.dec.sync.aligned.u32 %0;" ::"n"(RG3));
    asm volatile("barrier.cluster.wait.acquire.aligned;" ::: "memory");
    const uint32_t chk = lane * 32 + ((lane >> 2) << 2);
    const uint32_t bar = sb + B_MTRY + 8 * warp;
    uint32_t mph = 0, waited = 0, pub = 0, pph = 0, nsolo = 0;
    auto publish = [&](uint32_t upto) {
#pragma unroll 1
      for (; pub < upto; pub++) {
        const uint32_t e = prm.slot[pub], l = (e >> 6) & 1;
        if (warp == 3 && (e >> 16)) {
          mbar_wait_wd(sb + B_OTOK + l * 8, (pph >> l) & 1);
          pph ^= 1 << l;
          if (elect_one()) red_rel(&g_cnt[(e >> 16) * CSTRIDE], 1);
        }
      }
    };
#pragma unroll 1
    for (int m = 0; m < nslots; m++) {
      const uint32_t info = prm.slot[m], prod = (info >> 8) & 255, ls = info & 127;
      uint32_t g = 0;
#pragma unroll 1
      for (; waited < prod && waited + 1 < m; waited++) mbar_wait_wd(sb + B_OPI + (waited & 1) * 8, (waited >> 1) & 1);
      uint32_t t0 = lds32(sb + SM_TOPI + (~waited & 1) * 4);
      publish(waited);
      if ((ls & 3) == 0) {
        while (__any_sync(~0u, ld_acq(&g_cnt[(C_XN + (ls >> 2)) * CSTRIDE]) < XN_TARGET)) guard(g);
        fence_async_global();
      }
#pragma unroll 1
      for (uint32_t c = warp; c < 5; c += 4) {
        const uint32_t dst = sb + SM_H + c * 10240, full = sb + B_HFULL + 8 * c;
        const uint4* src = g_mem + (c * 2048 + (ls >> 6) * 1024 + (ls & 1) * 512 + prm.moff);
        const uint32_t d = prod ? prm.d2[(m - prod) * 5 + c] : 0;
        const uint4* tok = g_xn + (size_t)(ls * 2560 + c * 512);
        const uint32_t pp = (m & 1) ^ 1;
        const bool single = waited < prod;
        mbar_wait_wd(full, pp);
        const bool solo = SOLO && m > 0 && prod == m;
        const uint32_t tokb = solo ? sb + B_PVI : full;
        if (solo && c < 4) mbar_wait_wd(tokb, (nsolo++ & 1) ^ 1);
        mbar_expect_if(lane < 2 && !(solo && c == 4 && lane == 0), lane ? bar : tokb, lane ? 2048 : 8192);
        if (!single) while (__any_sync(~0u, clk() - t0 < d)) {}
        if (c >= 2) mbar_wait_wd(sb + B_HEMPTY + 8 * c, pp);
        mbar_wait_wd(sb + (c < 2 ? B_HEMPTY + 8 * c : c == 2 && !single ? B_PMEM : B_OB), pp);
        if ((c != 2 || single) && !(solo && c == 4)) { if (elect_one()) bulk_g2s(dst + 2048, tok, 8192, tokb); }
        if (single) {
          mbar_wait_wd(sb + B_OPI + (waited & 1) * 8, (waited >> 1) & 1);
          waited++;
          t0 = lds32(sb + SM_TOPI + (~waited & 1) * 4);
          if (solo && c == 0 && elect_one()) {
            mbar_expect(tokb, 8192);
            bulk_g2s(dst + 4 * 10240 + 2048, tok + 2048, 8192, tokb);
          }
          publish(waited);
          while (__any_sync(~0u, clk() - t0 < d)) {}
        }
        else if (c < 2) spin(prm.dh);
        if (elect_one()) bulk_g2s(dst, src, 2048, bar);
        if (c == 2 && !single) {
          mbar_wait_wd(sb + B_OB, pp);
          if (elect_one()) bulk_g2s(dst + 2048, tok, 8192, full);
        }
        g = 0;
        while (true) {
          mbar_wait_wd(bar, mph);
          mph ^= 1;
          const uint32_t v0 = lds32(dst + chk), v1 = lds32(dst + chk + 1024);
          if (__all_sync(~0u, v0 != ~0u && v1 != ~0u)) break;
          if (elect_one()) {
            mbar_expect(bar, 2048);
            bulk_g2s(dst, src, 2048, bar);
          }
          guard(g);
        }
        mbar_arrive_if(lane == 0, full, solo ? 2 : 1);
        TRACE(c < 2, m, 3 + 2 * c, gtl());
        TRACE(c < 2, m, 4 + 2 * c, g);
      }
    }
    publish(nslots);
    if (warp == 0) mbar_wait_wd(sb + B_END, 0);
  }
  __syncwarp();
  if (wid != 12 && lane0 == 0) mbar_arrive(sb + B_END);
  cluster_sync();
}
__device__ uint32_t g_xa[NBLK * 10 * 4096];
__device__ uint32_t g_h[NBLK * 24 * 4096];

enum { T_A = 0, T_F1 = 1, T_U = 2, T_D = 3, T_F2 = 4, T_NONE = 7 };
__host__ __device__ constexpr int c_phase(int type, int lb) { return C_O + type * 32 + lb; }
constexpr int C_TICKET = c_phase(5, 0), C_EXIT = C_TICKET + 1, C_USED = C_HALF + 2 * NBLK;
constexpr int G_NST = 7;
constexpr uint32_t GS_RED = G_NST * 32768, GS_BAR = GS_RED + 1088, G_SMEM = GS_BAR + 224;
constexpr uint32_t GB_FULL = GS_BAR, GB_EMPTY = GS_BAR + 64, GB_ORD = GS_BAR + 128, GB_READY = GS_BAR + 144, GB_ACK = GS_BAR + 152, GB_GATE = GS_BAR + 160, GB_SIG = GS_BAR + 176, GB_SACK = GS_BAR + 192,
                   GS_SIG = GS_BAR + 208, GS_COL = GS_BAR + 216;
#define FPL 6
constexpr int NF = 16;
constexpr int G_EARLY = 36;
constexpr int G_LATE = 96, PL = 6, ML = 8, DL = 30, TL = 10;
constexpr int GRC = 112, GRP = 32;
constexpr uint32_t E_UP = 1u << 8, E_HALF = 1u << 28, E_GRP = 1u << 29, E_HAND = 1u << 30, E_EXCL = 1u << 31;

struct GParams {
  __nv_bfloat16* out;
  const uint32_t* x;
  int moff, gd;
  int pend;
  uint8_t perm[G_EARLY], first[9];
  uint8_t need[5][2 * NBLK];
  uint32_t tab[G_EARLY * (PL + ML + DL) + G_LATE * TL];
};
constexpr int EL = PL + ML + DL, TAB_TAIL = G_EARLY * EL;
struct GIter {
  int p, left, period;
  uint32_t e, type, lb, n0, kb0, nkb;
  bool gemm, valid;
  DI GIter(const GParams& prm, int col) {
    if (col < G_EARLY) { p = col * EL; left = PL; period = 0; }
    else { p = TAB_TAIL + (col - G_EARLY) * TL; left = TL; period = prm.pend; }
  }
  DI bool next(const GParams& prm, int col) {
    do {
      if (left == 0) {
        if (++period > prm.pend) return false;
        left = period < prm.pend ? ML : DL;
        if (period > 1 && period < prm.pend) p -= ML;
      }
      e = prm.tab[p++]; left--;
    } while ((e & 7) == T_NONE);
    const int b = (e >> 4) & 15, blk = period < prm.pend ? period - b : b;
    type = e & 7; valid = blk >= 0; lb = (e & 8) * 2 + (blk & 15); n0 = (e >> 9) & 127; kb0 = (e >> 16) & 127;
    gemm = type != T_F1 && type != T_F2;
    nkb = valid ? (e >> 23) & 31 : 0;
    return true;
  }
  DI int id_(int pend) const { return period < pend ? period * 10 + ML - left : 160 + DL - left; }
};

#define GLOG(nt, i, v)
template <int TA> DI void wg_ss128(float* d, uint64_t da, uint64_t db, int sc) {
  asm volatile("{.reg .pred p; setp.ne.b32 p, %66, 0;\n"
               "wgmma.mma_async.sync.aligned.m64n128k16.f32.bf16.bf16 "
               "{%0,%1,%2,%3,%4,%5,%6,%7,%8,%9,%10,%11,%12,%13,%14,%15,%16,%17,%18,%19,%20,%21,%22,%23,%24,%25,%26,%27,%28,%29,%30,%31,"
               "%32,%33,%34,%35,%36,%37,%38,%39,%40,%41,%42,%43,%44,%45,%46,%47,%48,%49,%50,%51,%52,%53,%54,%55,%56,%57,%58,%59,%60,%61,%62,%63}, "
               "%64, %65, p, 1, 1, %67, 1;}"
               : ACC16(d, 0), ACC16(d, 16), ACC16(d, 32), ACC16(d, 48) : "l"(da), "l"(db), "r"(sc), "n"(TA));
}

template <int TA> DI void g_mainloop(float* acc, uint32_t sb, uint32_t hand, uint32_t gate, int nkb, int cw, int lane, uint32_t st, uint32_t ph) {
  const uint64_t da0 = (TA ? mkdesc(SMEM0, 4096, 512, 2) : mkdesc(SMEM0, 128, 1024, 0)) + (cw >> 2) * 512;
  const uint64_t db0 = mkdesc(SMEM0 + 16384, 8192, 1024, 1);
  uint32_t prev = 0;
#pragma unroll 1
  for (int kb = 0; kb < nkb; kb++) {
    mbar_wait(sb + GB_FULL + 8 * st, ph);
    mbar_wait(gate, 1);
    const uint64_t da = da0 + st * 2048, db = db0 + st * 2048;
    wg_fence();
#pragma unroll
    for (int k = 0; k < 4; k++) wg_ss128<TA>(acc, da + k * (TA ? 64 : 16), db + k * 128, 1);
    wg_commit();
    mbar_arrive_if(hand && kb == nkb - 1 && lane == 0, hand);
    wg_wait<1>();
    mbar_arrive_if(kb > 0 && lane == 0, sb + GB_EMPTY + 8 * prev);
    prev = st;
    if (++st == G_NST) { st = 0; ph ^= 1; }
  }
  wg_wait<0>();
  reg_fence<64>(acc);
  mbar_arrive_if(lane == 0, sb + GB_EMPTY + 8 * prev);
}

__global__ void __launch_bounds__(640, 1)
g_kernel(const __grid_constant__ CUtensorMap mapWo, const __grid_constant__ CUtensorMap mapWg, const __grid_constant__ CUtensorMap mapWu,
         const __grid_constant__ CUtensorMap mapWd, const __grid_constant__ GParams prm) {
  const uint32_t sb = smem_base();
  const int wid = __shfl_sync(~0u, threadIdx.x >> 5, 0), lane = threadIdx.x & 31;
  if (threadIdx.x == 0) {
    if ((sb & 0x3FFFF) != SMEM0) __trap();
    {
      uint32_t sm; asm volatile("mov.u32 %0, %%smid;" : "=r"(sm));
      uint32_t* const tk = &g_cnt[C_TICKET * CSTRIDE];
      uint32_t c = atomicAdd(tk, 1);
      if (c < G_EARLY) {
        const uint32_t k = sm < 64 ? (sm >> 1) & 7 : sm < 120 ? 1 + ((sm - 64) >> 1) % 7 : sm < 124 ? 1 + ((sm >> 1) & 1) : 0;
        const uint32_t t = atomicAdd(tk + 1 + k, 1);
        atomicAdd(tk + 9, 1);
        if (t < prm.first[k + 1] - prm.first[k]) c = prm.perm[prm.first[k] + t];
        else {
          uint32_t o = atomicAdd(tk + 10, 1), g = 0;
          while (ld_acq(tk + 9) < G_EARLY) guard(g);
          for (int j = 0; j < 8; j++)
            for (uint32_t i = prm.first[j] + ld_acq(tk + 1 + j); i < prm.first[j + 1]; i++) if (o-- == 0) c = prm.perm[i];
        }
      }
      sts32(sb + GS_COL, c);
    }
    for (int i = 0; i < G_NST; i++) { mbar_init(sb + GB_FULL + 8 * i, 1); mbar_init(sb + GB_EMPTY + 8 * i, 8); }
    mbar_init(sb + GB_ORD, 8); mbar_init(sb + GB_ORD + 8, 8); mbar_init(sb + GB_READY, 1); mbar_init(sb + GB_ACK, 1);
    mbar_init(sb + GB_GATE, 1); mbar_init(sb + GB_GATE + 8, 1);
    mbar_init(sb + GB_SIG, 8); mbar_init(sb + GB_SIG + 8, 8); mbar_init(sb + GB_SACK, 1); mbar_init(sb + GB_SACK + 8, 1);
    fence_async_smem();
  }
  __syncthreads();
  const int col = __shfl_sync(~0u, lds32(sb + GS_COL), 0);

  if (wid >= 16) {
    GIter t(prm, col);
    asm volatile("setmaxnreg.dec.sync.aligned.u32 %0;" ::"n"(GRP));
    uint32_t st = 0, ph = 1, k = 0;
    if (wid == 16) {
      while (t.next(prm, col)) {
        const CUtensorMap* m0 = t.type == T_A ? &mapWo : t.type == T_U ? &mapWg : &mapWd;
        const CUtensorMap* m1 = t.type == T_U ? &mapWu : m0;
        const int c0 = t.type == T_U ? t.n0 * 64 : (t.n0 & 7) * 128, c1 = t.type == T_U ? c0 : c0 + 64;
        if ((t.e & (E_HALF | E_UP)) == E_UP) poll_ge(&g_cnt[c_phase(t.type, t.lb) * CSTRIDE], prm.need[t.type][t.lb]);
#pragma unroll 1
        for (uint32_t kb = t.kb0; kb < t.kb0 + t.nkb; kb++) {
          mbar_wait(sb + GB_EMPTY + 8 * st, ph);
          if (elect_one()) {
            const uint32_t full = sb + GB_FULL + 8 * st, dst = sb + st * 32768;
            mbar_expect(full, (t.e & E_HALF) ? 24576 : 32768);
            tma_2d(dst + 16384, m0, c0, kb * 64, full);
            tma_2d(dst + 24576, m1, c1, kb * 64, full);
          }
          if (++st == G_NST) { st = 0; ph ^= 1; }
        }
      }
    } else if (wid == 17) {
      while (t.next(prm, col)) {
        if (!t.nkb) continue;
        const char* asrc = t.type == T_A ? (const char*)g_oT + (size_t)t.lb * (96 * 16384)
                         : t.type == T_U ? (const char*)g_xa + (size_t)(t.lb & 15) * (10 * 16384) : (const char*)g_h + (size_t)(t.lb & 15) * (24 * 16384);
        const uint32_t up = (t.e & E_HALF) ? (t.e & E_UP) * 32 : 0;
        GLOG(t.id_(prm.pend), 1, gtime());
        mbar_wait(sb + GB_READY, k & 1);
        mbar_arrive_if(lane == 0, sb + GB_ACK);
        k++;
#pragma unroll 1
        for (uint32_t kb = t.kb0; kb < t.kb0 + t.nkb; kb++) {
          mbar_wait(sb + GB_EMPTY + 8 * st, ph);
          if (elect_one()) bulk_g2s(sb + st * 32768 + up, asrc + (size_t)kb * 16384 + up, (t.e & E_HALF) ? 8192 : 16384, sb + GB_FULL + 8 * st);
          if (++st == G_NST) { st = 0; ph ^= 1; }
        }
      }
    } else if (wid == 18) {
      while (t.next(prm, col)) {
        if (!t.nkb) continue;
        const bool lower = t.type == T_A && (t.e & (E_HALF | E_UP)) == E_HALF;
        poll_ge(&g_cnt[(lower ? C_HALF + t.lb : c_phase(t.type, t.lb)) * CSTRIDE], prm.need[t.type][t.lb]);
        fence_async_global();
        GLOG(t.id_(prm.pend), 2, gtime());
        mbar_wait(sb + GB_ACK, (k & 1) ^ 1);
        mbar_arrive_if(lane == 0, sb + GB_READY);
        k++;
      }
    } else {
      uint32_t live = 3, par = 0, g = 0;
      while (live) {
        const bool ev = lane < 2 && ((live >> lane) & 1) && mbar_test(sb + GB_SIG + 8 * lane, (par >> lane) & 1);
        const uint32_t evs = __ballot_sync(~0u, ev);
        if (!evs) { guard(g); __nanosleep(20); continue; }
        const uint32_t msg = ev ? lds32(sb + GS_SIG + 4 * lane) : 0;
        mbar_arrive_if(ev, sb + GB_SACK + 8 * lane);
        mbar_arrive_if(msg >> 31, sb + GB_GATE + 8 * lane);
        if (msg) red_rel(&g_cnt[(msg & 0xffff) * CSTRIDE], (msg >> 16) & 255);
        par ^= evs;
        live &= ~__ballot_sync(~0u, ev && !msg);
        g = 0;
      }
      asm volatile("griddepcontrol.wait;" ::: "memory");
      if (col < 80 && lane < 16) g_mem[(col >> 4) * 2048 + (lane >> 3) * 1024 + 512 + prm.moff + (col & 15) * 8 + (lane & 7)] = make_uint4(~0u, ~0u, ~0u, ~0u);
      uint32_t last = 0;
      if (lane == 0) last = atomicAdd(&g_cnt[C_EXIT * CSTRIDE], 1) == gridDim.x - 1;
      if (__shfl_sync(~0u, last, 0)) {
        g_cnt[C_TICKET * CSTRIDE + lane] = 0;
        for (int i = lane; i < C_USED; i += 32) g_cnt[i * CSTRIDE] = 0;
      }
    }
  } else {
    asm volatile("setmaxnreg.inc.sync.aligned.u32 %0;" ::"n"(GRC));
    const int cw = wid & 7, wk = wid >> 3;
    GIter t(prm, col);
    uint32_t pos = 0, seen = 0, waited = 0;
    uint32_t nsig = 0;
    auto signal = [&](uint32_t msg) {
      mbar_wait(sb + GB_SACK + 8 * wk, (nsig++ & 1) ^ 1);
      if (cw == 0) sts32(sb + GS_SIG + 4 * wk, msg);
      __syncwarp();
      mbar_arrive_if(lane == 0, sb + GB_SIG + 8 * wk);
    };
    if (col < G_EARLY) {
      spin(prm.gd);
#pragma unroll 1
      for (int rg = 96 + col * 2 + wk; rg < 256; rg += 2 * G_EARLY) {
        uint32_t a[10];
        const uint32_t* src = prm.x + (size_t)(rg * 8 + (lane >> 2)) * (DM / 2) + cw * 40 + (lane & 3);
#pragma unroll
        for (int i = 0; i < 10; i++) a[i] = __ldg(src + i * 4);
        first_ln(a, rg, sb + GS_RED + wk * 512, cw, lane, 1 + wk);
        signal((C_XN + (rg >> 4)) | ((XN_TARGET / NF) << 16));
        bar_sync(1 + wk, 256);
      }
    }
    while (t.next(prm, col)) {
      const uint32_t pos0 = pos;
      pos = (pos + t.nkb) % (2 * G_NST);
      if (((t.e >> 29) & 1) != wk) { seen += (t.e >> 30) & 1; continue; }
      const uint32_t type = t.type, blk = t.lb & 15, layer = t.lb >> 4, n0 = t.n0;
      if (cw == 0 && t.valid) GLOG(t.id_(prm.pend), 0, 0x80000000u | type | (t.lb << 3) | (n0 << 8) | (t.nkb << 16));
      if (!t.gemm) {
        if (!t.valid) continue;
        const int rg = blk * 16 + n0;
        float4 v[5];
        const int off = (n0 * 40 + cw * 5) * 32 + lane, npl = t.kb0;
        const uint2* src = acc_planes(t.lb, type == T_F2) + off;
        if (cw == 0) {
          poll_ge(&g_cnt[c_phase(type, t.lb) * CSTRIDE], prm.need[type][t.lb]);
          mbar_arrive_if((t.e & E_EXCL) && lane == 0, sb + GB_GATE + 8 * wk);
          GLOG(t.id_(prm.pend), 2, gtime()); GLOG(t.id_(prm.pend), 3, gtime());
        }
        bar_sync(1 + wk, 256);
        {
          const uint32_t eye = (lane >> 3) == (lane & 3) ? ((lane & 4) ? 0x3f800000u : 0x00003f80u) : 0u;
#pragma unroll
          for (int i = 0; i < 5; i++) v[i] = make_float4(0.f, 0.f, 0.f, 0.f);
#pragma unroll 1
          for (int p0 = 0; p0 < npl; p0 += FPL) {
            uint32_t r[FPL / 2][5][4];
#pragma unroll
            for (int p = 0; p < FPL; p++)
#pragma unroll
              for (int i = 0; i < 5; i++) {
                const uint2 w = p0 + p < npl ? __ldcg(src + (size_t)(p0 + p) * PLANE + i * 32) : make_uint2(0, 0);
                r[p >> 1][i][(p & 1) * 2] = w.x; r[p >> 1][i][(p & 1) * 2 + 1] = w.y;
              }
#pragma unroll
            for (int p = 0; p < FPL / 2; p++) {
              if (p0 + 2 * p >= npl) break;
              if (t.e & E_EXCL) {
#pragma unroll
                for (int i = 0; i < 5; i++) mma16816(&v[i].x, r[p][i], eye, eye);
              } else {
#pragma unroll
                for (int i = 0; i < 5; i++) {
                  const uint32_t* w = r[p][i];
                  v[i].x += blo(w[0]) + blo(w[2]); v[i].y += bhi(w[0]) + bhi(w[2]); v[i].z += blo(w[1]) + blo(w[3]); v[i].w += bhi(w[1]) + bhi(w[3]);
                }
              }
            }
          }
        }
        if (type == T_F2 && layer == 1) {
          uint2* dst = (uint2*)prm.out + (size_t)(rg * 8 + (lane >> 2)) * (DM / 4) + cw * 20 + (lane & 1) * 2 + ((lane >> 1) & 1);
#pragma unroll
          for (int i = 0; i < 5; i++) {
            const uint32_t a = pack2(v[i].x, v[i].y), b = pack2(v[i].z, v[i].w);
            const uint32_t o = __shfl_xor_sync(~0u, (lane & 1) ? a : b, 1);
            dst[i * 4] = (lane & 1) ? make_uint2(o, b) : make_uint2(a, o);
          }
        } else {
          uint2* nx = (type == T_F1 ? acc_planes(t.lb, 1) : acc_planes(NBLK + blk, 0)) + off;
#pragma unroll
          for (int i = 0; i < 5; i++) {
            const uint2 w = make_uint2(pack2(v[i].x, v[i].y), pack2(v[i].z, v[i].w));
            nx[i * 32] = w;
            v[i] = make_float4(blo(w.x), bhi(w.x), blo(w.y), bhi(w.y));
          }
          float mean, rstd;
          ln_stats(v, sb + GS_RED + wk * 512, cw, lane, 1 + wk, mean, rstd);
          if (type == T_F2) store_img<4, 2048>(xn_row_group(1, rg) + lane, v, cw, mean, rstd);
          else store_img<3, 4096>(g_xa + (size_t)(blk * 10 * 4096 + n0 * 256) + lane, v, cw, mean, rstd);
        }
      } else {
        float acc[64];
#pragma unroll
        for (int j = 0; j < 64; j++) acc[j] = 0.f;
        if (waited != seen) { mbar_wait(sb + GB_ORD + 8 * (wk ^ 1), waited & 1); waited++; }
        const uint32_t hand = (t.e & E_HAND) ? sb + GB_ORD + 8 * wk : 0;
        if (!t.valid) { mbar_arrive_if(hand && lane == 0, hand); continue; }
        if (cw == 0) GLOG(t.id_(prm.pend), 3, gtime());
        const uint32_t ph = pos0 >= G_NST, st = pos0 - ph * G_NST, early = (t.e & E_EXCL) ? 0 : hand;
        const bool idle = (t.e & E_HALF) && ((t.e >> 8) & 1) != (cw >> 2);
        if (idle) {
          uint32_t s2 = st, p2 = ph;
#pragma unroll 1
          for (uint32_t kb = 0; kb < t.nkb; kb++) {
            mbar_wait(sb + GB_FULL + 8 * s2, p2);
            mbar_arrive_if(lane == 0, sb + GB_EMPTY + 8 * s2);
            if (++s2 == G_NST) { s2 = 0; p2 ^= 1; }
          }
          mbar_arrive_if(early && lane == 0, early);
        } else if (type == T_A) g_mainloop<1>(acc, sb, early, sb + GB_GATE + 8 * (wk ^ 1), t.nkb, cw, lane, st, ph);
        else g_mainloop<0>(acc, sb, early, sb + GB_GATE + 8 * (wk ^ 1), t.nkb, cw, lane, st, ph);
        if (cw == 0) GLOG(t.id_(prm.pend), 4, gtime());
        if (idle) {
        } else if (type == T_U) {
          uint32_t* dst = g_h + (size_t)((blk * 24 + n0) * 4096 + cw * 512) + lane;
#pragma unroll
          for (int j = 0; j < 8; j++) {
            float h[4];
#pragma unroll
            for (int e = 0; e < 4; e++) {
              float th;
              asm("tanh.approx.f32 %0, %1;" : "=f"(th) : "f"(0.5f * acc[4 * j + e]));
              h[e] = acc[32 + 4 * j + e] * fmaf(th, 0.5f, 0.5f);
            }
            dst[j * 32] = pack2(h[0], h[1]);
            dst[j * 32 + 256] = pack2(h[2], h[3]);
          }
        } else {
          uint2* dst = acc_planes(t.lb, type == T_D) + (size_t)((1 + (n0 >> 3)) * PLANE + (2 * cw * 40 + (n0 & 7) * 8) * 32) + lane;
#pragma unroll
          for (int j = 0; j < 16; j++) {
            const float* a = acc + (j >> 1) * 8 + (j & 1) * 2;
            dst[(j >> 1) * 32 + (j & 1) * 1280] = make_uint2(pack2(a[0], a[1]), pack2(a[4], a[5]));
          }
        }
        mbar_arrive_if(hand != early && lane == 0, hand);
      }
      if (cw == 0) GLOG(t.id_(prm.pend), 5, gtime());
      if (cw == 0) GLOG(t.id_(prm.pend), 6, gtime());
      if (type == T_F2 && layer == 1) mbar_arrive_if((t.e & E_EXCL) && cw == 0 && lane == 0, sb + GB_GATE + 8 * wk);
      else
        signal((type != T_F2 ? c_phase(type + 1, t.lb) | (1 << 16) : (C_XN + NBLK + blk) | ((XN_TARGET / NF) << 16)) | (t.gemm ? 0 : t.e & E_EXCL));
    }
    signal(0);
  }
}

typedef CUresult (*EncodeFn)(CUtensorMap*, CUtensorMapDataType, cuuint32_t, void*, const cuuint64_t*, const cuuint64_t*, const cuuint32_t*,
                             const cuuint32_t*, CUtensorMapInterleave, CUtensorMapSwizzle, CUtensorMapL2promotion, CUtensorMapFloatOOBfill);
static CUtensorMap make_map(EncodeFn fn, const void* p, uint64_t inner, uint64_t outer, uint32_t bi, uint32_t bo, int promo = 3) {
  CUtensorMap m;
  cuuint64_t dims[2] = {inner, outer}, str[1] = {inner * 2};
  cuuint32_t box[2] = {bi, bo}, es[2] = {1, 1};
  fn(&m, CU_TENSOR_MAP_DATA_TYPE_BFLOAT16, 2, (void*)p, dims, str, box, es, CU_TENSOR_MAP_INTERLEAVE_NONE, CU_TENSOR_MAP_SWIZZLE_128B,
     (CUtensorMapL2promotion)promo, CU_TENSOR_MAP_FLOAT_OOB_FILL_NONE);
  return m;
}
struct Tune {
  int lag = 11, excl = 6, gonly = 0, xl = 1, ronly = 0, pn = 30;
  int da = 100, db = 350, dc = 650, dd = 650, d2 = 2000, p1 = 400, p2 = 800;
  int ea = 60, eb = 310, ec = 550, ed = 550, e2 = 2200, q1 = 200, q2 = 400, d3 = 60, moff = 192, ds = 400, dh = 60, pa = 0, pb = 0, pc = 0, pd = 0, pe = 0, pf = 0, pg = 0, ph = 0, hold = 1, wpf = 4, gd = 22000, dq = 600, sl = 18, pr = 2, pg2 = 3;
};
static void fill_r(RParams& p, const Tune& t, int lag, int n0, int n1) {
  r_fill_desc(p);
  p.nslots = 0; p.d3 = t.d3; p.pn = t.pn; p.moff = t.moff; p.ds = t.ds; p.dh = t.dh; p.dq = t.dq;
  for (int c = 0; c < 5; c++) { p.d2[c] = t.d2 + (c == 0 ? 0 : c < 3 ? t.p1 : t.p2); p.d2[5 + c] = t.e2 + (c == 0 ? 0 : c < 3 ? t.q1 : t.q2); }
  const int d1[8] = {t.da, t.db, t.dc, t.dd, t.ea, t.eb, t.ec, t.ed};
  for (int i = 0; i < 8; i++) p.d1[i] = d1[i];
  int last[2] = {0, 0}, n = 0;
  for (int s0 = 0; s0 < NSEG + lag; s0++)
    for (int l = 0; l < 2; l++) {
      const int s = l ? s0 - lag : s0;
      if (s < 0 || s >= NSEG) continue;
      if (n >= n0 && n < n1) { p.slot[p.nslots] = s | (l << 6) | (last[l] << 8) | (((s & 3) == 3 ? C_O + l * NBLK + s / 4 : s == (l ? 61 : 1) ? C_HALF + l * NBLK + s / 4 : 0) << 16); last[l] = ++p.nslots; }
      n++;
    }
  for (int i = 0; i + 1 < p.nslots; i++) if (((p.slot[i] ^ p.slot[i + 1]) >> 6) & 1) p.slot[i] |= 128;
}
static uint32_t g_entry(int grp, int type, int layer, int blk, int i, int ks) {
  int n0 = i, kb0 = 0, kb1 = type == T_U ? 10 : 0;
  if (type == T_F1 || type == T_F2) kb0 = kb1 = ks + 1;
  if (type == T_A || type == T_D) {
    const int KB = type == T_A ? 96 : 24, sp = i / 5;
    n0 = i % 5 | (sp << 3); kb0 = sp * KB / ks; kb1 = (sp + 1) * KB / ks;
  }
  return type | (layer << 3) | (blk << 4) | (n0 << 9) | (kb0 << 16) | ((kb1 - kb0) << 23) | (grp ? E_GRP : 0);
}
static bool g_is_gemm(uint32_t e) { return (e & 7) == T_A || (e & 7) == T_U || (e & 7) == T_D; }
static void g_handover(uint32_t* e, int len) {
  uint32_t next = 0;
  for (int i = len - 1; i >= 0; i--)
    if (g_is_gemm(e[i])) { if ((e[i] & E_GRP) != next) e[i] |= E_HAND; next = e[i] & E_GRP; }
}
struct GList {
  GParams& g; uint32_t* tab; int ncol, stride, len, n[G_LATE], load[G_LATE], grp[G_LATE];
  GList(GParams& g_, uint32_t* t, int nc, int st, int l) : g(g_), tab(t), ncol(nc), stride(st), len(l) { for (int c = 0; c < nc; c++) { n[c] = load[c] = 0; grp[c] = 1; } }
  void add(int type, int lb, int ks, int c0, int c1, uint32_t flags = 0, int i0 = 0, int i1 = 999, int step = 1) {
    const int half = (flags & E_HALF) != 0, ln = type == T_F1 || type == T_F2;
    const int cnt = (type == T_U ? 24 : ln ? NF : 5 * ks) << half;
    if (type < T_F2) g.need[type + 1][lb] = cnt;
    int used[G_LATE] = {0};
    for (int i = i0; i < cnt && i < i1; i += step) {
      int best = c0;
      for (int c = c0; c < c1; c++) if (used[c] < used[best] || (used[c] == used[best] && load[c] < load[best])) best = c;
      used[best]++;
      if (!ln) grp[best] ^= 1;
      const uint32_t e = g_entry(grp[best], type, lb >> 4, lb & 15, i >> half, ks) | flags | (ln ? E_EXCL : 0) | ((i & half) ? E_UP : 0);
      if (n[best] >= len) abort();
      tab[best * stride + n[best]++] = e;
      load[best] += (((e >> 23) & 31) >> half) + 2;
    }
  }
  void put(int c, uint32_t e) { if (n[c] >= len) abort(); tab[c * stride + n[c]++] = e; if (g_is_gemm(e)) grp[c] = (e & E_GRP) != 0; }
  void finish() { for (int c = 0; c < ncol; c++) g_handover(tab + c * stride, len); }
};
static void fill_g(GParams& g, const Tune& t, void* out) {
  g.out = (__nv_bfloat16*)out;  g.pend = NBLK - 2;
  for (int b = 0; b < 2 * NBLK; b++) {
    g.need[T_A][b] = 96; g.need[T_F1][b] = 20; g.need[T_U][b] = NF; g.need[T_D][b] = 32; g.need[T_F2][b] = 15;
  }
  {
    const uint8_t perm[G_EARLY] = {0, 1, 2, 3, 16, 17, 18, 19, 34, 35, 4, 20, 21, 15, 22, 23, 5, 6, 7, 8, 9, 24, 25, 26, 10, 11, 12, 13, 14, 27, 28, 29, 30, 31, 32, 33};
    const uint8_t first[9] = {0, 10, 13, 16, 20, 24, 28, 32, 36};
    const int* pk = &t.pa;
    for (int i = 0; i < G_EARLY; i++) g.perm[i] = t.pa ? (pk[i / 5] >> (6 * (i % 5))) & 63 : perm[i];
    for (int i = 0; i < 9; i++) g.first[i] = first[i];
  }
  for (uint32_t& e : g.tab) e = T_NONE;
  GList pr(g, g.tab, G_EARLY, EL, PL);
  pr.add(T_A, 0, 7, 1, 36, E_HALF, 0, 999, 2); pr.add(T_A, 0, 7, 1, 36, E_HALF, 1, 999, 2); pr.add(T_F1, 0, 7, 20, 36); pr.add(T_U, 0, 0, 12, 36);
  pr.add(T_D, 0, 3, 20, 36); pr.add(T_F2, 0, 3, 20, 36);
  pr.finish();
  const int d = 3;
  const uint32_t xa = (t.excl & 1) ? E_EXCL : 0, xu = (t.excl & 2) ? E_EXCL : 0, xd = (t.excl & 4) ? E_EXCL : 0;
  for (int c = 0; c < G_EARLY; c++) {
    uint32_t* e = g.tab + c * EL + PL;
    if (c < 20) {
      *e++ = g_entry(0, T_A, 0, 0, c, 4) | xa;
      if (c < NF) *e++ = g_entry(0, T_F1, 0, 0, c, 4) | ((t.xl & 1) ? E_EXCL : 0);
      *e++ = g_entry(1, T_A, 1, d, c, 4);
      if (c >= 20 - NF) *e++ = g_entry(1, T_F1, 1, d, c - (20 - NF), 4);
    } else {
      const int j = c - 20;
      const uint32_t hf = E_HALF | ((j & 1) ? E_UP : 0);
      *e++ = g_entry(0, T_U, 0, 0, j, 0);
      *e++ = g_entry(1, T_U, 0, 0, 16 + j / 2, 0) | hf | xu;
      *e++ = g_entry(0, T_U, 1, d + 1, 16 + j / 2, 0) | hf;
      if (j < 15) *e++ = g_entry(1, T_D, 0, 0, j, 3) | xd;
      *e++ = g_entry(1, T_F2, 0, 0, j, 3) | ((t.xl & 2) ? E_EXCL : 0);
      if (j < 15) *e++ = g_entry(0, T_D, 1, d + 1, j, 3);
      *e++ = g_entry(0, T_U, 1, d, j, 0);
      *e++ = g_entry(1, T_F2, 1, d + 1, j, 3);
    }
    g_handover(g.tab + c * EL + PL, ML);
  }
  GList dr(g, g.tab + PL + ML, G_EARLY, EL, DL);
  GList tl(g, g.tab + TAB_TAIL, G_LATE, TL, TL);
  const int L1 = NBLK;
  auto ufull = [&](int lb) { dr.add(T_U, lb, 0, 20, 36, 0, 0, 16); g.need[T_D][lb] = 32; };
  auto uhalf = [&](int lb) { dr.add(T_U, lb, 0, 20, 36, E_HALF, 32); g.need[T_D][lb] = 32; };
  for (int c = 0; c < G_EARLY; c++)
    for (int i = 0; i < ML; i++) {
      uint32_t e = g.tab[c * EL + PL + i] & ~E_HAND;
      const uint32_t ty = e & 7;
      if (ty == T_NONE || ((e & 8) && (ty == T_F2 || (ty == T_U && !(e & E_HALF))))) continue;
      e = (e & ~0xf0u) | (14 - ((e >> 4) & 15)) << 4;
      dr.put(c, e | (ty == T_F2 ? E_EXCL : 0));
    }
  dr.add(T_A, 15, 4, 0, 20, E_EXCL);
  dr.add(T_F1, 15, 4, 0, 16);
  dr.add(T_U, 15, 0, 12, 36, E_EXCL);
  for (int c = 0; c < 20; c++) {
    const int tile = c % 5, sp = c / 5, len = tile < 2 ? (96 - t.sl) / 3 : 48 - t.sl, nl = tile < 2 ? 3 : 2;
    const int k0 = sp <= nl ? sp * len : nl * len + t.sl, nk = sp < nl ? len : sp == 3 ? 96 - k0 : t.sl;
    dr.put(c, (g_entry(dr.grp[c] ^ 1, T_A, 1, 12, c, 4) & ~0x0fff0000u) | k0 << 16 | nk << 23);
  }
  dr.add(T_F1, L1 + 12, 4, 0, 16);
  uhalf(L1 + 11);
  dr.add(T_D, 15, 3, 20, 36, E_EXCL); dr.add(T_F2, 15, 3, 20, 36);
  dr.add(T_A, L1 + 13, 4, 0, 20); dr.add(T_F1, L1 + 13, 4, 0, 20);
  ufull(L1 + 11);
  dr.add(T_D, L1 + 11, 3, 20, 36);
  ufull(L1 + 12); uhalf(L1 + 12);
  dr.add(T_A, L1 + 14, 4, 0, 20);
  dr.add(T_A, L1 + 15, 7, 0, 35, E_HALF, 0, 999, 2); dr.add(T_A, L1 + 15, 7, 0, 35, E_HALF | E_EXCL, 1, 999, 2);
  dr.add(T_F1, L1 + 14, 4, 0, 16);
  dr.add(T_F1, L1 + 15, 7, 20, 36);
  dr.add(T_F2, L1 + 10, 3, 0, 16); dr.add(T_F2, L1 + 11, 3, 4, 20);  dr.add(T_F2, L1 + 12, 3, 0, 20);
  dr.add(T_D, L1 + 13, 3, 20, 36, (t.hold & 1) ? E_UP : 0); dr.add(T_F2, L1 + 13, 3, 20, 36);
  dr.finish();
  tl.add(T_D, L1 + 12, 3, 72, G_LATE);
  tl.add(T_U, L1 + 14, 0, 0, 24); tl.add(T_U, L1 + 13, 0, 24, 48);
  tl.add(T_D, L1 + 14, 4, 0, 48, E_HALF);
  tl.add(T_F2, L1 + 14, 4, 0, 48);
  tl.add(T_U, L1 + 15, 0, 48, G_LATE, E_HALF);
  tl.add(T_D, L1 + 15, 4, 48, G_LATE, E_HALF);
  tl.add(T_F2, L1 + 15, 4, 48, G_LATE);
  tl.finish();
}
static void launch_all(void* const* d_in, void* d_out, const Tune& t, cudaStream_t st) {
  static EncodeFn fn = nullptr;
  if (!fn) {
    void* f = nullptr;
    cudaDriverEntryPointQueryResult qr;
    cudaGetDriverEntryPoint("cuTensorMapEncodeTiled", &f, cudaEnableDefault, &qr);
    fn = (EncodeFn)f;
    cudaFuncSetAttribute(r_kernel, cudaFuncAttributeMaxDynamicSharedMemorySize, R_SMEM);
    cudaFuncSetAttribute(g_kernel, cudaFuncAttributeMaxDynamicSharedMemorySize, G_SMEM);
  }
  const CUtensorMap mq = make_map(fn, d_in[2], HD, DM, 64, 128, t.pr), mk = make_map(fn, d_in[3], HD, DM, 64, 128, t.pr), mv = make_map(fn, d_in[4], HD, DM, 64, 128, t.pr),
                    mo = make_map(fn, d_in[5], DM, HD, 64, 64, t.pg2), mg = make_map(fn, d_in[8], FF, DM, 64, 64, t.pg2), mu = make_map(fn, d_in[9], FF, DM, 64, 64, t.pg2),
                    md = make_map(fn, d_in[10], DM, FF, 64, 64, t.pg2);
  auto launch_r = [&](int lag, int n0, int n1) {
    RParams p;
    fill_r(p, t, lag, n0, n1);
    for (int i = 0; i < 4; i++) p.w[i] = (const char*)d_in[2 + i];
    p.mem0 = (const uint4*)d_in[1]; p.x = (const uint32_t*)d_in[0]; p.pf = t.wpf;
    cudaLaunchConfig_t cfg = {};
    cfg.gridDim = dim3(3, NH); cfg.blockDim = dim3(512); cfg.dynamicSmemBytes = R_SMEM; cfg.stream = st;
    cudaLaunchAttribute at[1];
    at[0].id = cudaLaunchAttributeClusterDimension; at[0].val.clusterDim.x = 3; at[0].val.clusterDim.y = 1; at[0].val.clusterDim.z = 1;
    cfg.attrs = at; cfg.numAttrs = 1;
    cudaLaunchKernelEx(&cfg, r_kernel, mq, mk, mv, mo, p);
  };
  auto launch_g = [&](const GParams& g, bool pdl) {
    cudaLaunchConfig_t cfg = {};
    cfg.gridDim = dim3(132); cfg.blockDim = dim3(640); cfg.dynamicSmemBytes = G_SMEM; cfg.stream = st;
    cudaLaunchAttribute at[2];
    at[0].id = cudaLaunchAttributeProgrammaticStreamSerialization; at[0].val.programmaticStreamSerializationAllowed = 1;
    cfg.attrs = at; cfg.numAttrs = pdl ? 1 : 0;
    cudaLaunchKernelEx(&cfg, g_kernel, mo, mg, mu, md, g);
  };
  GParams g;
  fill_g(g, t, d_out);
  g.moff = t.moff; g.gd = t.gd; g.x = (const uint32_t*)d_in[0];
  launch_r(t.lag, 0, 2 * NSEG);
  launch_g(g, true);
}

extern "C" void kernel_launch(void* const* d_in, const int* in_sizes, int n_in, void* d_out, int out_size) {
  launch_all(d_in, d_out, Tune(), cudaStreamPerThread);
}
```

```cpp
#include <cuda_runtime.h>
#include <cuda_bf16.h>
#include <cuda.h>
#include <stdint.h>
#include <stdlib.h>

constexpr int SEQ = 2048, DM = 640, NH = 32, DH = 192, HD = NH * DH, FF = 1536;
constexpr int NSEG = 64, SEGL = 32, NMEM = 8;
constexpr int NBLK = 16;

#define DI __device__ __forceinline__

DI uint32_t smem_base() {
  extern __shared__ __align__(1024) unsigned char smem_raw[];
  uint32_t a;
  asm volatile("{.reg .u64 t; cvta.to.shared.u64 t, %1; cvt.u32.u64 %0, t;}" : "=r"(a) : "l"(smem_raw));
  return a;
}
DI uint32_t mapa(uint32_t a, uint32_t r) {
  uint32_t o;
  asm("mapa.shared::cluster.u32 %0, %1, %2;" : "=r"(o) : "r"(a), "r"(r));
  return o;
}
DI void mbar_init(uint32_t bar, uint32_t cnt) { asm volatile("mbarrier.init.shared::cta.b64 [%0], %1;" ::"r"(bar), "r"(cnt) : "memory"); }
DI void mbar_arrive(uint32_t bar) { asm volatile("mbarrier.arrive.shared::cta.b64 _, [%0];" ::"r"(bar) : "memory"); }
DI void mbar_arrive_remote(uint32_t bar) { asm volatile("mbarrier.arrive.release.cluster.shared::cluster.b64 _, [%0];" ::"r"(bar) : "memory"); }
DI void mbar_expect(uint32_t bar, uint32_t tx) { asm volatile("mbarrier.arrive.expect_tx.shared::cta.b64 _, [%0], %1;" ::"r"(bar), "r"(tx) : "memory"); }
DI void mbar_arrive_if(bool p, uint32_t bar) { asm volatile("{.reg .pred p; setp.ne.b32 p, %1, 0; @p mbarrier.arrive.shared::cta.b64 _, [%0];}" ::"r"(bar), "r"((int)p) : "memory"); }
DI void mbar_arrive_if(bool p, uint32_t bar, uint32_t cnt) {
  asm volatile("{.reg .pred p; setp.ne.b32 p, %1, 0; @p mbarrier.arrive.shared::cta.b64 _, [%0], %2;}" ::"r"(bar), "r"((int)p), "r"(cnt) : "memory");
}
DI void mbar_expect_if(bool p, uint32_t bar, uint32_t tx) {
  asm volatile("{.reg .pred p; setp.ne.b32 p, %2, 0; @p mbarrier.arrive.expect_tx.shared::cta.b64 _, [%0], %1;}" ::"r"(bar), "r"(tx), "r"((int)p) : "memory");
}
DI bool mbar_test(uint32_t bar, uint32_t par) {
  uint32_t ok;
  asm volatile("{.reg .pred p; mbarrier.test_wait.parity.shared::cta.b64 p, [%1], %2; selp.u32 %0, 1, 0, p;}" : "=r"(ok) : "r"(bar), "r"(par) : "memory");
  return ok;
}
DI void mbar_wait(uint32_t bar, uint32_t par) {
  asm volatile(
      "{.reg .pred p;\n"
      "LOOP:\n"
      "mbarrier.try_wait.parity.shared::cta.b64 p, [%0], %1;\n"
      "@!p bra LOOP;\n}" ::"r"(bar), "r"(par) : "memory");
}
DI void mbar_wait_wd(uint32_t bar, uint32_t par) {
  asm volatile(
      "{.reg .pred p; .reg .u32 c;\n"
      "mov.u32 c, 0;\n"
      "LOOP:\n"
      "mbarrier.try_wait.parity.shared::cta.b64 p, [%0], %1;\n"
      "@p bra DONE;\n"
      "add.u32 c, c, 1;\n"
      "setp.lt.u32 p, c, 4000000;\n"
      "@p bra LOOP;\n"
      "trap;\n"
      "DONE:\n}" ::"r"(bar), "r"(par) : "memory");
}
DI void fence_async_smem() { asm volatile("fence.proxy.async.shared::cta;" ::: "memory"); }
DI void fence_async_global() { asm volatile("fence.proxy.async.global;" ::: "memory"); }
DI void bar_sync(int id, int n) { asm volatile("bar.sync %0, %1;" ::"r"(id), "r"(n) : "memory"); }
DI void bar_arrive(int id, int n) { asm volatile("bar.arrive %0, %1;" ::"r"(id), "r"(n) : "memory"); }
DI void cluster_sync() { asm volatile("barrier.cluster.arrive.release.aligned; barrier.cluster.wait.acquire.aligned;" ::: "memory"); }
DI bool elect_one() {
  uint32_t p;
  asm volatile("{.reg .pred p; elect.sync _|p, 0xffffffff; selp.u32 %0, 1, 0, p;}" : "=r"(p));
  return p;
}
DI void bulk_g2s(uint32_t dst, const void* src, uint32_t bytes, uint32_t bar) {
  asm volatile("cp.async.bulk.shared::cluster.global.mbarrier::complete_tx::bytes [%0], [%1], %2, [%3];" ::"r"(dst), "l"(src), "r"(bytes), "r"(bar) : "memory");
}
DI void bulk_g2s_mc(uint32_t dst, const void* src, uint32_t bytes, uint32_t bar, uint16_t mask) {
  asm volatile("cp.async.bulk.shared::cluster.global.mbarrier::complete_tx::bytes.multicast::cluster [%0], [%1], %2, [%3], %4;" ::"r"(dst), "l"(src), "r"(bytes), "r"(bar), "h"(mask) : "memory");
}
DI void bulk_s2s(uint32_t dst, uint32_t src, uint32_t bytes, uint32_t bar) {
  asm volatile("cp.async.bulk.shared::cluster.shared::cta.mbarrier::complete_tx::bytes [%0], [%1], %2, [%3];" ::"r"(dst), "r"(src), "r"(bytes), "r"(bar) : "memory");
}
DI void tma_2d(uint32_t dst, const CUtensorMap* map, int c0, int c1, uint32_t bar) {
  asm volatile("cp.async.bulk.tensor.2d.shared::cluster.global.mbarrier::complete_tx::bytes [%0], [%1, {%3, %4}], [%2];" ::"r"(dst), "l"(map), "r"(bar), "r"(c0), "r"(c1) : "memory");
}
DI void tma_pf(const CUtensorMap* map, int c0, int c1) {
  asm volatile("cp.async.bulk.prefetch.tensor.2d.L2.global [%0, {%1, %2}];" ::"l"(map), "r"(c0), "r"(c1) : "memory");
}
DI void st_async4(uint32_t a, uint32_t x, uint32_t y, uint32_t z, uint32_t w, uint32_t bar) {
  asm volatile("st.async.shared::cluster.mbarrier::complete_tx::bytes.v4.b32 [%0], {%1,%2,%3,%4}, [%5];" ::"r"(a), "r"(x), "r"(y), "r"(z), "r"(w), "r"(bar) : "memory");
}
DI void st_async2(uint32_t a, uint32_t x, uint32_t y, uint32_t bar) {
  asm volatile("st.async.shared::cluster.mbarrier::complete_tx::bytes.v2.b32 [%0], {%1,%2}, [%3];" ::"r"(a), "r"(x), "r"(y), "r"(bar) : "memory");
}
DI void st_async1(uint32_t a, uint32_t x, uint32_t bar) {
  asm volatile("st.async.shared::cluster.mbarrier::complete_tx::bytes.b32 [%0], %1, [%2];" ::"r"(a), "r"(x), "r"(bar) : "memory");
}
DI void sts32(uint32_t a, uint32_t x) { asm volatile("st.shared.b32 [%0], %1;" ::"r"(a), "r"(x) : "memory"); }
DI void sts128(uint32_t a, uint4 v) { asm volatile("st.shared.v4.b32 [%0], {%1,%2,%3,%4};" ::"r"(a), "r"(v.x), "r"(v.y), "r"(v.z), "r"(v.w) : "memory"); }
DI uint32_t lds32(uint32_t a) { uint32_t v; asm volatile("ld.shared.b32 %0, [%1];" : "=r"(v) : "r"(a) : "memory"); return v; }
DI uint2 lds64(uint32_t a) { uint2 v; asm volatile("ld.shared.v2.b32 {%0,%1}, [%2];" : "=r"(v.x), "=r"(v.y) : "r"(a) : "memory"); return v; }
DI uint4 lds128(uint32_t a) { uint4 v; asm volatile("ld.shared.v4.b32 {%0,%1,%2,%3}, [%4];" : "=r"(v.x), "=r"(v.y), "=r"(v.z), "=r"(v.w) : "r"(a) : "memory"); return v; }
DI void stsm4(uint32_t a, uint32_t r0, uint32_t r1, uint32_t r2, uint32_t r3) {
  asm volatile("stmatrix.sync.aligned.m8n8.x4.shared.b16 [%0], {%1,%2,%3,%4};" ::"r"(a), "r"(r0), "r"(r1), "r"(r2), "r"(r3) : "memory");
}
DI void stsm2(uint32_t a, uint32_t r0, uint32_t r1) {
  asm volatile("stmatrix.sync.aligned.m8n8.x2.shared.b16 [%0], {%1,%2};" ::"r"(a), "r"(r0), "r"(r1) : "memory");
}
DI uint32_t movm(uint32_t a) { uint32_t d; asm volatile("movmatrix.sync.aligned.m8n8.trans.b16 %0, %1;" : "=r"(d) : "r"(a)); return d; }
DI uint32_t pack2(float lo, float hi) { uint32_t d; asm("cvt.rn.bf16x2.f32 %0, %1, %2;" : "=r"(d) : "f"(hi), "f"(lo)); return d; }
DI uint4 ld_rlx4(const void* p) {
  uint4 v;
  asm volatile("ld.relaxed.gpu.global.v4.u32 {%0,%1,%2,%3}, [%4];" : "=r"(v.x), "=r"(v.y), "=r"(v.z), "=r"(v.w) : "l"(p) : "memory");
  return v;
}
DI void st_rlx4(void* p, uint32_t x, uint32_t y, uint32_t z, uint32_t w) {
  asm volatile("st.relaxed.gpu.global.v4.u32 [%0], {%1,%2,%3,%4};" ::"l"(p), "r"(x), "r"(y), "r"(z), "r"(w) : "memory");
}
DI void st_rlx1(void* p, uint32_t x) { asm volatile("st.relaxed.gpu.global.u32 [%0], %1;" ::"l"(p), "r"(x) : "memory"); }
DI uint32_t ld_acq(const uint32_t* p) { uint32_t v; asm volatile("ld.acquire.gpu.global.u32 %0, [%1];" : "=r"(v) : "l"(p) : "memory"); return v; }
DI uint32_t ld_rlx(const uint32_t* p) { uint32_t v; asm volatile("ld.relaxed.gpu.global.u32 %0, [%1];" : "=r"(v) : "l"(p) : "memory"); return v; }
DI void red_rel(uint32_t* p, uint32_t v) { asm volatile("red.release.gpu.global.add.u32 [%0], %1;" ::"l"(p), "r"(v) : "memory"); }
DI void guard(uint32_t& g) { asm volatile("{.reg .pred p; add.u32 %0, %0, 1; setp.gt.u32 p, %0, 8000000; @p trap;}" : "+r"(g)); }
DI void poll_ge(const uint32_t* p, uint32_t target) {
  asm volatile(
      "{.reg .pred p; .reg .u32 v;\n"
      "LOOP:\n"
      "ld.acquire.gpu.global.u32 v, [%0];\n"
      "setp.lt.u32 p, v, %1;\n"
      "vote.sync.any.pred p, p, 0xffffffff;\n"
      "@p bra.uni LOOP;\n}" ::"l"(p), "r"(target) : "memory");
}
DI float ex2(float x) { float y; asm("ex2.approx.ftz.f32 %0, %1;" : "=f"(y) : "f"(x)); return y; }

DI void wg_fence() { asm volatile("wgmma.fence.sync.aligned;" ::: "memory"); }
DI void wg_commit() { asm volatile("wgmma.commit_group.sync.aligned;" ::: "memory"); }
template <int N> DI void wg_wait() { asm volatile("wgmma.wait_group.sync.aligned %0;" ::"n"(N) : "memory"); }
template <int N> DI void reg_fence(float* d) {
#pragma unroll
  for (int i = 0; i < N; i++) asm volatile("" : "+f"(d[i])::"memory");
}
__host__ __device__ constexpr uint64_t mkdesc(uint32_t addr, uint32_t lbo, uint32_t sbo, uint32_t sw) {
  return (uint64_t)((addr & 0x3FFFF) >> 4) | ((uint64_t)(lbo >> 4) << 16) | ((uint64_t)(sbo >> 4) << 32) | ((uint64_t)sw << 62);
}

#define ACC4(d, o) "+f"(d[o]), "+f"(d[o + 1]), "+f"(d[o + 2]), "+f"(d[o + 3])
#define ACC16(d, o) ACC4(d, o), ACC4(d, o + 4), ACC4(d, o + 8), ACC4(d, o + 12)
#define ACC20(d) ACC16(d, 0), ACC4(d, 16)

template <int TA, int TB> DI void wg_ss40(float* d, uint64_t da, uint64_t db, int sc) {
  asm volatile("{.reg .pred p; setp.ne.b32 p, %22, 0;\n"
               "wgmma.mma_async.sync.aligned.m64n40k16.f32.bf16.bf16 {%0,%1,%2,%3,%4,%5,%6,%7,%8,%9,%10,%11,%12,%13,%14,%15,%16,%17,%18,%19}, %20, %21, p, 1, 1, %23, %24;}"
               : ACC20(d) : "l"(da), "l"(db), "r"(sc), "n"(TA), "n"(TB));
}
DI void wg_rs40(float* d, uint32_t a0, uint32_t a1, uint32_t a2, uint32_t a3, uint64_t db, int sc) {
  asm volatile("{.reg .pred p; setp.ne.b32 p, %25, 0;\n"
               "wgmma.mma_async.sync.aligned.m64n40k16.f32.bf16.bf16 {%0,%1,%2,%3,%4,%5,%6,%7,%8,%9,%10,%11,%12,%13,%14,%15,%16,%17,%18,%19}, {%20,%21,%22,%23}, %24, p, 1, 1, 0;}"
               : ACC20(d) : "r"(a0), "r"(a1), "r"(a2), "r"(a3), "l"(db), "r"(sc));
}
DI void wg_rs32(float* d, uint32_t a0, uint32_t a1, uint32_t a2, uint32_t a3, uint64_t db, int sc) {
  asm volatile("{.reg .pred p; setp.ne.b32 p, %21, 0;\n"
               "wgmma.mma_async.sync.aligned.m64n32k16.f32.bf16.bf16 {%0,%1,%2,%3,%4,%5,%6,%7,%8,%9,%10,%11,%12,%13,%14,%15}, {%16,%17,%18,%19}, %20, p, 1, 1, 0;}"
               : ACC16(d, 0) : "r"(a0), "r"(a1), "r"(a2), "r"(a3), "l"(db), "r"(sc));
}
DI void wg_ss32k(float* d, uint64_t da, uint64_t db, int sc) {
  asm volatile("{.reg .pred p; setp.ne.b32 p, %18, 0;\n"
               "wgmma.mma_async.sync.aligned.m64n32k16.f32.bf16.bf16 {%0,%1,%2,%3,%4,%5,%6,%7,%8,%9,%10,%11,%12,%13,%14,%15}, %16, %17, p, 1, 1, 1, 0;}"
               : ACC16(d, 0) : "l"(da), "l"(db), "r"(sc));
}
DI void wg_ss8k(float* d, uint64_t da, uint64_t db, int sc) {
  asm volatile("{.reg .pred p; setp.ne.b32 p, %6, 0;\n"
               "wgmma.mma_async.sync.aligned.m64n8k16.f32.bf16.bf16 {%0,%1,%2,%3}, %4, %5, p, 1, 1, 1, 0;}"
               : ACC4(d, 0) : "l"(da), "l"(db), "r"(sc));
}
DI void wg_rs8(float* d, uint32_t a0, uint32_t a1, uint32_t a2, uint32_t a3, uint64_t db, int sc) {
  asm volatile("{.reg .pred p; setp.ne.b32 p, %9, 0;\n"
               "wgmma.mma_async.sync.aligned.m64n8k16.f32.bf16.bf16 {%0,%1,%2,%3}, {%4,%5,%6,%7}, %8, p, 1, 1, 0;}"
               : ACC4(d, 0) : "r"(a0), "r"(a1), "r"(a2), "r"(a3), "l"(db), "r"(sc));
}
DI void mma16816(float* c, const uint32_t* a, uint32_t b0, uint32_t b1) {
  asm volatile("mma.sync.aligned.m16n8k16.row.col.f32.bf16.bf16.f32 {%0,%1,%2,%3}, {%4,%5,%6,%7}, {%8,%9}, {%0,%1,%2,%3};"
               : ACC4(c, 0) : "r"(a[0]), "r"(a[1]), "r"(a[2]), "r"(a[3]), "r"(b0), "r"(b1));
}
DI void wg_ss8(float* d, uint64_t da, uint64_t db, int sc) {
  asm volatile("{.reg .pred p; setp.ne.b32 p, %6, 0;\n"
               "wgmma.mma_async.sync.aligned.m64n8k16.f32.bf16.bf16 {%0,%1,%2,%3}, %4, %5, p, 1, 1, 1, 1;}"
               : ACC4(d, 0) : "l"(da), "l"(db), "r"(sc));
}
DI void wg_rs16(float* d, uint32_t a0, uint32_t a1, uint32_t a2, uint32_t a3, uint64_t db, int sc) {
  asm volatile("{.reg .pred p; setp.ne.b32 p, %13, 0;\n"
               "wgmma.mma_async.sync.aligned.m64n16k16.f32.bf16.bf16 {%0,%1,%2,%3,%4,%5,%6,%7}, {%8,%9,%10,%11}, %12, p, 1, 1, 0;}"
               : ACC4(d, 0), ACC4(d, 4) : "r"(a0), "r"(a1), "r"(a2), "r"(a3), "l"(db), "r"(sc));
}
__device__ uint4 g_xn[2 * NSEG * 10 * 256];
__device__ uint4 g_oT[2 * NBLK * 96 * 1024];
constexpr int PART_RING = 96 * 256;
__device__ uint4 g_part[4 * PART_RING];
constexpr int MEM_OFF = 192;
#define P4 ~0u, ~0u, ~0u, ~0u
#define P16 P4, P4, P4, P4
#define P256 P16, P16, P16, P16, P16, P16, P16, P16, P16, P16, P16, P16, P16, P16, P16, P16
#define P2K P256, P256, P256, P256, P256, P256, P256, P256
#define P8K P2K, P2K, P2K, P2K
__device__ __align__(8192) uint32_t g_mem32[5 * 2 * 2 * 2048] = {P8K, P8K, P8K, P8K, P8K};
#define g_mem ((uint4*)g_mem32)
constexpr int C_XN = 0;
constexpr int C_O = C_XN + 2 * NBLK;
constexpr int C_HALF = C_O + 6 * 2 * NBLK;
constexpr int C_TOTAL = 512;
constexpr int CSTRIDE = 32;
__device__ uint32_t g_cnt[C_TOTAL * CSTRIDE];
constexpr uint32_t XN_TARGET = 128;

#define TRACE(c, n, i, v)
#define SLOG(i)
#define PROF(i)
#define PROFA(c)
#define PROFV(i, v)

constexpr uint32_t SMEM0 = 1024;
constexpr uint32_t SM_WK = 0, SM_WO = 81920, SM_H = 163840, SM_QT = 215040, QSTR = 1056  , SM_KT = SM_QT + 5 * QSTR + 1024,
                   SM_SR = SM_KT + 5120  , SM_PROF = SM_SR + 5760, R_SMEM = 232448,
                   SM_RED = SM_QT + 1024, SM_BAR = SM_RED + 768;
constexpr uint32_t SM_P = SM_KT, SM_OB = SM_QT + 3200;
constexpr uint32_t B_HFULL = SM_BAR, B_HEMPTY = SM_BAR + 40, B_MTRY = SM_BAR + 80, B_W = SM_BAR + 112, B_SR = B_W + 32,
                   B_PMEM = B_SR + 24, B_PTOK = B_SR + 32, B_OB = B_SR + 40, B_OPD = B_SR + 48, B_RFREE = B_SR + 56,
                   B_GATE = B_SR + 64, B_PSUM = B_SR + 72, B_END = B_SR + 80, B_PVI = B_SR + 88,
                   B_OPI = B_SR + 96, B_OTOK = B_SR + 112, SM_TOPI = B_SR + 128, B_PACE = SM_TOPI + 8,
                   SM_RS = SM_QT + 2 * QSTR + 1024;
static_assert(B_PACE + 32 <= SM_QT + 2 * QSTR, "barriers must fit the unused q row group");

struct RParams {
  uint64_t dH, dHt, dWK, dWO, dQT, dKT, dP, dOB[6];
  const char* w[4];
  const uint4* mem0;
  const uint32_t* x;
  int pf;
  int nslots, d3, pn, moff, ds, dh, dq;
  int d2[10], d1[8];
  uint32_t slot[2 * NSEG];
};
static void r_fill_desc(RParams& p) {
  p.dH = mkdesc(SMEM0 + SM_H, 128, 2048, 0);
  p.dHt = mkdesc(SMEM0 + SM_H + 2048, 128, 2048, 0);
  p.dWK = mkdesc(SMEM0 + SM_WK, 1024, 1024, 1);
  p.dWO = mkdesc(SMEM0 + SM_WO, 1024, 1024, 1);
  for (int i = 0; i < 6; i++) p.dOB[i] = mkdesc(SMEM0 + SM_OB + (i < 3 ? 0 : (i - 3) * 1024), 128, 128, 0);
  p.dQT = mkdesc(SMEM0 + SM_QT, 128, QSTR, 0);
  p.dKT = mkdesc(SMEM0 + SM_KT, 128, 1024, 0);
  p.dP = mkdesc(SMEM0 + SM_P, 128, 640, 0);
}
DI uint64_t dadd(uint64_t d, int bytes) {
  uint64_t r;
  asm volatile("add.u64 %0, %1, %2;" : "=l"(r) : "l"(d), "l"((long long)(bytes / 16)));
  return r;
}
template <int BYTES> DI void dstep(uint64_t& d) { asm volatile("add.u64 %0, %0, %1;" : "+l"(d) : "n"((long long)(BYTES / 16))); }
__host__ __device__ constexpr int hoff(int ks) { return (ks >> 3) * 10240 + (ks & 7) * 256; }

DI int opaque(int v) { asm volatile("" : "+r"(v)); return v; }
DI uint32_t pin(uint32_t v, int lane) { return __shfl_sync(~0u, v + (lane >> 5), lane); }
DI char* pin(char* p, int lane) { return (char*)__shfl_sync(~0u, (unsigned long long)p, lane); }
DI float blo(uint32_t w) { return __uint_as_float(w << 16); }
DI float bhi(uint32_t w) { return __uint_as_float(w & 0xffff0000u); }
#define R_FB 1
#define PIN_DST 1
#define RG0 232
#define RG1 216
#define RG2 40
#define RG3 24
DI void ldsm4t(uint32_t* r, uint32_t a) {
  asm volatile("ldmatrix.sync.aligned.m8n8.x4.trans.shared.b16 {%0,%1,%2,%3}, [%4];" : "=r"(r[0]), "=r"(r[1]), "=r"(r[2]), "=r"(r[3]) : "r"(a) : "memory");
}
DI void st_tagged(void* p, float a, float b, uint32_t keep, uint32_t tagbit) {
  asm volatile("{.reg .b32 t; cvt.rn.bf16x2.f32 t, %2, %1; lop3.b32 t, t, %3, %4, 0xea; st.relaxed.gpu.global.b32 [%0], t;}" ::"l"(p), "f"(a), "f"(b),
               "r"(keep), "r"(tagbit) : "memory");
}
DI uint32_t lop_bad(uint32_t a, uint32_t b, uint32_t m) { uint32_t d; asm("lop3.b32 %0, %1, %2, %3, 0x7e;" : "=r"(d) : "r"(a), "r"(b), "r"(m)); return d; }
DI uint32_t lop_or3(uint32_t a, uint32_t b, uint32_t c) { uint32_t d; asm("lop3.b32 %0, %1, %2, %3, 0xfe;" : "=r"(d) : "r"(a), "r"(b), "r"(c)); return d; }
DI uint32_t clk() { uint32_t t; asm volatile("mov.u32 %0, %%clock;" : "=r"(t)); return t; }
DI void spin(uint32_t cyc) { const uint32_t t0 = clk(); while (__any_sync(~0u, clk() - t0 < cyc)) {} }
template <int NL> DI float2 poll_sum(const uint32_t* src, uint32_t tag, uint32_t even, uint32_t& g) {
  uint32_t r[NL];
  while (true) {
#pragma unroll
    for (int i = 0; i < NL; i++) r[i] = ld_rlx(src + i * 32);
    uint32_t bad = lop_or3(lop_bad(r[0], r[1], tag), lop_bad(r[2], r[3], tag), lop_bad(r[4], r[5], tag));
    if (NL == 12) bad = lop_or3(bad, lop_bad(r[6], r[7], tag), lop_bad(r[8], r[9], tag));
    asm volatile("lop3.b32 %0, %0, %1, %2, 0xa8;" : "+r"(bad) : "r"(lop_bad(r[NL - 2], r[NL - 1], tag)), "r"(even));
    if (!__any_sync(~0u, bad)) break;
    g++;
  }
  float x[NL / 2], y[NL / 2];
#pragma unroll
  for (int i = 0; i < NL / 2; i++) { x[i] = blo(r[2 * i]) + blo(r[2 * i + 1]); y[i] = bhi(r[2 * i]) + bhi(r[2 * i + 1]); }
  float2 u = make_float2((x[0] + x[1]) + (x[2] + x[3]), (y[0] + y[1]) + (y[2] + y[3]));
  if (NL == 12) { u.x += x[4] + x[5]; u.y += y[4] + y[5]; }
  return u;
}

constexpr int PLANE = 16 * 40 * 32, MAXPL = 13;
__device__ uint2 g_acc[(size_t)2 * NBLK * 2 * MAXPL * PLANE];
DI uint2* acc_planes(int lb, int d) { return g_acc + (size_t)((lb * 2 + d) * MAXPL) * PLANE; }
DI void ln_stats(const float4* v, uint32_t red, int warp, int lane, int bar, float& mean, float& rstd) {
  float s = 0.f;
#pragma unroll
  for (int i = 0; i < 5; i++) s += (v[i].x + v[i].y) + (v[i].z + v[i].w);
  s += __shfl_xor_sync(~0u, s, 1);
  s += __shfl_xor_sync(~0u, s, 2);
  s *= 1.f / 80;
  float q = 0.f;
#pragma unroll
  for (int i = 0; i < 5; i++) q += ((v[i].x - s) * (v[i].x - s) + (v[i].y - s) * (v[i].y - s)) + ((v[i].z - s) * (v[i].z - s) + (v[i].w - s) * (v[i].w - s));
  q += __shfl_xor_sync(~0u, q, 1);
  q += __shfl_xor_sync(~0u, q, 2);
  if ((lane & 3) == 0) asm volatile("st.shared.v2.f32 [%0], {%1,%2};" ::"r"(red + lane * 16 + warp * 8), "f"(s), "f"(q) : "memory");
  bar_sync(bar, 256);
  const uint4 t = lds128(red + lane * 16);
  const float m0 = __uint_as_float(t.x), m1 = __uint_as_float(t.z);
  mean = m0 + m1;
  mean += __shfl_xor_sync(~0u, mean, 1);
  mean += __shfl_xor_sync(~0u, mean, 2);
  mean *= 0.125f;
  q = __uint_as_float(t.y) + __uint_as_float(t.w) + 80.f * ((m0 - mean) * (m0 - mean) + (m1 - mean) * (m1 - mean));
  q += __shfl_xor_sync(~0u, q, 1);
  q += __shfl_xor_sync(~0u, q, 2);
  rstd = rsqrtf(q * (1.f / DM) + 1e-5f);
}
template <int SH, int STR> DI void store_img(uint32_t* dst, const float4* v, int warp, float mean, float rstd) {
#pragma unroll
  for (int i = 0; i < 5; i++) {
    const int U = 10 * warp + 2 * i;
    uint32_t* p = dst + (U >> SH) * STR + (U & ((1 << SH) - 1)) * 32;
    p[0] = pack2((v[i].x - mean) * rstd, (v[i].y - mean) * rstd);
    p[32] = pack2((v[i].z - mean) * rstd, (v[i].w - mean) * rstd);
  }
}
DI uint32_t* xn_row_group(int layer, int rg) { return (uint32_t*)(g_xn + (size_t)((layer * NSEG + (rg >> 2)) * 2560 + (rg & 3) * 128)); }

DI void first_ln(const uint32_t* a, int rg, uint32_t red, int warp, int lane, int bar) {
  float4 v[5];
#pragma unroll
  for (int i = 0; i < 5; i++) {
    v[i] = make_float4(blo(a[2 * i]), bhi(a[2 * i]), blo(a[2 * i + 1]), bhi(a[2 * i + 1]));
    acc_planes(rg >> 4, 0)[((rg & 15) * 40 + warp * 5 + i) * 32 + lane] = make_uint2(a[2 * i], a[2 * i + 1]);
  }
  float mean, rstd;
  ln_stats(v, red, warp, lane, bar, mean, rstd);
  store_img<4, 2048>(xn_row_group(0, rg) + lane, v, warp, mean, rstd);
}
#define QK_P0 32
#define QK_KB 0
struct QKOrder { int op[76]; };
__host__ __device__ constexpr QKOrder qk_order() {
  QKOrder o = {};
  int n = 0, k = 0, q = 0;
  for (; k < QK_P0; k++, q++) { o.op[n++] = 64 | k; o.op[n++] = q; }
  for (int i = 0; i < QK_KB; i++) o.op[n++] = 64 | k++;
  for (int i = 0; i < -QK_KB; i++) o.op[n++] = q++;
  const int nk = 40 - k, nq = 36 - q;
  for (int i = 0, dk = 0, dq = 0; i < nk + nq; i++) {
    if (dq * nk <= dk * nq + (QK_KB ? 0 : -nq) && dq < nq) { o.op[n++] = q++; dq++; } else if (dk < nk) { o.op[n++] = 64 | k++; dk++; } else { o.op[n++] = q++; dq++; }
  }
  return o;
}
__global__ void __launch_bounds__(512, 1)
r_kernel(const __grid_constant__ CUtensorMap mapWq, const __grid_constant__ CUtensorMap mapWk, const __grid_constant__ CUtensorMap mapWv,
         const __grid_constant__ CUtensorMap mapWo, const __grid_constant__ RParams prm) {
  const uint32_t sb = smem_base();
  const int wid = __shfl_sync(~0u, threadIdx.x >> 5, 0);
  const int lane0 = __shfl_sync(~0u, threadIdx.x & 31, threadIdx.x & 31);
  const int lane = lane0;
  const int warp = wid & 3, wg = wid >> 2;
  const uint32_t rank = blockIdx.x, head = blockIdx.y, cta = head * 3 + rank;
  const uint32_t peer1 = mapa(sb, rank == 2 ? 0 : rank + 1), peer2 = mapa(sb, rank == 0 ? 2 : rank - 1);
  const int nslots = prm.nslots;

  SLOG(0);
  if (threadIdx.x == 384) {
    if ((sb & 0x3FFFF) != SMEM0) __trap();
    for (int c = 0; c < 5; c++) { mbar_init(sb + B_HFULL + 8 * c, 2); mbar_init(sb + B_HEMPTY + 8 * c, c == 4 ? 8 : 4); }
    for (int c = 0; c < 11; c++) mbar_init(sb + B_MTRY + 8 * c, 1);
    mbar_init(sb + B_PTOK, rank == 0 ? 3 : 2); mbar_init(sb + B_OB, 5); mbar_init(sb + B_OPD, 4);
    mbar_init(sb + B_OPI, 1); mbar_init(sb + B_OPI + 8, 1); mbar_init(sb + B_RFREE, 1); mbar_init(sb + B_GATE, 1); mbar_init(sb + B_PMEM, 2); mbar_init(sb + B_PSUM, 2); mbar_init(sb + B_PVI, 5); mbar_init(sb + B_OTOK, 4); mbar_init(sb + B_OTOK + 8, 4); mbar_init(sb + B_END, 15);
    for (int c = 0; c < 4; c++) mbar_init(sb + B_PACE + 8 * c, 1);
    asm volatile("fence.mbarrier_init.release.cluster;" ::: "memory");
    fence_async_smem();
  }
  asm volatile("griddepcontrol.launch_dependents;");
  asm volatile("barrier.cluster.arrive.release.aligned;" ::: "memory");

  if (wg < 2) {
  {
    uint32_t xa[10];
    const uint32_t* src = prm.x + (size_t)(cta * 8 + (lane >> 2)) * (DM / 2) + wid * 40 + (lane & 3);
#pragma unroll
    for (int i = 0; i < 10; i++) xa[i] = __ldg(src + i * 4);
    asm volatile("barrier.cluster.wait.acquire.aligned;" ::: "memory");
    first_ln(xa, cta, sb + SM_SR, wid, lane, 8);
    bar_arrive(10, 288);
  }
  if (wg == 0) {
    asm volatile("setmaxnreg.inc.sync.aligned.u32 %0;" ::"n"(RG0));
    uint32_t wq[160];
    SLOG(1);
    mbar_wait(sb + B_W, 0);
    SLOG(2);
    {
      const uint32_t ld_off = ((lane >> 4) * 8 + (lane & 7)) * 128 + (((2 * warp + ((lane >> 3) & 1)) ^ (lane & 7)) << 4);
#pragma unroll
      for (int ks = 0; ks < 40; ks++) ldsm4t(wq + 4 * ks, sb + SM_WO + ks * 2048 + ld_off);
    }
    fence_async_smem();
    bar_arrive(5, 160);
    mbar_wait(sb + B_W + 16, 0);
    SLOG(3);
    const uint32_t st_addr = pin(sb + SM_QT + (lane >> 4) * 1024 + (2 * warp + ((lane >> 3) & 1)) * 128 + (lane & 7) * 16, lane);
    const uint32_t sq_addr = pin(sb + SM_QT + (2 + (lane & 3)) * QSTR + warp * 256 + (lane >> 2) * 16, lane);
    const uint32_t to_lo = warp == 0 ? peer1 : mapa(sb, warp == 2 ? 2 : 0), to_hi = warp == 0 ? peer2 : mapa(sb, warp == 1 ? 1 : 0);
    const uint32_t sr_off = SM_SR + warp * 1920 + rank * 640, sr_bar = B_SR + warp * 8;
    const uint32_t sa0 = pin(to_lo + sr_off + lane * 16, lane), sb0 = pin(to_lo + sr_bar, lane), sa1 = pin(to_lo + sr_off + 512 + lane * 4, lane), sb1 = pin(sb0, lane);
    const uint32_t sa2 = pin(to_hi + sr_off + lane * 16, lane), sb2 = pin(to_hi + sr_bar, lane), sa3 = pin(to_hi + sr_off + 512 + lane * 4, lane), sb3 = pin(sb2, lane);
    uint32_t nsolo = 0;
#pragma unroll 1
    for (int n = 0; n < nslots; n++) {
      const uint32_t par = n & 1;
      PROFA(warp == PW);
      const bool alt = prm.slot[n] & 128;
      auto next = [&](uint64_t& d, int ks) { if ((ks & 7) == 7) dstep<10240 - 7 * 256>(d); else dstep<256>(d); };
      auto store_k = [&](const float* ka) {
        stsm2(st_addr + (SM_KT - SM_QT), pack2(ka[0], ka[1]), pack2(ka[2], ka[3]));
        stsm4(st_addr + (SM_KT - SM_QT) + 1024, pack2(ka[4], ka[5]), pack2(ka[6], ka[7]), pack2(ka[8], ka[9]), pack2(ka[10], ka[11]));
        stsm4(st_addr + (SM_KT - SM_QT) + 3072, pack2(ka[12], ka[13]), pack2(ka[14], ka[15]), pack2(ka[16], ka[17]), pack2(ka[18], ka[19]));
      };
      auto store_qt = [&](const float* q) {
        sts128(sq_addr, make_uint4(pack2(q[0], q[1]), pack2(q[4], q[5]), pack2(q[8], q[9]), pack2(q[12], q[13])));
        sts128(sq_addr + 128, make_uint4(pack2(q[2], q[3]), pack2(q[6], q[7]), pack2(q[10], q[11]), pack2(q[14], q[15])));
      };
      if (n > 0 && ((prm.slot[n] >> 8) & 255) == n) {
        {
          float qt[16];
          uint64_t rh = prm.dHt;
          mbar_wait(sb + B_OPI + (par ^ 1) * 8, ((n - 1) >> 1) & 1);
          mbar_wait(sb + B_GATE, 1);
          spin(prm.dq);
          mbar_wait(sb + B_PVI, nsolo++ & 1);
          float kt[16];
          uint64_t rk = prm.dWK;
          wg_fence();
#pragma unroll
          for (int ks = 0; ks < 40; ks++) {
            wg_ss32k(kt, rk, rh, ks != 0);
            wg_rs32(qt, wq[4 * ks], wq[4 * ks + 1], wq[4 * ks + 2], wq[4 * ks + 3], rh, ks != 0);
            if (ks < 39) { dstep<2048>(rk); next(rh, ks); }
          }
          wg_commit();
          mbar_wait(sb + B_OPD, par ^ 1);
          wg_wait<0>();
          reg_fence<16>(qt); reg_fence<16>(kt);
          store_qt(qt);
          stsm4(st_addr + (SM_KT - SM_QT) + 1024, pack2(kt[0], kt[1]), pack2(kt[2], kt[3]), pack2(kt[4], kt[5]), pack2(kt[6], kt[7]));
          stsm4(st_addr + (SM_KT - SM_QT) + 3072, pack2(kt[8], kt[9]), pack2(kt[10], kt[11]), pack2(kt[12], kt[13]), pack2(kt[14], kt[15]));
        }
        float qm[4], km[4];
        uint64_t rk = prm.dWK, rh = prm.dH;
        bool ok = false;
#pragma unroll
        for (int g = 0; g < 20; g++) {
          if ((g & 3) == 0 && !ok) mbar_wait(sb + B_HFULL + 2 * g, par);
          if (g == 0) PROF(0);
          if ((g & 3) == 3 && g < 19) ok = mbar_test(sb + B_HFULL + 2 * (g + 1), par);
          if ((g & 3) == 0) wg_fence();
#pragma unroll
          for (int ks = 2 * g; ks < 2 * g + 2; ks++) {
            wg_ss8k(km, rk, rh, ks != 0);
            wg_rs8(qm, wq[4 * ks], wq[4 * ks + 1], wq[4 * ks + 2], wq[4 * ks + 3], rh, ks != 0);
            if (ks < 39) { dstep<2048>(rk); next(rh, ks); }
          }
          if (g == 18) wg_commit();
        }
        wg_commit();
        wg_wait<1>();
        bar_arrive(2, 256);
        wg_wait<0>();
        reg_fence<4>(qm); reg_fence<4>(km);
        PROF(9);
        stsm2(st_addr + (SM_KT - SM_QT), pack2(km[0], km[1]), pack2(km[2], km[3]));
        stsm2(st_addr, pack2(qm[0], qm[1]), pack2(qm[2], qm[3]));
      } else {
      float qa[20], ka[20];
      uint64_t rk = prm.dWK, rh = prm.dH, rq;
      auto K = [&](int ks) { wg_ss40<1, 0>(ka, rk, rh, ks != 0); };
      auto Q = [&](int ks, uint64_t db) { wg_rs40(qa, wq[4 * ks], wq[4 * ks + 1], wq[4 * ks + 2], wq[4 * ks + 3], db, ks != 0); };
      constexpr QKOrder ord = qk_order();
      auto first = [&](int g, int c) { for (int i = 0; i < 76; i++) if ((ord.op[i] & 63) >> 3 == c) return i >> 2 == g; return false; };
      bool ok = true;
      mbar_wait(sb + B_HFULL, par);
#pragma unroll
      for (int g = 0; g < 19; g++) {
        if (!ok) {
#pragma unroll
          for (int c = 1; c < 5; c++) if (first(g, c)) mbar_wait(sb + B_HFULL + 8 * c, par);
          mbar_wait(sb + B_GATE, 1);
        }
        if (g == 0) PROF(0);
        if (g < 18) ok = mbar_test(sb + B_GATE, 1);
#pragma unroll
        for (int c = 1; c < 5; c++) if (first(g + 1, c)) ok &= mbar_test(sb + B_HFULL + 8 * c, par);
        wg_fence();
#pragma unroll
        for (int i = 4 * g; i < 4 * g + 4; i++) {
          const int ks = ord.op[i] & 63;
          if (i < 2 * QK_P0) {
            if (ord.op[i] & 64) K(ks);
            else { Q(ks, rh); dstep<2048>(rk); next(rh, ks); if (i == 2 * QK_P0 - 1) rq = rh; }
          } else if (ord.op[i] & 64) { K(ks); if (ks < 39) { dstep<2048>(rk); next(rh, ks); } }
          else { Q(ks, rq); next(rq, ks); }
        }
        if (g == 17) wg_commit();
      }
      wg_commit();
#pragma unroll
      for (int ks = 36; ks < 40; ks++) { Q(ks, rq); if (ks < 39) dstep<256>(rq); }
      wg_commit();
      wg_wait<2>();
      if (alt) bar_arrive(2, 256);
      mbar_wait(sb + B_OPD, par ^ 1);
      wg_wait<1>();
      if (!alt) bar_arrive(2, 256);
      reg_fence<20>(ka);
      store_k(ka);
      wg_wait<0>();
      reg_fence<20>(qa);
      PROF(9);
      stsm2(st_addr, pack2(qa[0], qa[1]), pack2(qa[2], qa[3]));
      store_qt(qa + 4);
      }
      mbar_arrive_if(lane == 0, sb + B_HEMPTY + 32);
      fence_async_smem();
      bar_sync(1, 128);
      PROF(1);
      float qa[20];
      wg_fence();
#pragma unroll
      for (int k = 0; k < 4; k++) wg_ss40<1, 1>(qa, dadd(prm.dQT, k * 256), dadd(prm.dKT, k * 256), k != 0);
      wg_commit();
      bar_arrive(7, 256);
      wg_wait<0>();
      reg_fence<20>(qa);
      PROF(3);
      if (warp < 3) {
        uint32_t p[5];
#pragma unroll
        for (int j = 0; j < 5; j++) p[j] = pack2(qa[4 * j], qa[4 * j + 1]);
        if (warp == 0) {
          st_async4(sa0, p[0], p[1], p[2], p[3], sb0);
          st_async4(sa2, p[0], p[1], p[2], p[3], sb2);
          st_async1(sa1, p[4], sb1);
          st_async1(sa3, p[4], sb3);
          sts128(sb + sr_off + lane * 16, make_uint4(p[0], p[1], p[2], p[3]));
          sts32(sb + sr_off + 512 + lane * 4, p[4]);
          __syncwarp();
          mbar_expect_if(lane == 0, sb + B_SR, 1280);
        } else {
          uint32_t h[5];
#pragma unroll
          for (int j = 0; j < 5; j++) h[j] = pack2(qa[4 * j + 2], qa[4 * j + 3]);
          spin(prm.d3);
          st_async4(sa0, p[0], p[1], p[2], p[3], sb0);
          st_async4(sa2, h[0], h[1], h[2], h[3], sb2);
          st_async1(sa1, p[4], sb1);
          st_async1(sa3, h[4], sb3);
        }
      }
    }
  } else {
    asm volatile("setmaxnreg.inc.sync.aligned.u32 %0;" ::"n"(RG1));
    uint32_t wv[160];
    mbar_wait(sb + B_W + 8, 0);
    SLOG(4);
    {
      const uint32_t ld_off = ((lane >> 4) * 8 + (lane & 7)) * 128 + (((2 * warp + ((lane >> 3) & 1)) ^ (lane & 7)) << 4);
#pragma unroll
      for (int ks = 0; ks < 40; ks++) ldsm4t(wv + 4 * ks, sb + SM_WO + ks * 2048 + ld_off);
    }
    fence_async_smem();
    bar_arrive(6, 160);
    const uint64_t dH = prm.dH;
    uint32_t op[8];
    const uint32_t ob_off = SM_OB + (4 * rank + warp) * 256 + lane * 4;
    const uint32_t oa0 = pin(peer1 + ob_off, lane), ob0 = pin(peer1 + B_OB, lane), oa1 = pin(peer2 + ob_off, lane), ob1 = pin(peer2 + B_OB, lane);
    const uint32_t oa2 = pin(oa0 + 128, lane), ob2 = pin(ob0, lane), oa3 = pin(oa1 + 128, lane), ob3 = pin(ob1, lane);
    const uint32_t o_loc = pin(sb + ob_off, lane), rs_addr = pin(sb + SM_RS + (lane & 3) * 8, lane);
    const uint32_t tok_off = pin((cta * 1024 + 64 * warp + (lane ^ (lane >> 3))) * 16, lane), keep = pin((lane & 1) ? ~0u : ~1u, lane);
    const uint32_t pb_off = pin((8 * rank + 2 * warp) * 4096 + head * 128 + lane * 4, lane);
    const uint32_t ph_off = pin(72 * 4096 + 2 * warp * 12288 + cta * 64 + (lane & 2) * 3072 + (lane >> 2) * 8 + (lane & 1) * 4, lane);
    auto store_tok = [&](int m, int lane) {
      const uint32_t ls = prm.slot[m] & 127, sig = prm.slot[m] >> 16;
      uint4* dst = (uint4*)((char*)(g_oT + (size_t)((ls >> 2) * (96 * 1024) + (ls & 3) * 256)) + tok_off);
      dst[0] = make_uint4(op[0], op[1], op[2], op[3]);
      dst[32] = make_uint4(op[4], op[5], op[6], op[7]);
      __syncwarp();
      mbar_arrive_if(sig && lane == 0, sb + B_OTOK + (ls >> 6) * 8);
    };
#pragma unroll 1
    for (int n = 0; n < nslots; n++) {
      const uint32_t par = n & 1;
      const int lane = opaque(lane0);
      PROFA(warp == PW);
      float va[20];
      const bool alt = prm.slot[n] & 128;
      mbar_expect_if(warp == 0 && lane == 0, sb + B_PTOK, rank == 0 ? 1280 : 1920);
      bar_sync(2, 256);
#pragma unroll
      for (int g = 0; g < 10; g++) {
        wg_fence();
#pragma unroll
        for (int ks = 4 * g; ks < 4 * g + 4; ks++) { wg_rs40(va, wv[4 * ks], wv[4 * ks + 1], wv[4 * ks + 2], wv[4 * ks + 3], dadd(dH, hoff(ks)), ks != 0); }
        wg_commit();
        if (g >= 2 && !(g & 1)) {
          wg_wait<1>();
          if (lane == 0) mbar_arrive(sb + B_HEMPTY + 8 * (g / 2 - 1));
        }
        if (g == 1 ? !alt : g == 2 && alt) bar_sync(7, 256);
      }
      wg_wait<0>();
      reg_fence<20>(va);
      if (lane == 0) mbar_arrive(sb + B_HEMPTY + 32);
      PROF(10);
      uint32_t vf[10];
#pragma unroll
      for (int j = 0; j < 10; j++) {
        const int i = (j + 4) % 10;
        asm volatile("cvt.rn.bf16x2.f32 %0, %1, %2;" : "=r"(vf[i]) : "f"(va[2 * i + 1]), "f"(va[2 * i]));
        if (j == 5) mbar_wait(sb + B_W + 8, 0);
      }
      uint32_t z0, z1;
      asm volatile("shr.u32 %0, %2, 5; shr.u32 %1, %2, 6;" : "=r"(z0), "=r"(z1) : "r"(lane));
      const uint32_t info = prm.slot[n];
      const uint32_t tagbit = ~(info >> 1) & ~keep;
      char* const ring = (char*)(g_part + (size_t)((((info >> 5) & 2) + (info & 1)) * PART_RING));
      char* const pb = pin(ring + pb_off, lane);
      char* const ph = ring + ph_off;
      mbar_wait(sb + B_PMEM, par);
      float om[4];
      wg_fence();
      wg_rs8(om, vf[0], vf[1], vf[2], vf[3], prm.dP, 0);
      wg_rs8(om, vf[4], vf[5], vf[6], vf[7], dadd(prm.dP, 256), 1);
      wg_rs8(om, vf[8], vf[9], z0, z1, dadd(prm.dP, 512 - (128 << 16)), 1);
      wg_commit();
      {
        wg_wait<0>();
        reg_fence<4>(om);
        const uint32_t b0 = pack2(om[0], om[1]), b1 = pack2(om[2], om[3]);
        st_async1(oa0, b0, ob0);
        st_async1(oa1, b0, ob1);
        st_async1(oa2, b1, ob2);
        st_async1(oa3, b1, ob3);
        sts32(o_loc, b0);
        sts32(o_loc + 128, b1);
        fence_async_smem();
        __syncwarp();
        mbar_arrive_if(lane == 0, sb + B_OB);
      }
      PROF(11);
      {
        float c[8];
        mbar_wait(sb + B_PSUM, par);
        const uint2 rs = lds64(rs_addr);
        const float r0 = __uint_as_float(rs.x), r1 = __uint_as_float(rs.y);
        if (n == 0) { SLOG(5); mbar_wait(sb + B_W + 24, 0); SLOG(6); }
        mbar_wait(sb + B_OB, par);
        asm volatile("fence.proxy.async::generic.acquire.sync_restrict::shared::cluster.cluster;" ::: "memory");
        PROF(16);
        if ((info & 63) == NSEG - 1) {
          mbar_wait(sb + B_OPI + par * 8, (n >> 1) & 1);
          mbar_arrive_if(warp == 3 && lane == 0, sb + B_GATE);
#pragma unroll
          for (int p = 0; p < 6; p++) st_rlx1(pb + (p >> 1) * 98304 + (p & 1) * 4096, tagbit);
          st_rlx1(ph, tagbit);
          st_rlx1(ph + 12288, tagbit);
        } else {
#pragma unroll
        for (int p = 0; p < 4; p++) {
          float* const cur = c + 4 * (p & 1);
          float* const prv = c + 4 * (~p & 1);
          if (p == 2) mbar_wait(sb + B_OPI + par * 8, (n >> 1) & 1);
          wg_fence();
#pragma unroll
          for (int ks = 0; ks < (p < 3 ? 12 : 4); ks++) {
            wg_ss8(cur, dadd(prm.dWO, p * 24576 + ks * 2048), dadd(prm.dOB[p < 3 ? p : 3 + rank], ks * 256), ks != 0);
            if (p == 3 && ks == 3) mbar_arrive_if(warp == 3 && lane == 0, sb + B_GATE);
            if (p > 0 && ks == 3) {
              wg_commit();
              wg_wait<1>();
              reg_fence<4>(prv);
              st_tagged(pb + (p - 1) * 98304, prv[0] * r0, prv[1] * r1, keep, tagbit);
              st_tagged(pb + (p - 1) * 98304 + 4096, prv[2] * r0, prv[3] * r1, keep, tagbit);
            }
          }
          if (p < 3) wg_commit();
        }
        wg_wait<0>();
        reg_fence<4>(c + 4);
        st_tagged(ph, c[4] * r0, c[5] * r1, keep, tagbit);
        st_tagged(ph + 12288, c[6] * r0, c[7] * r1, keep, tagbit);
        }
        PROF(17);
      }
      mbar_wait(sb + B_PTOK, par);
      PROF(12);
      {
        float ot[16];
        wg_fence();
        wg_rs32(ot, vf[0], vf[1], vf[2], vf[3], dadd(prm.dP, 640), 0);
        wg_rs32(ot, vf[4], vf[5], vf[6], vf[7], dadd(prm.dP, 640 + 256), 1);
        wg_rs32(ot, vf[8], vf[9], z0, z1, dadd(prm.dP, 640 + 512 - (128 << 16)), 1);
        wg_commit();
        wg_wait<0>();
        reg_fence<16>(ot);
#pragma unroll
        for (int i = 0; i < 8; i++) op[(i & 1) * 4 + (i >> 1)] = pack2(ot[2 * i], ot[2 * i + 1]);
      }
      if (lane == 0) mbar_arrive(sb + B_OPD);
      PROF(13);
      if (info & 128) spin(prm.ds);
      store_tok(n, lane);
    }
  }
  } else if (wg == 2) {
    asm volatile("setmaxnreg.dec.sync.aligned.u32 %0;" ::"n"(RG2));
    asm volatile("barrier.cluster.wait.acquire.aligned;" ::: "memory");
    if (warp == 1) {
      const uint32_t depth = prm.pf & 7;
#pragma unroll 1
      for (uint32_t i = 0; i < 20 + depth; i++) {
        if (i >= depth) {
          const uint32_t j = i - depth;
          mbar_wait_wd(sb + B_PACE + 8 * (j & 3), (j >> 2) & 1);
          if (j % 5 == 4) mbar_arrive_if(lane == 0 && (j != 14 || depth == 1), sb + B_W + (j == 4 ? 0 : j == 9 ? 16 : j == 14 ? 8 : 24));
        }
        if (i >= 20) continue;
        const uint32_t m = i / 5, k = i % 5, bar = sb + B_PACE + 8 * (i & 3);
        if (i == 10) bar_sync(5, 160);
        if (i == 15) {
          if ((prm.pf & 8) && elect_one())
            for (int q = 0; q < 4; q++) tma_pf(&mapWo, (q / 3 * 3 + rank) * 64, head * DH + q % 3 * 64);
#pragma unroll 1
          for (uint32_t j = 16 - depth; j < 15; j++) mbar_wait_wd(sb + B_PACE + 8 * (j & 3), (j >> 2) & 1);
          mbar_arrive_if(lane == 0 && depth > 1, sb + B_W + 8);
          bar_sync(6, 160);
        }
        if (elect_one()) {
          mbar_expect(bar, 16384);
          if (m < 3) tma_2d(sb + (m == 1 ? SM_WK : SM_WO) + k * 16384, m == 0 ? &mapWq : m == 1 ? &mapWk : &mapWv, cta * 64, k * 128, bar);
          else
            for (uint32_t q = 2 * k; q < 2 * k + 2; q++)
              tma_2d(sb + SM_WO + q * 8192, &mapWo, q < 9 ? (q / 3 * 3 + rank) * 64 : 576, head * DH + (q < 9 ? q % 3 : rank) * 64, bar);
        }
      }
    }
    if (warp == 2 && cta < 80 && lane < 16)
      g_mem[(cta >> 4) * 2048 + (lane >> 3) * 1024 + prm.moff + (cta & 15) * 8 + (lane & 7)] = prm.mem0[(lane & 7) * 80 + cta];
    if (warp == 3) {
      bar_sync(10, 288);
      if (lane == 0) red_rel(&g_cnt[(C_XN + (cta >> 4)) * CSTRIDE], 8);
    }
    const uint32_t grp = warp == 1 ? 1 + rank : 4 - (rank >> 1);
    constexpr float SC = 0.07216878364870322f * 1.4426950408889634f;
    const bool split = cta >= 72;
    const uint32_t wd = split ? 72 * 16 + cta * 16 : cta * 32;
    const uint32_t src_off = pin(split ? 72 * 4096 + (cta - 72) * 6144 + warp * 1536 + (lane & 2) * 32 + (lane >> 2) * 8 + (lane & 1) * 4 : cta * 4096 + warp * 1024 + lane * 4, lane);
    const uint32_t dst_off = pin(((wd >> 9) * 8192 + prm.moff * 4 + (wd & 511) + lane) * 4, lane);
    const uint32_t red = pin(sb + SM_RED + (warp < 2 ? 0 : (warp - 1) * 256) + lane * 8, lane);
    const uint32_t fl = (warp & 2) * 8 + (lane >> 3) * 4 + (lane & 3), hf = lane & 4;
    const uint32_t s0 = pin(sb + SM_SR + fl * 16 + hf * 2, lane), s1 = pin(sb + fl * 4, lane), pd = pin(s1 + hf * 64, lane);
    const uint32_t even = pin(~lane & 1, lane);
    uint32_t nred = 0;
    const uint32_t arm = pin(warp == 0 && (lane == 5 || ((lane == 1 || lane == 2) && lane + rank != 3)) ? sb + B_SR + lane * 8 : 0, lane);
#pragma unroll 1
    for (int n = 0; n < nslots; n++) {
      const uint32_t par = n & 1;
      const int lane = opaque(lane0);
      PROFA(warp == PW2);
      const uint32_t info = prm.slot[n], s = info & 63, l = (info >> 6) & 1;
      {
        mbar_expect_if(arm, arm, lane == 5 ? 2048 : 1920);
        if (warp == 0 || warp == 3) {
          mbar_wait(sb + B_SR, par);
          PROF(4);
          const uint2 a0 = lds64(s0), a1 = lds64(s0 + 640), a2 = lds64(s0 + 1280);
          const uint32_t b0 = lds32(s1 + SM_SR + 512), b1 = lds32(s1 + SM_SR + 1152), b2 = lds32(s1 + SM_SR + 1792);
          float v[6];
          v[0] = blo(a0.x) + blo(a1.x) + blo(a2.x); v[1] = bhi(a0.x) + bhi(a1.x) + bhi(a2.x);
          v[2] = blo(a0.y) + blo(a1.y) + blo(a2.y); v[3] = bhi(a0.y) + bhi(a1.y) + bhi(a2.y);
          v[4] = blo(b0) + blo(b1) + blo(b2); v[5] = bhi(b0) + bhi(b1) + bhi(b2);
          float m = fmaxf(fmaxf(v[0], v[1]), fmaxf(v[2], v[3]));
          m = fmaxf(fmaxf(m, __shfl_xor_sync(~0u, m, 4)), fmaxf(v[4], v[5]));
          {
            const float m1 = __shfl_xor_sync(~0u, m, 1), m2 = __shfl_xor_sync(~0u, m, 2), m3 = __shfl_xor_sync(~0u, m, 3);
            m = fmaxf(fmaxf(m, m1), fmaxf(m2, m3));
          }
          const float ms = -m * SC;
#pragma unroll
          for (int i = 0; i < 6; i++) v[i] = ex2(fmaf(v[i], SC, ms));
          float sum = (v[0] + v[1]) + (v[2] + v[3]);
          const float so = __shfl_xor_sync(~0u, sum, 4);
          sts32(pd + SM_P, pack2(v[0], v[1]));
          sts32(pd + SM_P + 128, pack2(v[2], v[3]));
          sts32(s1 + SM_P + 512, pack2(v[4], v[5]));
          fence_async_smem();
          __syncwarp();
          mbar_arrive_if(lane == 0, sb + B_PMEM);
          PROF(5);
          sum += so + (v[4] + v[5]);
          {
            const float t1 = __shfl_xor_sync(~0u, sum, 1), t2 = __shfl_xor_sync(~0u, sum, 2), t3 = __shfl_xor_sync(~0u, sum, 3);
            sum = (sum + t1) + (t2 + t3);
          }
          float r;
          asm("rcp.approx.ftz.f32 %0, %1;" : "=f"(r) : "f"(sum));
          sts32(sb + SM_RS + (warp & 2) * 8 + (lane >> 3) * 4, __float_as_uint(r));
          __syncwarp();
          mbar_arrive_if(lane == 0, sb + B_PSUM);
        } else {
          if (warp + rank != 3) {
            const uint32_t src = sb + SM_SR + warp * 1920;
            mbar_wait(sb + B_SR + warp * 8, par);
            const uint4 a0 = lds128(src + lane * 16), a1 = lds128(src + 640 + lane * 16), a2 = lds128(src + 1280 + lane * 16);
            const uint32_t b0 = lds32(src + 512 + lane * 4), b1 = lds32(src + 1152 + lane * 4), b2 = lds32(src + 1792 + lane * 4);
            float v[10];
            v[0] = blo(a0.x) + blo(a1.x) + blo(a2.x); v[1] = bhi(a0.x) + bhi(a1.x) + bhi(a2.x);
            v[2] = blo(a0.y) + blo(a1.y) + blo(a2.y); v[3] = bhi(a0.y) + bhi(a1.y) + bhi(a2.y);
            v[4] = blo(a0.z) + blo(a1.z) + blo(a2.z); v[5] = bhi(a0.z) + bhi(a1.z) + bhi(a2.z);
            v[6] = blo(a0.w) + blo(a1.w) + blo(a2.w); v[7] = bhi(a0.w) + bhi(a1.w) + bhi(a2.w);
            v[8] = blo(b0) + blo(b1) + blo(b2); v[9] = bhi(b0) + bhi(b1) + bhi(b2);
            {
              const int lim = 6 + 2 * grp + (lane & 24) + ((lane >> 2) & 1) - 2 * (lane & 3);
#pragma unroll
              for (int i = 2; i < 10; i++) if ((i >> 1) * 8 + (i & 1) > lim) v[i] = -INFINITY;
            }
            float m = fmaxf(fmaxf(fmaxf(v[0], v[1]), fmaxf(v[2], v[3])), fmaxf(fmaxf(v[4], v[5]), fmaxf(v[6], v[7])));
            m = fmaxf(m, fmaxf(v[8], v[9]));
            {
              const float m1 = __shfl_xor_sync(~0u, m, 1), m2 = __shfl_xor_sync(~0u, m, 2), m3 = __shfl_xor_sync(~0u, m, 3);
              m = fmaxf(fmaxf(m, m1), fmaxf(m2, m3));
            }
            const float ms = -m * SC;
#pragma unroll
            for (int i = 0; i < 10; i++) v[i] = ex2(fmaf(v[i], SC, ms));
            float sum = ((v[0] + v[1]) + (v[2] + v[3])) + ((v[4] + v[5]) + (v[6] + v[7])) + (v[8] + v[9]);
            {
              const float s1 = __shfl_xor_sync(~0u, sum, 1), s2 = __shfl_xor_sync(~0u, sum, 2), s3 = __shfl_xor_sync(~0u, sum, 3);
              sum = (sum + s1) + (s2 + s3);
            }
            float r;
            asm("rcp.approx.ftz.f32 %0, %1;" : "=f"(r) : "f"(sum));
            {
              const uint32_t row = SM_P + grp * 640;
#pragma unroll
              for (int j = 0; j < 5; j++) sts32(sb + row + j * 128 + lane * 4, pack2(v[2 * j] * r, v[2 * j + 1] * r));
              fence_async_smem();
              __syncwarp();
              mbar_arrive_if(lane == 0, sb + B_PTOK);
              if (elect_one()) {
                bulk_s2s(peer1 + row, sb + row, 640, peer1 + B_PTOK);
                bulk_s2s(peer2 + row, sb + row, 640, peer2 + B_PTOK);
              }
            }
          }
        }
      }
      const uint32_t* const src = (const uint32_t*)((char*)(g_part + (size_t)((l * 2 + (s & 1)) * PART_RING)) + src_off);
      uint32_t* const dst = (uint32_t*)pin((char*)(g_mem + l * 1024 + (~s & 1) * 512) + dst_off, lane);
      {
        const uint32_t d1 = prm.d1[cta / 24 + ((info >> 5) & 4)];
        if (warp == 3) {
          mbar_wait(sb + B_OB, par);
          mbar_arrive_if(lane == 0, sb + B_GATE);
          sts32(sb + SM_TOPI + par * 4, clk());
          __syncwarp();
          mbar_arrive_if(lane == 0, sb + B_OPI + par * 8);
          TRACE(true, n, 0, gtl());
        }
        const bool reduce = cta < 88 && s != NSEG - 1;
        if (reduce || warp == 0) mbar_wait(sb + B_OPI + par * 8, (n >> 1) & 1);
        if (!reduce) continue;
        mbar_wait(sb + B_RFREE, (nred++ & 1) ^ 1);
        mbar_wait(sb + B_GATE, 1);
        if (d1) spin(d1);
      }
      {
        uint32_t g = 0;
        float2 u;
        PROF(14);
        if (!split) {
          u = poll_sum<8>(src, ~(s >> 1), even, g);
        } else {
          u = poll_sum<12>(src, ~(s >> 1), even, g);
          u.x += __shfl_xor_sync(~0u, u.x, 2);
          u.y += __shfl_xor_sync(~0u, u.y, 2);
        }
        PROF(18);
        if (warp != 1) {
          asm volatile("st.shared.v2.f32 [%0], {%1,%2};" ::"r"(red), "f"(u.x), "f"(u.y) : "memory");
          bar_arrive(3, 128);
        } else {
          bar_sync(3, 128);
          const uint2 o0 = lds64(red), o1 = lds64(red + 256), o2 = lds64(red + 512);
          const uint32_t w = movm(pack2((u.x + __uint_as_float(o0.x)) + (__uint_as_float(o1.x) + __uint_as_float(o2.x)),
                                        (u.y + __uint_as_float(o0.y)) + (__uint_as_float(o1.y) + __uint_as_float(o2.y))));
          if (!split || lane < 16) {
            st_rlx1(dst, w);
            st_rlx1(dst + ((s & 1) ? 2048 : -2048), ~0u);
          }
          mbar_arrive_if(lane == 0, sb + B_RFREE);
        }
        PROF(19);
        PROFV(2, g);
        TRACE(warp == 1, n, 1, gtl());
        TRACE(g, n, 2, g);
      }
    }
  } else {
    asm volatile("setmaxnreg.dec.sync.aligned.u32 %0;" ::"n"(RG3));
    asm volatile("barrier.cluster.wait.acquire.aligned;" ::: "memory");
    const uint32_t chk = lane * 32 + ((lane >> 2) << 2);
    const uint32_t bar = sb + B_MTRY + 8 * warp;
    uint32_t mph = 0, waited = 0, pub = 0, pph = 0, nsolo = 0;
    auto publish = [&](uint32_t upto) {
#pragma unroll 1
      for (; pub < upto; pub++) {
        const uint32_t e = prm.slot[pub], l = (e >> 6) & 1;
        if (warp == 3 && (e >> 16)) {
          mbar_wait_wd(sb + B_OTOK + l * 8, (pph >> l) & 1);
          pph ^= 1 << l;
          if (elect_one()) red_rel(&g_cnt[(e >> 16) * CSTRIDE], 1);
        }
      }
    };
#pragma unroll 1
    for (int m = 0; m < nslots; m++) {
      const uint32_t info = prm.slot[m], prod = (info >> 8) & 255, ls = info & 127;
      uint32_t g = 0;
#pragma unroll 1
      for (; waited < prod && waited + 1 < m; waited++) mbar_wait_wd(sb + B_OPI + (waited & 1) * 8, (waited >> 1) & 1);
      uint32_t t0 = lds32(sb + SM_TOPI + (~waited & 1) * 4);
      publish(waited);
      if ((ls & 3) == 0) {
        while (__any_sync(~0u, ld_acq(&g_cnt[(C_XN + (ls >> 2)) * CSTRIDE]) < XN_TARGET)) guard(g);
        fence_async_global();
      }
#pragma unroll 1
      for (uint32_t c = warp; c < 5; c += 4) {
        const uint32_t dst = sb + SM_H + c * 10240, full = sb + B_HFULL + 8 * c;
        const uint4* src = g_mem + (c * 2048 + (ls >> 6) * 1024 + (ls & 1) * 512 + prm.moff);
        const uint32_t d = prod ? prm.d2[(m - prod) * 5 + c] : 0;
        const uint4* tok = g_xn + (size_t)(ls * 2560 + c * 512);
        const uint32_t pp = (m & 1) ^ 1;
        const bool single = waited < prod;
        mbar_wait_wd(full, pp);
        const bool solo = m > 0 && prod == m;
        const uint32_t tokb = solo ? sb + B_PVI : full;
        if (solo && c < 4) mbar_wait_wd(tokb, (nsolo++ & 1) ^ 1);
        mbar_expect_if(lane < 2 && !(solo && c == 4 && lane == 0), lane ? bar : tokb, lane ? 2048 : 8192);
        if (!single) while (__any_sync(~0u, clk() - t0 < d)) {}
        if (c >= 2) mbar_wait_wd(sb + B_HEMPTY + 8 * c, pp);
        mbar_wait_wd(sb + (c < 2 ? B_HEMPTY + 8 * c : c == 2 && !single ? B_PMEM : B_OB), pp);
        if ((c != 2 || single) && !(solo && c == 4)) { if (elect_one()) bulk_g2s(dst + 2048, tok, 8192, tokb); }
        if (single) {
          mbar_wait_wd(sb + B_OPI + (waited & 1) * 8, (waited >> 1) & 1);
          waited++;
          t0 = lds32(sb + SM_TOPI + (~waited & 1) * 4);
          if (solo && c == 0 && elect_one()) {
            mbar_expect(tokb, 8192);
            bulk_g2s(dst + 4 * 10240 + 2048, tok + 2048, 8192, tokb);
          }
          publish(waited);
          while (__any_sync(~0u, clk() - t0 < d)) {}
        }
        else if (c < 2) spin(prm.dh);
        if (elect_one()) bulk_g2s(dst, src, 2048, bar);
        if (c == 2 && !single) {
          mbar_wait_wd(sb + B_OB, pp);
          if (elect_one()) bulk_g2s(dst + 2048, tok, 8192, full);
        }
        g = 0;
        while (true) {
          mbar_wait_wd(bar, mph);
          mph ^= 1;
          const uint32_t v0 = lds32(dst + chk), v1 = lds32(dst + chk + 1024);
          if (__all_sync(~0u, v0 != ~0u && v1 != ~0u)) break;
          if (elect_one()) {
            mbar_expect(bar, 2048);
            bulk_g2s(dst, src, 2048, bar);
          }
          guard(g);
        }
        mbar_arrive_if(lane == 0, full, solo ? 2 : 1);
        TRACE(c < 2, m, 3 + 2 * c, gtl());
        TRACE(c < 2, m, 4 + 2 * c, g);
      }
    }
    publish(nslots);
    if (warp == 0) mbar_wait_wd(sb + B_END, 0);
  }
  __syncwarp();
  if (wid != 12 && lane0 == 0) mbar_arrive(sb + B_END);
  cluster_sync();
}
__device__ uint32_t g_xa[NBLK * 10 * 4096];
__device__ uint32_t g_h[NBLK * 24 * 4096];

enum { T_A = 0, T_F1 = 1, T_U = 2, T_D = 3, T_F2 = 4, T_NONE = 7 };
__host__ __device__ constexpr int c_phase(int type, int lb) { return C_O + type * 32 + lb; }
constexpr int C_TICKET = c_phase(5, 0), C_EXIT = C_TICKET + 1, C_USED = C_HALF + 2 * NBLK;
constexpr int G_NST = 7;
constexpr uint32_t GS_RED = G_NST * 32768, GS_BAR = GS_RED + 1088, G_SMEM = GS_BAR + 224;
constexpr uint32_t GB_FULL = GS_BAR, GB_EMPTY = GS_BAR + 64, GB_ORD = GS_BAR + 128, GB_READY = GS_BAR + 144, GB_ACK = GS_BAR + 152, GB_GATE = GS_BAR + 160, GB_SIG = GS_BAR + 176, GB_SACK = GS_BAR + 192,
                   GS_SIG = GS_BAR + 208, GS_COL = GS_BAR + 216;
#define FPL 6
constexpr int NF = 16;
constexpr int G_EARLY = 36;
constexpr int G_LATE = 96, PL = 6, ML = 8, DL = 30, TL = 10;
constexpr int GRC = 112, GRP = 32;
constexpr uint32_t E_UP = 1u << 8, E_HALF = 1u << 28, E_GRP = 1u << 29, E_HAND = 1u << 30, E_EXCL = 1u << 31;

struct GParams {
  __nv_bfloat16* out;
  const uint32_t* x;
  int moff, gd;
  int pend;
  uint8_t perm[G_EARLY], first[9];
  uint8_t need[5][2 * NBLK];
  uint32_t tab[G_EARLY * (PL + ML + DL) + G_LATE * TL];
};
constexpr int EL = PL + ML + DL, TAB_TAIL = G_EARLY * EL;
struct GIter {
  int p, left, period;
  uint32_t e, type, lb, n0, kb0, nkb;
  bool gemm, valid;
  DI GIter(const GParams& prm, int col) {
    if (col < G_EARLY) { p = col * EL; left = PL; period = 0; }
    else { p = TAB_TAIL + (col - G_EARLY) * TL; left = TL; period = prm.pend; }
  }
  DI bool next(const GParams& prm, int col) {
    do {
      if (left == 0) {
        if (++period > prm.pend) return false;
        left = period < prm.pend ? ML : DL;
        if (period > 1 && period < prm.pend) p -= ML;
      }
      e = prm.tab[p++]; left--;
    } while ((e & 7) == T_NONE);
    const int b = (e >> 4) & 15, blk = period < prm.pend ? period - b : b;
    type = e & 7; valid = blk >= 0; lb = (e & 8) * 2 + (blk & 15); n0 = (e >> 9) & 127; kb0 = (e >> 16) & 127;
    gemm = type != T_F1 && type != T_F2;
    nkb = valid ? (e >> 23) & 31 : 0;
    return true;
  }
  DI int id_(int pend) const { return period < pend ? period * 10 + ML - left : 160 + DL - left; }
};

#define GLOG(nt, i, v)
template <int TA> DI void wg_ss128(float* d, uint64_t da, uint64_t db, int sc) {
  asm volatile("{.reg .pred p; setp.ne.b32 p, %66, 0;\n"
               "wgmma.mma_async.sync.aligned.m64n128k16.f32.bf16.bf16 "
               "{%0,%1,%2,%3,%4,%5,%6,%7,%8,%9,%10,%11,%12,%13,%14,%15,%16,%17,%18,%19,%20,%21,%22,%23,%24,%25,%26,%27,%28,%29,%30,%31,"
               "%32,%33,%34,%35,%36,%37,%38,%39,%40,%41,%42,%43,%44,%45,%46,%47,%48,%49,%50,%51,%52,%53,%54,%55,%56,%57,%58,%59,%60,%61,%62,%63}, "
               "%64, %65, p, 1, 1, %67, 1;}"
               : ACC16(d, 0), ACC16(d, 16), ACC16(d, 32), ACC16(d, 48) : "l"(da), "l"(db), "r"(sc), "n"(TA));
}

template <int TA> DI void g_mainloop(float* acc, uint32_t sb, uint32_t hand, uint32_t gate, int nkb, int cw, int lane, uint32_t st, uint32_t ph) {
  const uint64_t da0 = (TA ? mkdesc(SMEM0, 4096, 512, 2) : mkdesc(SMEM0, 128, 1024, 0)) + (cw >> 2) * 512;
  const uint64_t db0 = mkdesc(SMEM0 + 16384, 8192, 1024, 1);
  uint32_t prev = 0;
#pragma unroll 1
  for (int kb = 0; kb < nkb; kb++) {
    mbar_wait(sb + GB_FULL + 8 * st, ph);
    mbar_wait(gate, 1);
    const uint64_t da = da0 + st * 2048, db = db0 + st * 2048;
    wg_fence();
#pragma unroll
    for (int k = 0; k < 4; k++) wg_ss128<TA>(acc, da + k * (TA ? 64 : 16), db + k * 128, 1);
    wg_commit();
    mbar_arrive_if(hand && kb == nkb - 1 && lane == 0, hand);
    wg_wait<1>();
    mbar_arrive_if(kb > 0 && lane == 0, sb + GB_EMPTY + 8 * prev);
    prev = st;
    if (++st == G_NST) { st = 0; ph ^= 1; }
  }
  wg_wait<0>();
  reg_fence<64>(acc);
  mbar_arrive_if(lane == 0, sb + GB_EMPTY + 8 * prev);
}

__global__ void __launch_bounds__(640, 1)
g_kernel(const __grid_constant__ CUtensorMap mapWo, const __grid_constant__ CUtensorMap mapWg, const __grid_constant__ CUtensorMap mapWu,
         const __grid_constant__ CUtensorMap mapWd, const __grid_constant__ GParams prm) {
  const uint32_t sb = smem_base();
  const int wid = __shfl_sync(~0u, threadIdx.x >> 5, 0), lane = threadIdx.x & 31;
  if (threadIdx.x == 0) {
    if ((sb & 0x3FFFF) != SMEM0) __trap();
    {
      uint32_t sm; asm volatile("mov.u32 %0, %%smid;" : "=r"(sm));
      uint32_t* const tk = &g_cnt[C_TICKET * CSTRIDE];
      uint32_t c = atomicAdd(tk, 1);
      if (c < G_EARLY) {
        const uint32_t k = sm < 64 ? (sm >> 1) & 7 : sm < 120 ? 1 + ((sm - 64) >> 1) % 7 : sm < 124 ? 1 + ((sm >> 1) & 1) : 0;
        const uint32_t t = atomicAdd(tk + 1 + k, 1);
        atomicAdd(tk + 9, 1);
        if (t < prm.first[k + 1] - prm.first[k]) c = prm.perm[prm.first[k] + t];
        else {
          uint32_t o = atomicAdd(tk + 10, 1), g = 0;
          while (ld_acq(tk + 9) < G_EARLY) guard(g);
          for (int j = 0; j < 8; j++)
            for (uint32_t i = prm.first[j] + ld_acq(tk + 1 + j); i < prm.first[j + 1]; i++) if (o-- == 0) c = prm.perm[i];
        }
      }
      sts32(sb + GS_COL, c);
    }
    for (int i = 0; i < G_NST; i++) { mbar_init(sb + GB_FULL + 8 * i, 1); mbar_init(sb + GB_EMPTY + 8 * i, 8); }
    mbar_init(sb + GB_ORD, 8); mbar_init(sb + GB_ORD + 8, 8); mbar_init(sb + GB_READY, 1); mbar_init(sb + GB_ACK, 1);
    mbar_init(sb + GB_GATE, 1); mbar_init(sb + GB_GATE + 8, 1);
    mbar_init(sb + GB_SIG, 8); mbar_init(sb + GB_SIG + 8, 8); mbar_init(sb + GB_SACK, 1); mbar_init(sb + GB_SACK + 8, 1);
    fence_async_smem();
  }
  __syncthreads();
  const int col = __shfl_sync(~0u, lds32(sb + GS_COL), 0);

  if (wid >= 16) {
    GIter t(prm, col);
    asm volatile("setmaxnreg.dec.sync.aligned.u32 %0;" ::"n"(GRP));
    uint32_t st = 0, ph = 1, k = 0;
    if (wid == 16) {
      while (t.next(prm, col)) {
        const CUtensorMap* m0 = t.type == T_A ? &mapWo : t.type == T_U ? &mapWg : &mapWd;
        const CUtensorMap* m1 = t.type == T_U ? &mapWu : m0;
        const int c0 = t.type == T_U ? t.n0 * 64 : (t.n0 & 7) * 128, c1 = t.type == T_U ? c0 : c0 + 64;
        if ((t.e & (E_HALF | E_UP)) == E_UP) poll_ge(&g_cnt[c_phase(t.type, t.lb) * CSTRIDE], prm.need[t.type][t.lb]);
#pragma unroll 1
        for (uint32_t kb = t.kb0; kb < t.kb0 + t.nkb; kb++) {
          mbar_wait(sb + GB_EMPTY + 8 * st, ph);
          if (elect_one()) {
            const uint32_t full = sb + GB_FULL + 8 * st, dst = sb + st * 32768;
            mbar_expect(full, (t.e & E_HALF) ? 24576 : 32768);
            tma_2d(dst + 16384, m0, c0, kb * 64, full);
            tma_2d(dst + 24576, m1, c1, kb * 64, full);
          }
          if (++st == G_NST) { st = 0; ph ^= 1; }
        }
      }
    } else if (wid == 17) {
      while (t.next(prm, col)) {
        if (!t.nkb) continue;
        const char* asrc = t.type == T_A ? (const char*)g_oT + (size_t)t.lb * (96 * 16384)
                         : t.type == T_U ? (const char*)g_xa + (size_t)(t.lb & 15) * (10 * 16384) : (const char*)g_h + (size_t)(t.lb & 15) * (24 * 16384);
        const uint32_t up = (t.e & E_HALF) ? (t.e & E_UP) * 32 : 0;
        GLOG(t.id_(prm.pend), 1, gtime());
        mbar_wait(sb + GB_READY, k & 1);
        mbar_arrive_if(lane == 0, sb + GB_ACK);
        k++;
#pragma unroll 1
        for (uint32_t kb = t.kb0; kb < t.kb0 + t.nkb; kb++) {
          mbar_wait(sb + GB_EMPTY + 8 * st, ph);
          if (elect_one()) bulk_g2s(sb + st * 32768 + up, asrc + (size_t)kb * 16384 + up, (t.e & E_HALF) ? 8192 : 16384, sb + GB_FULL + 8 * st);
          if (++st == G_NST) { st = 0; ph ^= 1; }
        }
      }
    } else if (wid == 18) {
      while (t.next(prm, col)) {
        if (!t.nkb) continue;
        const bool lower = t.type == T_A && (t.e & (E_HALF | E_UP)) == E_HALF;
        poll_ge(&g_cnt[(lower ? C_HALF + t.lb : c_phase(t.type, t.lb)) * CSTRIDE], prm.need[t.type][t.lb]);
        fence_async_global();
        GLOG(t.id_(prm.pend), 2, gtime());
        mbar_wait(sb + GB_ACK, (k & 1) ^ 1);
        mbar_arrive_if(lane == 0, sb + GB_READY);
        k++;
      }
    } else {
      uint32_t live = 3, par = 0, g = 0;
      while (live) {
        const bool ev = lane < 2 && ((live >> lane) & 1) && mbar_test(sb + GB_SIG + 8 * lane, (par >> lane) & 1);
        const uint32_t evs = __ballot_sync(~0u, ev);
        if (!evs) { guard(g); __nanosleep(20); continue; }
        const uint32_t msg = ev ? lds32(sb + GS_SIG + 4 * lane) : 0;
        mbar_arrive_if(ev, sb + GB_SACK + 8 * lane);
        mbar_arrive_if(msg >> 31, sb + GB_GATE + 8 * lane);
        if (msg) red_rel(&g_cnt[(msg & 0xffff) * CSTRIDE], (msg >> 16) & 255);
        par ^= evs;
        live &= ~__ballot_sync(~0u, ev && !msg);
        g = 0;
      }
      asm volatile("griddepcontrol.wait;" ::: "memory");
      if (col < 80 && lane < 16) g_mem[(col >> 4) * 2048 + (lane >> 3) * 1024 + 512 + prm.moff + (col & 15) * 8 + (lane & 7)] = make_uint4(~0u, ~0u, ~0u, ~0u);
      uint32_t last = 0;
      if (lane == 0) last = atomicAdd(&g_cnt[C_EXIT * CSTRIDE], 1) == gridDim.x - 1;
      if (__shfl_sync(~0u, last, 0)) {
        g_cnt[C_TICKET * CSTRIDE + lane] = 0;
        for (int i = lane; i < C_USED; i += 32) g_cnt[i * CSTRIDE] = 0;
      }
    }
  } else {
    asm volatile("setmaxnreg.inc.sync.aligned.u32 %0;" ::"n"(GRC));
    const int cw = wid & 7, wk = wid >> 3;
    GIter t(prm, col);
    uint32_t pos = 0, seen = 0, waited = 0;
    uint32_t nsig = 0;
    auto signal = [&](uint32_t msg) {
      mbar_wait(sb + GB_SACK + 8 * wk, (nsig++ & 1) ^ 1);
      if (cw == 0) sts32(sb + GS_SIG + 4 * wk, msg);
      __syncwarp();
      mbar_arrive_if(lane == 0, sb + GB_SIG + 8 * wk);
    };
    if (col < G_EARLY) {
      spin(prm.gd);
#pragma unroll 1
      for (int rg = 96 + col * 2 + wk; rg < 256; rg += 2 * G_EARLY) {
        uint32_t a[10];
        const uint32_t* src = prm.x + (size_t)(rg * 8 + (lane >> 2)) * (DM / 2) + cw * 40 + (lane & 3);
#pragma unroll
        for (int i = 0; i < 10; i++) a[i] = __ldg(src + i * 4);
        first_ln(a, rg, sb + GS_RED + wk * 512, cw, lane, 1 + wk);
        signal((C_XN + (rg >> 4)) | ((XN_TARGET / NF) << 16));
        bar_sync(1 + wk, 256);
      }
    }
    while (t.next(prm, col)) {
      const uint32_t pos0 = pos;
      pos = (pos + t.nkb) % (2 * G_NST);
      if (((t.e >> 29) & 1) != wk) { seen += (t.e >> 30) & 1; continue; }
      const uint32_t type = t.type, blk = t.lb & 15, layer = t.lb >> 4, n0 = t.n0;
      if (cw == 0 && t.valid) GLOG(t.id_(prm.pend), 0, 0x80000000u | type | (t.lb << 3) | (n0 << 8) | (t.nkb << 16));
      if (!t.gemm) {
        if (!t.valid) continue;
        const int rg = blk * 16 + n0;
        float4 v[5];
        const int off = (n0 * 40 + cw * 5) * 32 + lane, npl = t.kb0;
        const uint2* src = acc_planes(t.lb, type == T_F2) + off;
        if (cw == 0) {
          poll_ge(&g_cnt[c_phase(type, t.lb) * CSTRIDE], prm.need[type][t.lb]);
          mbar_arrive_if((t.e & E_EXCL) && lane == 0, sb + GB_GATE + 8 * wk);
          GLOG(t.id_(prm.pend), 2, gtime()); GLOG(t.id_(prm.pend), 3, gtime());
        }
        bar_sync(1 + wk, 256);
        {
          const uint32_t eye = (lane >> 3) == (lane & 3) ? ((lane & 4) ? 0x3f800000u : 0x00003f80u) : 0u;
#pragma unroll
          for (int i = 0; i < 5; i++) v[i] = make_float4(0.f, 0.f, 0.f, 0.f);
#pragma unroll 1
          for (int p0 = 0; p0 < npl; p0 += FPL) {
            uint32_t r[FPL / 2][5][4];
#pragma unroll
            for (int p = 0; p < FPL; p++)
#pragma unroll
              for (int i = 0; i < 5; i++) {
                const uint2 w = p0 + p < npl ? __ldcg(src + (size_t)(p0 + p) * PLANE + i * 32) : make_uint2(0, 0);
                r[p >> 1][i][(p & 1) * 2] = w.x; r[p >> 1][i][(p & 1) * 2 + 1] = w.y;
              }
#pragma unroll
            for (int p = 0; p < FPL / 2; p++) {
              if (p0 + 2 * p >= npl) break;
              if (t.e & E_EXCL) {
#pragma unroll
                for (int i = 0; i < 5; i++) mma16816(&v[i].x, r[p][i], eye, eye);
              } else {
#pragma unroll
                for (int i = 0; i < 5; i++) {
                  const uint32_t* w = r[p][i];
                  v[i].x += blo(w[0]) + blo(w[2]); v[i].y += bhi(w[0]) + bhi(w[2]); v[i].z += blo(w[1]) + blo(w[3]); v[i].w += bhi(w[1]) + bhi(w[3]);
                }
              }
            }
          }
        }
        if (type == T_F2 && layer == 1) {
          uint2* dst = (uint2*)prm.out + (size_t)(rg * 8 + (lane >> 2)) * (DM / 4) + cw * 20 + (lane & 1) * 2 + ((lane >> 1) & 1);
#pragma unroll
          for (int i = 0; i < 5; i++) {
            const uint32_t a = pack2(v[i].x, v[i].y), b = pack2(v[i].z, v[i].w);
            const uint32_t o = __shfl_xor_sync(~0u, (lane & 1) ? a : b, 1);
            dst[i * 4] = (lane & 1) ? make_uint2(o, b) : make_uint2(a, o);
          }
        } else {
          uint2* nx = (type == T_F1 ? acc_planes(t.lb, 1) : acc_planes(NBLK + blk, 0)) + off;
#pragma unroll
          for (int i = 0; i < 5; i++) {
            const uint2 w = make_uint2(pack2(v[i].x, v[i].y), pack2(v[i].z, v[i].w));
            nx[i * 32] = w;
            v[i] = make_float4(blo(w.x), bhi(w.x), blo(w.y), bhi(w.y));
          }
          float mean, rstd;
          ln_stats(v, sb + GS_RED + wk * 512, cw, lane, 1 + wk, mean, rstd);
          if (type == T_F2) store_img<4, 2048>(xn_row_group(1, rg) + lane, v, cw, mean, rstd);
          else store_img<3, 4096>(g_xa + (size_t)(blk * 10 * 4096 + n0 * 256) + lane, v, cw, mean, rstd);
        }
      } else {
        float acc[64];
#pragma unroll
        for (int j = 0; j < 64; j++) acc[j] = 0.f;
        if (waited != seen) { mbar_wait(sb + GB_ORD + 8 * (wk ^ 1), waited & 1); waited++; }
        const uint32_t hand = (t.e & E_HAND) ? sb + GB_ORD + 8 * wk : 0;
        if (!t.valid) { mbar_arrive_if(hand && lane == 0, hand); continue; }
        if (cw == 0) GLOG(t.id_(prm.pend), 3, gtime());
        const uint32_t ph = pos0 >= G_NST, st = pos0 - ph * G_NST, early = (t.e & E_EXCL) ? 0 : hand;
        const bool idle = (t.e & E_HALF) && ((t.e >> 8) & 1) != (cw >> 2);
        if (idle) {
          uint32_t s2 = st, p2 = ph;
#pragma unroll 1
          for (uint32_t kb = 0; kb < t.nkb; kb++) {
            mbar_wait(sb + GB_FULL + 8 * s2, p2);
            mbar_arrive_if(lane == 0, sb + GB_EMPTY + 8 * s2);
            if (++s2 == G_NST) { s2 = 0; p2 ^= 1; }
          }
          mbar_arrive_if(early && lane == 0, early);
        } else if (type == T_A) g_mainloop<1>(acc, sb, early, sb + GB_GATE + 8 * (wk ^ 1), t.nkb, cw, lane, st, ph);
        else g_mainloop<0>(acc, sb, early, sb + GB_GATE + 8 * (wk ^ 1), t.nkb, cw, lane, st, ph);
        if (cw == 0) GLOG(t.id_(prm.pend), 4, gtime());
        if (idle) {
        } else if (type == T_U) {
          uint32_t* dst = g_h + (size_t)((blk * 24 + n0) * 4096 + cw * 512) + lane;
#pragma unroll
          for (int j = 0; j < 8; j++) {
            float h[4];
#pragma unroll
            for (int e = 0; e < 4; e++) {
              float th;
              asm("tanh.approx.f32 %0, %1;" : "=f"(th) : "f"(0.5f * acc[4 * j + e]));
              h[e] = acc[32 + 4 * j + e] * fmaf(th, 0.5f, 0.5f);
            }
            dst[j * 32] = pack2(h[0], h[1]);
            dst[j * 32 + 256] = pack2(h[2], h[3]);
          }
        } else {
          uint2* dst = acc_planes(t.lb, type == T_D) + (size_t)((1 + (n0 >> 3)) * PLANE + (2 * cw * 40 + (n0 & 7) * 8) * 32) + lane;
#pragma unroll
          for (int j = 0; j < 16; j++) {
            const float* a = acc + (j >> 1) * 8 + (j & 1) * 2;
            dst[(j >> 1) * 32 + (j & 1) * 1280] = make_uint2(pack2(a[0], a[1]), pack2(a[4], a[5]));
          }
        }
        mbar_arrive_if(hand != early && lane == 0, hand);
      }
      if (cw == 0) GLOG(t.id_(prm.pend), 5, gtime());
      if (cw == 0) GLOG(t.id_(prm.pend), 6, gtime());
      if (type == T_F2 && layer == 1) mbar_arrive_if((t.e & E_EXCL) && cw == 0 && lane == 0, sb + GB_GATE + 8 * wk);
      else
        signal((type != T_F2 ? c_phase(type + 1, t.lb) | (1 << 16) : (C_XN + NBLK + blk) | ((XN_TARGET / NF) << 16)) | (t.gemm ? 0 : t.e & E_EXCL));
    }
    signal(0);
  }
}

typedef CUresult (*EncodeFn)(CUtensorMap*, CUtensorMapDataType, cuuint32_t, void*, const cuuint64_t*, const cuuint64_t*, const cuuint32_t*,
                             const cuuint32_t*, CUtensorMapInterleave, CUtensorMapSwizzle, CUtensorMapL2promotion, CUtensorMapFloatOOBfill);
static CUtensorMap make_map(EncodeFn fn, const void* p, uint64_t inner, uint64_t outer, uint32_t bi, uint32_t bo, int promo = 3) {
  CUtensorMap m;
  cuuint64_t dims[2] = {inner, outer}, str[1] = {inner * 2};
  cuuint32_t box[2] = {bi, bo}, es[2] = {1, 1};
  fn(&m, CU_TENSOR_MAP_DATA_TYPE_BFLOAT16, 2, (void*)p, dims, str, box, es, CU_TENSOR_MAP_INTERLEAVE_NONE, CU_TENSOR_MAP_SWIZZLE_128B,
     (CUtensorMapL2promotion)promo, CU_TENSOR_MAP_FLOAT_OOB_FILL_NONE);
  return m;
}
struct Tune {
  int lag = 11, excl = 6, gonly = 0, xl = 1, ronly = 0, pn = 30;
  int da = 120, db = 350, dc = 650, dd = 650, d2 = 2170, p1 = 300, p2 = 800;
  int ea = 60, eb = 310, ec = 550, ed = 550, e2 = 2200, q1 = 200, q2 = 400, d3 = 60, moff = 192, ds = 400, dh = 60, pa = 0, pb = 0, pc = 0, pd = 0, pe = 0, pf = 0, pg = 0, ph = 0, hold = 1, wpf = 4, gd = 22000, dq = 300, sl = 18, pr = 2, pg2 = 3;
};
static void fill_r(RParams& p, const Tune& t, int lag, int n0, int n1) {
  r_fill_desc(p);
  p.nslots = 0; p.d3 = t.d3; p.pn = t.pn; p.moff = t.moff; p.ds = t.ds; p.dh = t.dh; p.dq = t.dq;
  for (int c = 0; c < 5; c++) { p.d2[c] = t.d2 + (c == 0 ? 0 : c < 3 ? t.p1 : t.p2); p.d2[5 + c] = t.e2 + (c == 0 ? 0 : c < 3 ? t.q1 : t.q2); }
  const int d1[8] = {t.da, t.db, t.dc, t.dd, t.ea, t.eb, t.ec, t.ed};
  for (int i = 0; i < 8; i++) p.d1[i] = d1[i];
  int last[2] = {0, 0}, n = 0;
  for (int s0 = 0; s0 < NSEG + lag; s0++)
    for (int l = 0; l < 2; l++) {
      const int s = l ? s0 - lag : s0;
      if (s < 0 || s >= NSEG) continue;
      if (n >= n0 && n < n1) { p.slot[p.nslots] = s | (l << 6) | (last[l] << 8) | (((s & 3) == 3 ? C_O + l * NBLK + s / 4 : s == (l ? 61 : 1) ? C_HALF + l * NBLK + s / 4 : 0) << 16); last[l] = ++p.nslots; }
      n++;
    }
  for (int i = 0; i + 1 < p.nslots; i++) if (((p.slot[i] ^ p.slot[i + 1]) >> 6) & 1) p.slot[i] |= 128;
}
static uint32_t g_entry(int grp, int type, int layer, int blk, int i, int ks) {
  int n0 = i, kb0 = 0, kb1 = type == T_U ? 10 : 0;
  if (type == T_F1 || type == T_F2) kb0 = kb1 = ks + 1;
  if (type == T_A || type == T_D) {
    const int KB = type == T_A ? 96 : 24, sp = i / 5;
    n0 = i % 5 | (sp << 3); kb0 = sp * KB / ks; kb1 = (sp + 1) * KB / ks;
  }
  return type | (layer << 3) | (blk << 4) | (n0 << 9) | (kb0 << 16) | ((kb1 - kb0) << 23) | (grp ? E_GRP : 0);
}
static bool g_is_gemm(uint32_t e) { return (e & 7) == T_A || (e & 7) == T_U || (e & 7) == T_D; }
static void g_handover(uint32_t* e, int len) {
  uint32_t next = 0;
  for (int i = len - 1; i >= 0; i--)
    if (g_is_gemm(e[i])) { if ((e[i] & E_GRP) != next) e[i] |= E_HAND; next = e[i] & E_GRP; }
}
struct GList {
  GParams& g; uint32_t* tab; int ncol, stride, len, n[G_LATE], load[G_LATE], grp[G_LATE];
  GList(GParams& g_, uint32_t* t, int nc, int st, int l) : g(g_), tab(t), ncol(nc), stride(st), len(l) { for (int c = 0; c < nc; c++) { n[c] = load[c] = 0; grp[c] = 1; } }
  void add(int type, int lb, int ks, int c0, int c1, uint32_t flags = 0, int i0 = 0, int i1 = 999, int step = 1) {
    const int half = (flags & E_HALF) != 0, ln = type == T_F1 || type == T_F2;
    const int cnt = (type == T_U ? 24 : ln ? NF : 5 * ks) << half;
    if (type < T_F2) g.need[type + 1][lb] = cnt;
    int used[G_LATE] = {0};
    for (int i = i0; i < cnt && i < i1; i += step) {
      int best = c0;
      for (int c = c0; c < c1; c++) if (used[c] < used[best] || (used[c] == used[best] && load[c] < load[best])) best = c;
      used[best]++;
      if (!ln) grp[best] ^= 1;
      const uint32_t e = g_entry(grp[best], type, lb >> 4, lb & 15, i >> half, ks) | flags | (ln ? E_EXCL : 0) | ((i & half) ? E_UP : 0);
      if (n[best] >= len) abort();
      tab[best * stride + n[best]++] = e;
      load[best] += (((e >> 23) & 31) >> half) + 2;
    }
  }
  void put(int c, uint32_t e) { if (n[c] >= len) abort(); tab[c * stride + n[c]++] = e; if (g_is_gemm(e)) grp[c] = (e & E_GRP) != 0; }
  void finish() { for (int c = 0; c < ncol; c++) g_handover(tab + c * stride, len); }
};
static void fill_g(GParams& g, const Tune& t, void* out) {
  g.out = (__nv_bfloat16*)out;  g.pend = NBLK - 2;
  for (int b = 0; b < 2 * NBLK; b++) {
    g.need[T_A][b] = 96; g.need[T_F1][b] = 20; g.need[T_U][b] = NF; g.need[T_D][b] = 32; g.need[T_F2][b] = 15;
  }
  {
    const uint8_t perm[G_EARLY] = {0, 1, 2, 3, 16, 17, 18, 19, 34, 35, 4, 20, 21, 15, 22, 23, 5, 6, 7, 8, 9, 24, 25, 26, 10, 11, 12, 13, 14, 27, 28, 29, 30, 31, 32, 33};
    const uint8_t first[9] = {0, 10, 13, 16, 20, 24, 28, 32, 36};
    const int* pk = &t.pa;
    for (int i = 0; i < G_EARLY; i++) g.perm[i] = t.pa ? (pk[i / 5] >> (6 * (i % 5))) & 63 : perm[i];
    for (int i = 0; i < 9; i++) g.first[i] = first[i];
  }
  for (uint32_t& e : g.tab) e = T_NONE;
  GList pr(g, g.tab, G_EARLY, EL, PL);
  pr.add(T_A, 0, 7, 1, 36, E_HALF, 0, 999, 2); pr.add(T_A, 0, 7, 1, 36, E_HALF, 1, 999, 2); pr.add(T_F1, 0, 7, 20, 36); pr.add(T_U, 0, 0, 12, 36);
  pr.add(T_D, 0, 3, 20, 36); pr.add(T_F2, 0, 3, 20, 36);
  pr.finish();
  const int d = 3;
  const uint32_t xa = (t.excl & 1) ? E_EXCL : 0, xu = (t.excl & 2) ? E_EXCL : 0, xd = (t.excl & 4) ? E_EXCL : 0;
  for (int c = 0; c < G_EARLY; c++) {
    uint32_t* e = g.tab + c * EL + PL;
    if (c < 20) {
      *e++ = g_entry(0, T_A, 0, 0, c, 4) | xa;
      if (c < NF) *e++ = g_entry(0, T_F1, 0, 0, c, 4) | ((t.xl & 1) ? E_EXCL : 0);
      *e++ = g_entry(1, T_A, 1, d, c, 4);
      if (c >= 20 - NF) *e++ = g_entry(1, T_F1, 1, d, c - (20 - NF), 4);
    } else {
      const int j = c - 20;
      const uint32_t hf = E_HALF | ((j & 1) ? E_UP : 0);
      *e++ = g_entry(0, T_U, 0, 0, j, 0);
      *e++ = g_entry(1, T_U, 0, 0, 16 + j / 2, 0) | hf | xu;
      *e++ = g_entry(0, T_U, 1, d + 1, 16 + j / 2, 0) | hf;
      if (j < 15) *e++ = g_entry(1, T_D, 0, 0, j, 3) | xd;
      *e++ = g_entry(1, T_F2, 0, 0, j, 3) | ((t.xl & 2) ? E_EXCL : 0);
      if (j < 15) *e++ = g_entry(0, T_D, 1, d + 1, j, 3);
      *e++ = g_entry(0, T_U, 1, d, j, 0);
      *e++ = g_entry(1, T_F2, 1, d + 1, j, 3);
    }
    g_handover(g.tab + c * EL + PL, ML);
  }
  GList dr(g, g.tab + PL + ML, G_EARLY, EL, DL);
  GList tl(g, g.tab + TAB_TAIL, G_LATE, TL, TL);
  const int L1 = NBLK;
  auto ufull = [&](int lb) { dr.add(T_U, lb, 0, 20, 36, 0, 0, 16); g.need[T_D][lb] = 32; };
  auto uhalf = [&](int lb) { dr.add(T_U, lb, 0, 20, 36, E_HALF, 32); g.need[T_D][lb] = 32; };
  for (int c = 0; c < G_EARLY; c++)
    for (int i = 0; i < ML; i++) {
      uint32_t e = g.tab[c * EL + PL + i] & ~E_HAND;
      const uint32_t ty = e & 7;
      if (ty == T_NONE || ((e & 8) && (ty == T_F2 || (ty == T_U && !(e & E_HALF))))) continue;
      e = (e & ~0xf0u) | (14 - ((e >> 4) & 15)) << 4;
      dr.put(c, e | (ty == T_F2 ? E_EXCL : 0));
    }
  dr.add(T_A, 15, 4, 0, 20, E_EXCL);
  dr.add(T_F1, 15, 4, 0, 16);
  dr.add(T_U, 15, 0, 12, 36, E_EXCL);
  for (int c = 0; c < 20; c++) {
    const int tile = c % 5, sp = c / 5, len = tile < 2 ? (96 - t.sl) / 3 : 48 - t.sl, nl = tile < 2 ? 3 : 2;
    const int k0 = sp <= nl ? sp * len : nl * len + t.sl, nk = sp < nl ? len : sp == 3 ? 96 - k0 : t.sl;
    dr.put(c, (g_entry(dr.grp[c] ^ 1, T_A, 1, 12, c, 4) & ~0x0fff0000u) | k0 << 16 | nk << 23);
  }
  dr.add(T_F1, L1 + 12, 4, 0, 16);
  uhalf(L1 + 11);
  dr.add(T_D, 15, 3, 20, 36, E_EXCL); dr.add(T_F2, 15, 3, 20, 36);
  dr.add(T_A, L1 + 13, 4, 0, 20); dr.add(T_F1, L1 + 13, 4, 0, 20);
  ufull(L1 + 11);
  dr.add(T_D, L1 + 11, 3, 20, 36);
  ufull(L1 + 12); uhalf(L1 + 12);
  dr.add(T_A, L1 + 14, 4, 0, 20);
  dr.add(T_A, L1 + 15, 7, 0, 35, E_HALF, 0, 999, 2); dr.add(T_A, L1 + 15, 7, 0, 35, E_HALF | E_EXCL, 1, 999, 2);
  dr.add(T_F1, L1 + 14, 4, 0, 16);
  dr.add(T_F1, L1 + 15, 7, 20, 36);
  dr.add(T_F2, L1 + 10, 3, 0, 16); dr.add(T_F2, L1 + 11, 3, 4, 20);  dr.add(T_F2, L1 + 12, 3, 0, 20);
  dr.add(T_D, L1 + 13, 3, 20, 36, (t.hold & 1) ? E_UP : 0); dr.add(T_F2, L1 + 13, 3, 20, 36);
  dr.finish();
  tl.add(T_D, L1 + 12, 3, 72, G_LATE);
  tl.add(T_U, L1 + 14, 0, 0, 24); tl.add(T_U, L1 + 13, 0, 24, 48);
  tl.add(T_D, L1 + 14, 4, 0, 48, E_HALF);
  tl.add(T_F2, L1 + 14, 4, 0, 48);
  tl.add(T_U, L1 + 15, 0, 48, G_LATE, E_HALF);
  tl.add(T_D, L1 + 15, 4, 48, G_LATE, E_HALF);
  tl.add(T_F2, L1 + 15, 4, 48, G_LATE);
  tl.finish();
}
static void launch_all(void* const* d_in, void* d_out, const Tune& t, cudaStream_t st) {
  static EncodeFn fn = nullptr;
  if (!fn) {
    void* f = nullptr;
    cudaDriverEntryPointQueryResult qr;
    cudaGetDriverEntryPoint("cuTensorMapEncodeTiled", &f, cudaEnableDefault, &qr);
    fn = (EncodeFn)f;
    cudaFuncSetAttribute(r_kernel, cudaFuncAttributeMaxDynamicSharedMemorySize, R_SMEM);
    cudaFuncSetAttribute(g_kernel, cudaFuncAttributeMaxDynamicSharedMemorySize, G_SMEM);
  }
  const CUtensorMap mq = make_map(fn, d_in[2], HD, DM, 64, 128, t.pr), mk = make_map(fn, d_in[3], HD, DM, 64, 128, t.pr), mv = make_map(fn, d_in[4], HD, DM, 64, 128, t.pr),
                    mo = make_map(fn, d_in[5], DM, HD, 64, 64, t.pg2), mg = make_map(fn, d_in[8], FF, DM, 64, 64, t.pg2), mu = make_map(fn, d_in[9], FF, DM, 64, 64, t.pg2),
                    md = make_map(fn, d_in[10], DM, FF, 64, 64, t.pg2);
  auto launch_r = [&](int lag, int n0, int n1) {
    RParams p;
    fill_r(p, t, lag, n0, n1);
    for (int i = 0; i < 4; i++) p.w[i] = (const char*)d_in[2 + i];
    p.mem0 = (const uint4*)d_in[1]; p.x = (const uint32_t*)d_in[0]; p.pf = t.wpf;
    cudaLaunchConfig_t cfg = {};
    cfg.gridDim = dim3(3, NH); cfg.blockDim = dim3(512); cfg.dynamicSmemBytes = R_SMEM; cfg.stream = st;
    cudaLaunchAttribute at[1];
    at[0].id = cudaLaunchAttributeClusterDimension; at[0].val.clusterDim.x = 3; at[0].val.clusterDim.y = 1; at[0].val.clusterDim.z = 1;
    cfg.attrs = at; cfg.numAttrs = 1;
    cudaLaunchKernelEx(&cfg, r_kernel, mq, mk, mv, mo, p);
  };
  auto launch_g = [&](const GParams& g, bool pdl) {
    cudaLaunchConfig_t cfg = {};
    cfg.gridDim = dim3(132); cfg.blockDim = dim3(640); cfg.dynamicSmemBytes = G_SMEM; cfg.stream = st;
    cudaLaunchAttribute at[2];
    at[0].id = cudaLaunchAttributeProgrammaticStreamSerialization; at[0].val.programmaticStreamSerializationAllowed = 1;
    cfg.attrs = at; cfg.numAttrs = pdl ? 1 : 0;
    cudaLaunchKernelEx(&cfg, g_kernel, mo, mg, mu, md, g);
  };
  GParams g;
  fill_g(g, t, d_out);
  g.moff = t.moff; g.gd = t.gd; g.x = (const uint32_t*)d_in[0];
  launch_r(t.lag, 0, 2 * NSEG);
  launch_g(g, true);
}

extern "C" void kernel_launch(void* const* d_in, const int* in_sizes, int n_in, void* d_out, int out_size) {
  launch_all(d_in, d_out, Tune(), cudaStreamPerThread);
}
```

```cpp
#include <cuda_runtime.h>
#include <cuda_bf16.h>
#include <cuda.h>
#include <stdint.h>
#include <stdlib.h>

constexpr int SEQ = 2048, DM = 640, NH = 32, DH = 192, HD = NH * DH, FF = 1536;
constexpr int NSEG = 64, SEGL = 32, NMEM = 8;
constexpr int NBLK = 16;

#define DI __device__ __forceinline__

DI uint32_t smem_base() {
  extern __shared__ __align__(1024) unsigned char smem_raw[];
  uint32_t a;
  asm volatile("{.reg .u64 t; cvta.to.shared.u64 t, %1; cvt.u32.u64 %0, t;}" : "=r"(a) : "l"(smem_raw));
  return a;
}
DI uint32_t mapa(uint32_t a, uint32_t r) {
  uint32_t o;
  asm("mapa.shared::cluster.u32 %0, %1, %2;" : "=r"(o) : "r"(a), "r"(r));
  return o;
}
DI void mbar_init(uint32_t bar, uint32_t cnt) { asm volatile("mbarrier.init.shared::cta.b64 [%0], %1;" ::"r"(bar), "r"(cnt) : "memory"); }
DI void mbar_arrive(uint32_t bar) { asm volatile("mbarrier.arrive.shared::cta.b64 _, [%0];" ::"r"(bar) : "memory"); }
DI void mbar_arrive_remote(uint32_t bar) { asm volatile("mbarrier.arrive.release.cluster.shared::cluster.b64 _, [%0];" ::"r"(bar) : "memory"); }
DI void mbar_expect(uint32_t bar, uint32_t tx) { asm volatile("mbarrier.arrive.expect_tx.shared::cta.b64 _, [%0], %1;" ::"r"(bar), "r"(tx) : "memory"); }
DI void mbar_arrive_if(bool p, uint32_t bar) { asm volatile("{.reg .pred p; setp.ne.b32 p, %1, 0; @p mbarrier.arrive.shared::cta.b64 _, [%0];}" ::"r"(bar), "r"((int)p) : "memory"); }
DI void mbar_arrive_if(bool p, uint32_t bar, uint32_t cnt) {
  asm volatile("{.reg .pred p; setp.ne.b32 p, %1, 0; @p mbarrier.arrive.shared::cta.b64 _, [%0], %2;}" ::"r"(bar), "r"((int)p), "r"(cnt) : "memory");
}
DI void mbar_expect_if(bool p, uint32_t bar, uint32_t tx) {
  asm volatile("{.reg .pred p; setp.ne.b32 p, %2, 0; @p mbarrier.arrive.expect_tx.shared::cta.b64 _, [%0], %1;}" ::"r"(bar), "r"(tx), "r"((int)p) : "memory");
}
DI bool mbar_test(uint32_t bar, uint32_t par) {
  uint32_t ok;
  asm volatile("{.reg .pred p; mbarrier.test_wait.parity.shared::cta.b64 p, [%1], %2; selp.u32 %0, 1, 0, p;}" : "=r"(ok) : "r"(bar), "r"(par) : "memory");
  return ok;
}
DI void mbar_wait(uint32_t bar, uint32_t par) {
  asm volatile(
      "{.reg .pred p;\n"
      "LOOP:\n"
      "mbarrier.try_wait.parity.shared::cta.b64 p, [%0], %1;\n"
      "@!p bra LOOP;\n}" ::"r"(bar), "r"(par) : "memory");
}
DI void mbar_wait_wd(uint32_t bar, uint32_t par) {
  asm volatile(
      "{.reg .pred p; .reg .u32 c;\n"
      "mov.u32 c, 0;\n"
      "LOOP:\n"
      "mbarrier.try_wait.parity.shared::cta.b64 p, [%0], %1;\n"
      "@p bra DONE;\n"
      "add.u32 c, c, 1;\n"
      "setp.lt.u32 p, c, 4000000;\n"
      "@p bra LOOP;\n"
      "trap;\n"
      "DONE:\n}" ::"r"(bar), "r"(par) : "memory");
}
DI void fence_async_smem() { asm volatile("fence.proxy.async.shared::cta;" ::: "memory"); }
DI void fence_async_global() { asm volatile("fence.proxy.async.global;" ::: "memory"); }
DI void bar_sync(int id, int n) { asm volatile("bar.sync %0, %1;" ::"r"(id), "r"(n) : "memory"); }
DI void bar_arrive(int id, int n) { asm volatile("bar.arrive %0, %1;" ::"r"(id), "r"(n) : "memory"); }
DI void cluster_sync() { asm volatile("barrier.cluster.arrive.release.aligned; barrier.cluster.wait.acquire.aligned;" ::: "memory"); }
DI bool elect_one() {
  uint32_t p;
  asm volatile("{.reg .pred p; elect.sync _|p, 0xffffffff; selp.u32 %0, 1, 0, p;}" : "=r"(p));
  return p;
}
DI void bulk_g2s(uint32_t dst, const void* src, uint32_t bytes, uint32_t bar) {
  asm volatile("cp.async.bulk.shared::cluster.global.mbarrier::complete_tx::bytes [%0], [%1], %2, [%3];" ::"r"(dst), "l"(src), "r"(bytes), "r"(bar) : "memory");
}
DI void bulk_g2s_mc(uint32_t dst, const void* src, uint32_t bytes, uint32_t bar, uint16_t mask) {
  asm volatile("cp.async.bulk.shared::cluster.global.mbarrier::complete_tx::bytes.multicast::cluster [%0], [%1], %2, [%3], %4;" ::"r"(dst), "l"(src), "r"(bytes), "r"(bar), "h"(mask) : "memory");
}
DI void bulk_s2s(uint32_t dst, uint32_t src, uint32_t bytes, uint32_t bar) {
  asm volatile("cp.async.bulk.shared::cluster.shared::cta.mbarrier::complete_tx::bytes [%0], [%1], %2, [%3];" ::"r"(dst), "r"(src), "r"(bytes), "r"(bar) : "memory");
}
DI void tma_2d(uint32_t dst, const CUtensorMap* map, int c0, int c1, uint32_t bar) {
  asm volatile("cp.async.bulk.tensor.2d.shared::cluster.global.mbarrier::complete_tx::bytes [%0], [%1, {%3, %4}], [%2];" ::"r"(dst), "l"(map), "r"(bar), "r"(c0), "r"(c1) : "memory");
}
DI void tma_pf(const CUtensorMap* map, int c0, int c1) {
  asm volatile("cp.async.bulk.prefetch.tensor.2d.L2.global [%0, {%1, %2}];" ::"l"(map), "r"(c0), "r"(c1) : "memory");
}
DI void st_async4(uint32_t a, uint32_t x, uint32_t y, uint32_t z, uint32_t w, uint32_t bar) {
  asm volatile("st.async.shared::cluster.mbarrier::complete_tx::bytes.v4.b32 [%0], {%1,%2,%3,%4}, [%5];" ::"r"(a), "r"(x), "r"(y), "r"(z), "r"(w), "r"(bar) : "memory");
}
DI void st_async2(uint32_t a, uint32_t x, uint32_t y, uint32_t bar) {
  asm volatile("st.async.shared::cluster.mbarrier::complete_tx::bytes.v2.b32 [%0], {%1,%2}, [%3];" ::"r"(a), "r"(x), "r"(y), "r"(bar) : "memory");
}
DI void st_async1(uint32_t a, uint32_t x, uint32_t bar) {
  asm volatile("st.async.shared::cluster.mbarrier::complete_tx::bytes.b32 [%0], %1, [%2];" ::"r"(a), "r"(x), "r"(bar) : "memory");
}
DI void sts32(uint32_t a, uint32_t x) { asm volatile("st.shared.b32 [%0], %1;" ::"r"(a), "r"(x) : "memory"); }
DI void sts128(uint32_t a, uint4 v) { asm volatile("st.shared.v4.b32 [%0], {%1,%2,%3,%4};" ::"r"(a), "r"(v.x), "r"(v.y), "r"(v.z), "r"(v.w) : "memory"); }
DI uint32_t lds32(uint32_t a) { uint32_t v; asm volatile("ld.shared.b32 %0, [%1];" : "=r"(v) : "r"(a) : "memory"); return v; }
DI uint2 lds64(uint32_t a) { uint2 v; asm volatile("ld.shared.v2.b32 {%0,%1}, [%2];" : "=r"(v.x), "=r"(v.y) : "r"(a) : "memory"); return v; }
DI uint4 lds128(uint32_t a) { uint4 v; asm volatile("ld.shared.v4.b32 {%0,%1,%2,%3}, [%4];" : "=r"(v.x), "=r"(v.y), "=r"(v.z), "=r"(v.w) : "r"(a) : "memory"); return v; }
DI void stsm4(uint32_t a, uint32_t r0, uint32_t r1, uint32_t r2, uint32_t r3) {
  asm volatile("stmatrix.sync.aligned.m8n8.x4.shared.b16 [%0], {%1,%2,%3,%4};" ::"r"(a), "r"(r0), "r"(r1), "r"(r2), "r"(r3) : "memory");
}
DI void stsm2(uint32_t a, uint32_t r0, uint32_t r1) {
  asm volatile("stmatrix.sync.aligned.m8n8.x2.shared.b16 [%0], {%1,%2};" ::"r"(a), "r"(r0), "r"(r1) : "memory");
}
DI uint32_t movm(uint32_t a) { uint32_t d; asm volatile("movmatrix.sync.aligned.m8n8.trans.b16 %0, %1;" : "=r"(d) : "r"(a)); return d; }
DI uint32_t pack2(float lo, float hi) { uint32_t d; asm("cvt.rn.bf16x2.f32 %0, %1, %2;" : "=r"(d) : "f"(hi), "f"(lo)); return d; }
DI uint4 ld_rlx4(const void* p) {
  uint4 v;
  asm volatile("ld.relaxed.gpu.global.v4.u32 {%0,%1,%2,%3}, [%4];" : "=r"(v.x), "=r"(v.y), "=r"(v.z), "=r"(v.w) : "l"(p) : "memory");
  return v;
}
DI void st_rlx4(void* p, uint32_t x, uint32_t y, uint32_t z, uint32_t w) {
  asm volatile("st.relaxed.gpu.global.v4.u32 [%0], {%1,%2,%3,%4};" ::"l"(p), "r"(x), "r"(y), "r"(z), "r"(w) : "memory");
}
DI void st_rlx1(void* p, uint32_t x) { asm volatile("st.relaxed.gpu.global.u32 [%0], %1;" ::"l"(p), "r"(x) : "memory"); }
DI uint32_t ld_acq(const uint32_t* p) { uint32_t v; asm volatile("ld.acquire.gpu.global.u32 %0, [%1];" : "=r"(v) : "l"(p) : "memory"); return v; }
DI uint32_t ld_rlx(const uint32_t* p) { uint32_t v; asm volatile("ld.relaxed.gpu.global.u32 %0, [%1];" : "=r"(v) : "l"(p) : "memory"); return v; }
DI void red_rel(uint32_t* p, uint32_t v) { asm volatile("red.release.gpu.global.add.u32 [%0], %1;" ::"l"(p), "r"(v) : "memory"); }
DI void guard(uint32_t& g) { asm volatile("{.reg .pred p; add.u32 %0, %0, 1; setp.gt.u32 p, %0, 8000000; @p trap;}" : "+r"(g)); }
DI void poll_ge(const uint32_t* p, uint32_t target) {
  asm volatile(
      "{.reg .pred p; .reg .u32 v;\n"
      "LOOP:\n"
      "ld.acquire.gpu.global.u32 v, [%0];\n"
      "setp.lt.u32 p, v, %1;\n"
      "vote.sync.any.pred p, p, 0xffffffff;\n"
      "@p bra.uni LOOP;\n}" ::"l"(p), "r"(target) : "memory");
}
DI float ex2(float x) { float y; asm("ex2.approx.ftz.f32 %0, %1;" : "=f"(y) : "f"(x)); return y; }

DI void wg_fence() { asm volatile("wgmma.fence.sync.aligned;" ::: "memory"); }
DI void wg_commit() { asm volatile("wgmma.commit_group.sync.aligned;" ::: "memory"); }
template <int N> DI void wg_wait() { asm volatile("wgmma.wait_group.sync.aligned %0;" ::"n"(N) : "memory"); }
template <int N> DI void reg_fence(float* d) {
#pragma unroll
  for (int i = 0; i < N; i++) asm volatile("" : "+f"(d[i])::"memory");
}
__host__ __device__ constexpr uint64_t mkdesc(uint32_t addr, uint32_t lbo, uint32_t sbo, uint32_t sw) {
  return (uint64_t)((addr & 0x3FFFF) >> 4) | ((uint64_t)(lbo >> 4) << 16) | ((uint64_t)(sbo >> 4) << 32) | ((uint64_t)sw << 62);
}

#define ACC4(d, o) "+f"(d[o]), "+f"(d[o + 1]), "+f"(d[o + 2]), "+f"(d[o + 3])
#define ACC16(d, o) ACC4(d, o), ACC4(d, o + 4), ACC4(d, o + 8), ACC4(d, o + 12)
#define ACC20(d) ACC16(d, 0), ACC4(d, 16)

template <int TA, int TB> DI void wg_ss40(float* d, uint64_t da, uint64_t db, int sc) {
  asm volatile("{.reg .pred p; setp.ne.b32 p, %22, 0;\n"
               "wgmma.mma_async.sync.aligned.m64n40k16.f32.bf16.bf16 {%0,%1,%2,%3,%4,%5,%6,%7,%8,%9,%10,%11,%12,%13,%14,%15,%16,%17,%18,%19}, %20, %21, p, 1, 1, %23, %24;}"
               : ACC20(d) : "l"(da), "l"(db), "r"(sc), "n"(TA), "n"(TB));
}
DI void wg_rs40(float* d, uint32_t a0, uint32_t a1, uint32_t a2, uint32_t a3, uint64_t db, int sc) {
  asm volatile("{.reg .pred p; setp.ne.b32 p, %25, 0;\n"
               "wgmma.mma_async.sync.aligned.m64n40k16.f32.bf16.bf16 {%0,%1,%2,%3,%4,%5,%6,%7,%8,%9,%10,%11,%12,%13,%14,%15,%16,%17,%18,%19}, {%20,%21,%22,%23}, %24, p, 1, 1, 0;}"
               : ACC20(d) : "r"(a0), "r"(a1), "r"(a2), "r"(a3), "l"(db), "r"(sc));
}
DI void wg_rs32(float* d, uint32_t a0, uint32_t a1, uint32_t a2, uint32_t a3, uint64_t db, int sc) {
  asm volatile("{.reg .pred p; setp.ne.b32 p, %21, 0;\n"
               "wgmma.mma_async.sync.aligned.m64n32k16.f32.bf16.bf16 {%0,%1,%2,%3,%4,%5,%6,%7,%8,%9,%10,%11,%12,%13,%14,%15}, {%16,%17,%18,%19}, %20, p, 1, 1, 0;}"
               : ACC16(d, 0) : "r"(a0), "r"(a1), "r"(a2), "r"(a3), "l"(db), "r"(sc));
}
DI void wg_ss32k(float* d, uint64_t da, uint64_t db, int sc) {
  asm volatile("{.reg .pred p; setp.ne.b32 p, %18, 0;\n"
               "wgmma.mma_async.sync.aligned.m64n32k16.f32.bf16.bf16 {%0,%1,%2,%3,%4,%5,%6,%7,%8,%9,%10,%11,%12,%13,%14,%15}, %16, %17, p, 1, 1, 1, 0;}"
               : ACC16(d, 0) : "l"(da), "l"(db), "r"(sc));
}
DI void wg_ss8k(float* d, uint64_t da, uint64_t db, int sc) {
  asm volatile("{.reg .pred p; setp.ne.b32 p, %6, 0;\n"
               "wgmma.mma_async.sync.aligned.m64n8k16.f32.bf16.bf16 {%0,%1,%2,%3}, %4, %5, p, 1, 1, 1, 0;}"
               : ACC4(d, 0) : "l"(da), "l"(db), "r"(sc));
}
DI void wg_rs8(float* d, uint32_t a0, uint32_t a1, uint32_t a2, uint32_t a3, uint64_t db, int sc) {
  asm volatile("{.reg .pred p; setp.ne.b32 p, %9, 0;\n"
               "wgmma.mma_async.sync.aligned.m64n8k16.f32.bf16.bf16 {%0,%1,%2,%3}, {%4,%5,%6,%7}, %8, p, 1, 1, 0;}"
               : ACC4(d, 0) : "r"(a0), "r"(a1), "r"(a2), "r"(a3), "l"(db), "r"(sc));
}
DI void mma16816(float* c, const uint32_t* a, uint32_t b0, uint32_t b1) {
  asm volatile("mma.sync.aligned.m16n8k16.row.col.f32.bf16.bf16.f32 {%0,%1,%2,%3}, {%4,%5,%6,%7}, {%8,%9}, {%0,%1,%2,%3};"
               : ACC4(c, 0) : "r"(a[0]), "r"(a[1]), "r"(a[2]), "r"(a[3]), "r"(b0), "r"(b1));
}
DI void wg_ss8(float* d, uint64_t da, uint64_t db, int sc) {
  asm volatile("{.reg .pred p; setp.ne.b32 p, %6, 0;\n"
               "wgmma.mma_async.sync.aligned.m64n8k16.f32.bf16.bf16 {%0,%1,%2,%3}, %4, %5, p, 1, 1, 1, 1;}"
               : ACC4(d, 0) : "l"(da), "l"(db), "r"(sc));
}
DI void wg_rs16(float* d, uint32_t a0, uint32_t a1, uint32_t a2, uint32_t a3, uint64_t db, int sc) {
  asm volatile("{.reg .pred p; setp.ne.b32 p, %13, 0;\n"
               "wgmma.mma_async.sync.aligned.m64n16k16.f32.bf16.bf16 {%0,%1,%2,%3,%4,%5,%6,%7}, {%8,%9,%10,%11}, %12, p, 1, 1, 0;}"
               : ACC4(d, 0), ACC4(d, 4) : "r"(a0), "r"(a1), "r"(a2), "r"(a3), "l"(db), "r"(sc));
}
__device__ uint4 g_xn[2 * NSEG * 10 * 256];
__device__ uint4 g_oT[2 * NBLK * 96 * 1024];
constexpr int PART_RING = 96 * 256;
__device__ uint4 g_part[4 * PART_RING];
constexpr int MEM_OFF = 192;
#define P4 ~0u, ~0u, ~0u, ~0u
#define P16 P4, P4, P4, P4
#define P256 P16, P16, P16, P16, P16, P16, P16, P16, P16, P16, P16, P16, P16, P16, P16, P16
#define P2K P256, P256, P256, P256, P256, P256, P256, P256
#define P8K P2K, P2K, P2K, P2K
__device__ __align__(8192) uint32_t g_mem32[5 * 2 * 2 * 2048] = {P8K, P8K, P8K, P8K, P8K};
#define g_mem ((uint4*)g_mem32)
constexpr int C_XN = 0;
constexpr int C_O = C_XN + 2 * NBLK;
constexpr int C_HALF = C_O + 6 * 2 * NBLK;
constexpr int C_TOTAL = 512;
constexpr int CSTRIDE = 32;
__device__ uint32_t g_cnt[C_TOTAL * CSTRIDE];
constexpr uint32_t XN_TARGET = 128;

#define TRACE(c, n, i, v)
#define SLOG(i)
#define PROF(i)
#define PROFA(c)
#define PROFV(i, v)

constexpr uint32_t SMEM0 = 1024;
constexpr uint32_t SM_WK = 0, SM_WO = 81920, SM_H = 163840, SM_QT = 215040, QSTR = 1056  , SM_KT = SM_QT + 5 * QSTR + 1024,
                   SM_SR = SM_KT + 5120  , SM_PROF = SM_SR + 5760, R_SMEM = 232448,
                   SM_RED = SM_QT + 1024, SM_BAR = SM_RED + 768;
constexpr uint32_t SM_P = SM_KT, SM_OB = SM_QT + 3200;
constexpr uint32_t B_HFULL = SM_BAR, B_HEMPTY = SM_BAR + 40, B_MTRY = SM_BAR + 80, B_W = SM_BAR + 112, B_SR = B_W + 32,
                   B_PMEM = B_SR + 24, B_PTOK = B_SR + 32, B_OB = B_SR + 40, B_OPD = B_SR + 48, B_RFREE = B_SR + 56,
                   B_GATE = B_SR + 64, B_PSUM = B_SR + 72, B_END = B_SR + 80, B_PVI = B_SR + 88,
                   B_OPI = B_SR + 96, B_OTOK = B_SR + 112, SM_TOPI = B_SR + 128, B_PACE = SM_TOPI + 8,
                   SM_RS = SM_QT + 2 * QSTR + 1024;
static_assert(B_PACE + 32 <= SM_QT + 2 * QSTR, "barriers must fit the unused q row group");

struct RParams {
  uint64_t dH, dHt, dWK, dWO, dQT, dKT, dP, dOB[6];
  const char* w[4];
  const uint4* mem0;
  const uint32_t* x;
  int pf;
  int nslots, d3, pn, moff, ds, dh, dq;
  int d2[10], d1[8];
  uint32_t slot[2 * NSEG];
};
static void r_fill_desc(RParams& p) {
  p.dH = mkdesc(SMEM0 + SM_H, 128, 2048, 0);
  p.dHt = mkdesc(SMEM0 + SM_H + 2048, 128, 2048, 0);
  p.dWK = mkdesc(SMEM0 + SM_WK, 1024, 1024, 1);
  p.dWO = mkdesc(SMEM0 + SM_WO, 1024, 1024, 1);
  for (int i = 0; i < 6; i++) p.dOB[i] = mkdesc(SMEM0 + SM_OB + (i < 3 ? 0 : (i - 3) * 1024), 128, 128, 0);
  p.dQT = mkdesc(SMEM0 + SM_QT, 128, QSTR, 0);
  p.dKT = mkdesc(SMEM0 + SM_KT, 128, 1024, 0);
  p.dP = mkdesc(SMEM0 + SM_P, 128, 640, 0);
}
DI uint64_t dadd(uint64_t d, int bytes) {
  uint64_t r;
  asm volatile("add.u64 %0, %1, %2;" : "=l"(r) : "l"(d), "l"((long long)(bytes / 16)));
  return r;
}
template <int BYTES> DI void dstep(uint64_t& d) { asm volatile("add.u64 %0, %0, %1;" : "+l"(d) : "n"((long long)(BYTES / 16))); }
__host__ __device__ constexpr int hoff(int ks) { return (ks >> 3) * 10240 + (ks & 7) * 256; }

DI int opaque(int v) { asm volatile("" : "+r"(v)); return v; }
DI uint32_t pin(uint32_t v, int lane) { return __shfl_sync(~0u, v + (lane >> 5), lane); }
DI char* pin(char* p, int lane) { return (char*)__shfl_sync(~0u, (unsigned long long)p, lane); }
DI float blo(uint32_t w) { return __uint_as_float(w << 16); }
DI float bhi(uint32_t w) { return __uint_as_float(w & 0xffff0000u); }
#define R_FB 1
#define PIN_DST 1
#define RG0 232
#define RG1 216
#define RG2 40
#define RG3 24
DI void ldsm4t(uint32_t* r, uint32_t a) {
  asm volatile("ldmatrix.sync.aligned.m8n8.x4.trans.shared.b16 {%0,%1,%2,%3}, [%4];" : "=r"(r[0]), "=r"(r[1]), "=r"(r[2]), "=r"(r[3]) : "r"(a) : "memory");
}
DI void st_tagged(void* p, float a, float b, uint32_t keep, uint32_t tagbit) {
  asm volatile("{.reg .b32 t; cvt.rn.bf16x2.f32 t, %2, %1; lop3.b32 t, t, %3, %4, 0xea; st.relaxed.gpu.global.b32 [%0], t;}" ::"l"(p), "f"(a), "f"(b),
               "r"(keep), "r"(tagbit) : "memory");
}
DI uint32_t lop_bad(uint32_t a, uint32_t b, uint32_t m) { uint32_t d; asm("lop3.b32 %0, %1, %2, %3, 0x7e;" : "=r"(d) : "r"(a), "r"(b), "r"(m)); return d; }
DI uint32_t lop_or3(uint32_t a, uint32_t b, uint32_t c) { uint32_t d; asm("lop3.b32 %0, %1, %2, %3, 0xfe;" : "=r"(d) : "r"(a), "r"(b), "r"(c)); return d; }
DI uint32_t clk() { uint32_t t; asm volatile("mov.u32 %0, %%clock;" : "=r"(t)); return t; }
DI void spin(uint32_t cyc) { const uint32_t t0 = clk(); while (__any_sync(~0u, clk() - t0 < cyc)) {} }
template <int NL> DI float2 poll_sum(const uint32_t* src, uint32_t tag, uint32_t even, uint32_t& g) {
  uint32_t r[NL];
  while (true) {
#pragma unroll
    for (int i = 0; i < NL; i++) r[i] = ld_rlx(src + i * 32);
    uint32_t bad = lop_or3(lop_bad(r[0], r[1], tag), lop_bad(r[2], r[3], tag), lop_bad(r[4], r[5], tag));
    if (NL == 12) bad = lop_or3(bad, lop_bad(r[6], r[7], tag), lop_bad(r[8], r[9], tag));
    asm volatile("lop3.b32 %0, %0, %1, %2, 0xa8;" : "+r"(bad) : "r"(lop_bad(r[NL - 2], r[NL - 1], tag)), "r"(even));
    if (!__any_sync(~0u, bad)) break;
    g++;
  }
  float x[NL / 2], y[NL / 2];
#pragma unroll
  for (int i = 0; i < NL / 2; i++) { x[i] = blo(r[2 * i]) + blo(r[2 * i + 1]); y[i] = bhi(r[2 * i]) + bhi(r[2 * i + 1]); }
  float2 u = make_float2((x[0] + x[1]) + (x[2] + x[3]), (y[0] + y[1]) + (y[2] + y[3]));
  if (NL == 12) { u.x += x[4] + x[5]; u.y += y[4] + y[5]; }
  return u;
}

constexpr int PLANE = 16 * 40 * 32, MAXPL = 13;
__device__ uint2 g_acc[(size_t)2 * NBLK * 2 * MAXPL * PLANE];
DI uint2* acc_planes(int lb, int d) { return g_acc + (size_t)((lb * 2 + d) * MAXPL) * PLANE; }
DI void ln_stats(const float4* v, uint32_t red, int warp, int lane, int bar, float& mean, float& rstd) {
  float s = 0.f;
#pragma unroll
  for (int i = 0; i < 5; i++) s += (v[i].x + v[i].y) + (v[i].z + v[i].w);
  s += __shfl_xor_sync(~0u, s, 1);
  s += __shfl_xor_sync(~0u, s, 2);
  s *= 1.f / 80;
  float q = 0.f;
#pragma unroll
  for (int i = 0; i < 5; i++) q += ((v[i].x - s) * (v[i].x - s) + (v[i].y - s) * (v[i].y - s)) + ((v[i].z - s) * (v[i].z - s) + (v[i].w - s) * (v[i].w - s));
  q += __shfl_xor_sync(~0u, q, 1);
  q += __shfl_xor_sync(~0u, q, 2);
  if ((lane & 3) == 0) asm volatile("st.shared.v2.f32 [%0], {%1,%2};" ::"r"(red + lane * 16 + warp * 8), "f"(s), "f"(q) : "memory");
  bar_sync(bar, 256);
  const uint4 t = lds128(red + lane * 16);
  const float m0 = __uint_as_float(t.x), m1 = __uint_as_float(t.z);
  mean = m0 + m1;
  mean += __shfl_xor_sync(~0u, mean, 1);
  mean += __shfl_xor_sync(~0u, mean, 2);
  mean *= 0.125f;
  q = __uint_as_float(t.y) + __uint_as_float(t.w) + 80.f * ((m0 - mean) * (m0 - mean) + (m1 - mean) * (m1 - mean));
  q += __shfl_xor_sync(~0u, q, 1);
  q += __shfl_xor_sync(~0u, q, 2);
  rstd = rsqrtf(q * (1.f / DM) + 1e-5f);
}
template <int SH, int STR> DI void store_img(uint32_t* dst, const float4* v, int warp, float mean, float rstd) {
#pragma unroll
  for (int i = 0; i < 5; i++) {
    const int U = 10 * warp + 2 * i;
    uint32_t* p = dst + (U >> SH) * STR + (U & ((1 << SH) - 1)) * 32;
    p[0] = pack2((v[i].x - mean) * rstd, (v[i].y - mean) * rstd);
    p[32] = pack2((v[i].z - mean) * rstd, (v[i].w - mean) * rstd);
  }
}
DI uint32_t* xn_row_group(int layer, int rg) { return (uint32_t*)(g_xn + (size_t)((layer * NSEG + (rg >> 2)) * 2560 + (rg & 3) * 128)); }

DI void first_ln(const uint32_t* a, int rg, uint32_t red, int warp, int lane, int bar) {
  float4 v[5];
#pragma unroll
  for (int i = 0; i < 5; i++) {
    v[i] = make_float4(blo(a[2 * i]), bhi(a[2 * i]), blo(a[2 * i + 1]), bhi(a[2 * i + 1]));
    acc_planes(rg >> 4, 0)[((rg & 15) * 40 + warp * 5 + i) * 32 + lane] = make_uint2(a[2 * i], a[2 * i + 1]);
  }
  float mean, rstd;
  ln_stats(v, red, warp, lane, bar, mean, rstd);
  store_img<4, 2048>(xn_row_group(0, rg) + lane, v, warp, mean, rstd);
}
#define QK_P0 32
#define QK_KB 0
struct QKOrder { int op[76]; };
__host__ __device__ constexpr QKOrder qk_order() {
  QKOrder o = {};
  int n = 0, k = 0, q = 0;
  for (; k < QK_P0; k++, q++) { o.op[n++] = 64 | k; o.op[n++] = q; }
  for (int i = 0; i < QK_KB; i++) o.op[n++] = 64 | k++;
  for (int i = 0; i < -QK_KB; i++) o.op[n++] = q++;
  const int nk = 40 - k, nq = 36 - q;
  for (int i = 0, dk = 0, dq = 0; i < nk + nq; i++) {
    if (dq * nk <= dk * nq + (QK_KB ? 0 : -nq) && dq < nq) { o.op[n++] = q++; dq++; } else if (dk < nk) { o.op[n++] = 64 | k++; dk++; } else { o.op[n++] = q++; dq++; }
  }
  return o;
}
__global__ void __launch_bounds__(512, 1)
r_kernel(const __grid_constant__ CUtensorMap mapWq, const __grid_constant__ CUtensorMap mapWk, const __grid_constant__ CUtensorMap mapWv,
         const __grid_constant__ CUtensorMap mapWo, const __grid_constant__ RParams prm) {
  const uint32_t sb = smem_base();
  const int wid = __shfl_sync(~0u, threadIdx.x >> 5, 0);
  const int lane0 = __shfl_sync(~0u, threadIdx.x & 31, threadIdx.x & 31);
  const int lane = lane0;
  const int warp = wid & 3, wg = wid >> 2;
  const uint32_t rank = blockIdx.x, head = blockIdx.y, cta = head * 3 + rank;
  const uint32_t peer1 = mapa(sb, rank == 2 ? 0 : rank + 1), peer2 = mapa(sb, rank == 0 ? 2 : rank - 1);
  const int nslots = prm.nslots;

  SLOG(0);
  if (threadIdx.x == 384) {
    if ((sb & 0x3FFFF) != SMEM0) __trap();
    for (int c = 0; c < 5; c++) { mbar_init(sb + B_HFULL + 8 * c, 2); mbar_init(sb + B_HEMPTY + 8 * c, c == 4 ? 8 : 4); }
    for (int c = 0; c < 11; c++) mbar_init(sb + B_MTRY + 8 * c, 1);
    mbar_init(sb + B_PTOK, rank == 0 ? 3 : 2); mbar_init(sb + B_OB, 5); mbar_init(sb + B_OPD, 4);
    mbar_init(sb + B_OPI, 1); mbar_init(sb + B_OPI + 8, 1); mbar_init(sb + B_RFREE, 1); mbar_init(sb + B_GATE, 1); mbar_init(sb + B_PMEM, 2); mbar_init(sb + B_PSUM, 2); mbar_init(sb + B_PVI, 5); mbar_init(sb + B_OTOK, 4); mbar_init(sb + B_OTOK + 8, 4); mbar_init(sb + B_END, 15);
    for (int c = 0; c < 4; c++) mbar_init(sb + B_PACE + 8 * c, 1);
    asm volatile("fence.mbarrier_init.release.cluster;" ::: "memory");
    fence_async_smem();
  }
  asm volatile("griddepcontrol.launch_dependents;");
  asm volatile("barrier.cluster.arrive.release.aligned;" ::: "memory");

  if (wg < 2) {
  {
    uint32_t xa[10];
    const uint32_t* src = prm.x + (size_t)(cta * 8 + (lane >> 2)) * (DM / 2) + wid * 40 + (lane & 3);
#pragma unroll
    for (int i = 0; i < 10; i++) xa[i] = __ldg(src + i * 4);
    asm volatile("barrier.cluster.wait.acquire.aligned;" ::: "memory");
    first_ln(xa, cta, sb + SM_SR, wid, lane, 8);
    bar_arrive(10, 288);
  }
  if (wg == 0) {
    asm volatile("setmaxnreg.inc.sync.aligned.u32 %0;" ::"n"(RG0));
    uint32_t wq[160];
    SLOG(1);
    mbar_wait(sb + B_W, 0);
    SLOG(2);
    {
      const uint32_t ld_off = ((lane >> 4) * 8 + (lane & 7)) * 128 + (((2 * warp + ((lane >> 3) & 1)) ^ (lane & 7)) << 4);
#pragma unroll
      for (int ks = 0; ks < 40; ks++) ldsm4t(wq + 4 * ks, sb + SM_WO + ks * 2048 + ld_off);
    }
    fence_async_smem();
    bar_arrive(5, 160);
    mbar_wait(sb + B_W + 16, 0);
    SLOG(3);
    const uint32_t st_addr = pin(sb + SM_QT + (lane >> 4) * 1024 + (2 * warp + ((lane >> 3) & 1)) * 128 + (lane & 7) * 16, lane);
    const uint32_t sq_addr = pin(sb + SM_QT + (2 + (lane & 3)) * QSTR + warp * 256 + (lane >> 2) * 16, lane);
    const uint32_t to_lo = warp == 0 ? peer1 : mapa(sb, warp == 2 ? 2 : 0), to_hi = warp == 0 ? peer2 : mapa(sb, warp == 1 ? 1 : 0);
    const uint32_t sr_off = SM_SR + warp * 1920 + rank * 640, sr_bar = B_SR + warp * 8;
    const uint32_t sa0 = pin(to_lo + sr_off + lane * 16, lane), sb0 = pin(to_lo + sr_bar, lane), sa1 = pin(to_lo + sr_off + 512 + lane * 4, lane), sb1 = pin(sb0, lane);
    const uint32_t sa2 = pin(to_hi + sr_off + lane * 16, lane), sb2 = pin(to_hi + sr_bar, lane), sa3 = pin(to_hi + sr_off + 512 + lane * 4, lane), sb3 = pin(sb2, lane);
    uint32_t nsolo = 0;
#pragma unroll 1
    for (int n = 0; n < nslots; n++) {
      const uint32_t par = n & 1;
      PROFA(warp == PW);
      const bool alt = prm.slot[n] & 128;
      auto next = [&](uint64_t& d, int ks) { if ((ks & 7) == 7) dstep<10240 - 7 * 256>(d); else dstep<256>(d); };
      auto store_k = [&](const float* ka) {
        stsm2(st_addr + (SM_KT - SM_QT), pack2(ka[0], ka[1]), pack2(ka[2], ka[3]));
        stsm4(st_addr + (SM_KT - SM_QT) + 1024, pack2(ka[4], ka[5]), pack2(ka[6], ka[7]), pack2(ka[8], ka[9]), pack2(ka[10], ka[11]));
        stsm4(st_addr + (SM_KT - SM_QT) + 3072, pack2(ka[12], ka[13]), pack2(ka[14], ka[15]), pack2(ka[16], ka[17]), pack2(ka[18], ka[19]));
      };
      auto store_qt = [&](const float* q) {
        sts128(sq_addr, make_uint4(pack2(q[0], q[1]), pack2(q[4], q[5]), pack2(q[8], q[9]), pack2(q[12], q[13])));
        sts128(sq_addr + 128, make_uint4(pack2(q[2], q[3]), pack2(q[6], q[7]), pack2(q[10], q[11]), pack2(q[14], q[15])));
      };
      if (n > 0 && ((prm.slot[n] >> 8) & 255) == n) {
        {
          float qt[16];
          uint64_t rh = prm.dHt;
          mbar_wait(sb + B_OPI + (par ^ 1) * 8, ((n - 1) >> 1) & 1);
          mbar_wait(sb + B_GATE, 1);
          spin(prm.dq);
          mbar_wait(sb + B_PVI, nsolo++ & 1);
          float kt[16];
          uint64_t rk = prm.dWK;
          wg_fence();
#pragma unroll
          for (int ks = 0; ks < 40; ks++) {
            wg_ss32k(kt, rk, rh, ks != 0);
            wg_rs32(qt, wq[4 * ks], wq[4 * ks + 1], wq[4 * ks + 2], wq[4 * ks + 3], rh, ks != 0);
            if (ks < 39) { dstep<2048>(rk); next(rh, ks); }
          }
          wg_commit();
          mbar_wait(sb + B_OPD, par ^ 1);
          wg_wait<0>();
          reg_fence<16>(qt); reg_fence<16>(kt);
          store_qt(qt);
          stsm4(st_addr + (SM_KT - SM_QT) + 1024, pack2(kt[0], kt[1]), pack2(kt[2], kt[3]), pack2(kt[4], kt[5]), pack2(kt[6], kt[7]));
          stsm4(st_addr + (SM_KT - SM_QT) + 3072, pack2(kt[8], kt[9]), pack2(kt[10], kt[11]), pack2(kt[12], kt[13]), pack2(kt[14], kt[15]));
        }
        float qm[4], km[4];
        uint64_t rk = prm.dWK, rh = prm.dH;
        bool ok = false;
#pragma unroll
        for (int g = 0; g < 20; g++) {
          if ((g & 3) == 0 && !ok) mbar_wait(sb + B_HFULL + 2 * g, par);
          if (g == 0) PROF(0);
          if ((g & 3) == 3 && g < 19) ok = mbar_test(sb + B_HFULL + 2 * (g + 1), par);
          if ((g & 3) == 0) wg_fence();
#pragma unroll
          for (int ks = 2 * g; ks < 2 * g + 2; ks++) {
            wg_ss8k(km, rk, rh, ks != 0);
            wg_rs8(qm, wq[4 * ks], wq[4 * ks + 1], wq[4 * ks + 2], wq[4 * ks + 3], rh, ks != 0);
            if (ks < 39) { dstep<2048>(rk); next(rh, ks); }
          }
          if (g == 18) wg_commit();
        }
        wg_commit();
        wg_wait<1>();
        bar_arrive(2, 256);
        wg_wait<0>();
        reg_fence<4>(qm); reg_fence<4>(km);
        PROF(9);
        stsm2(st_addr + (SM_KT - SM_QT), pack2(km[0], km[1]), pack2(km[2], km[3]));
        stsm2(st_addr, pack2(qm[0], qm[1]), pack2(qm[2], qm[3]));
      } else {
      float qa[20], ka[20];
      uint64_t rk = prm.dWK, rh = prm.dH, rq;
      auto K = [&](int ks) { wg_ss40<1, 0>(ka, rk, rh, ks != 0); };
      auto Q = [&](int ks, uint64_t db) { wg_rs40(qa, wq[4 * ks], wq[4 * ks + 1], wq[4 * ks + 2], wq[4 * ks + 3], db, ks != 0); };
      constexpr QKOrder ord = qk_order();
      auto first = [&](int g, int c) { for (int i = 0; i < 76; i++) if ((ord.op[i] & 63) >> 3 == c) return i >> 2 == g; return false; };
      bool ok = true;
      mbar_wait(sb + B_HFULL, par);
#pragma unroll
      for (int g = 0; g < 19; g++) {
        if (!ok) {
#pragma unroll
          for (int c = 1; c < 5; c++) if (first(g, c)) mbar_wait(sb + B_HFULL + 8 * c, par);
          mbar_wait(sb + B_GATE, 1);
        }
        if (g == 0) PROF(0);
        if (g < 18) ok = mbar_test(sb + B_GATE, 1);
#pragma unroll
        for (int c = 1; c < 5; c++) if (first(g + 1, c)) ok &= mbar_test(sb + B_HFULL + 8 * c, par);
        wg_fence();
#pragma unroll
        for (int i = 4 * g; i < 4 * g + 4; i++) {
          const int ks = ord.op[i] & 63;
          if (i < 2 * QK_P0) {
            if (ord.op[i] & 64) K(ks);
            else { Q(ks, rh); dstep<2048>(rk); next(rh, ks); if (i == 2 * QK_P0 - 1) rq = rh; }
          } else if (ord.op[i] & 64) { K(ks); if (ks < 39) { dstep<2048>(rk); next(rh, ks); } }
          else { Q(ks, rq); next(rq, ks); }
        }
        if (g == 17) wg_commit();
      }
      wg_commit();
#pragma unroll
      for (int ks = 36; ks < 40; ks++) { Q(ks, rq); if (ks < 39) dstep<256>(rq); }
      wg_commit();
      wg_wait<2>();
      if (alt) bar_arrive(2, 256);
      mbar_wait(sb + B_OPD, par ^ 1);
      wg_wait<1>();
      if (!alt) bar_arrive(2, 256);
      reg_fence<20>(ka);
      store_k(ka);
      wg_wait<0>();
      reg_fence<20>(qa);
      PROF(9);
      stsm2(st_addr, pack2(qa[0], qa[1]), pack2(qa[2], qa[3]));
      store_qt(qa + 4);
      }
      mbar_arrive_if(lane == 0, sb + B_HEMPTY + 32);
      fence_async_smem();
      bar_sync(1, 128);
      PROF(1);
      float qa[20];
      wg_fence();
#pragma unroll
      for (int k = 0; k < 4; k++) wg_ss40<1, 1>(qa, dadd(prm.dQT, k * 256), dadd(prm.dKT, k * 256), k != 0);
      wg_commit();
      bar_arrive(7, 256);
      wg_wait<0>();
      reg_fence<20>(qa);
      PROF(3);
      if (warp < 3) {
        uint32_t p[5];
#pragma unroll
        for (int j = 0; j < 5; j++) p[j] = pack2(qa[4 * j], qa[4 * j + 1]);
        if (warp == 0) {
          st_async4(sa0, p[0], p[1], p[2], p[3], sb0);
          st_async4(sa2, p[0], p[1], p[2], p[3], sb2);
          st_async1(sa1, p[4], sb1);
          st_async1(sa3, p[4], sb3);
          sts128(sb + sr_off + lane * 16, make_uint4(p[0], p[1], p[2], p[3]));
          sts32(sb + sr_off + 512 + lane * 4, p[4]);
          __syncwarp();
          mbar_expect_if(lane == 0, sb + B_SR, 1280);
        } else {
          uint32_t h[5];
#pragma unroll
          for (int j = 0; j < 5; j++) h[j] = pack2(qa[4 * j + 2], qa[4 * j + 3]);
          spin(prm.d3);
          st_async4(sa0, p[0], p[1], p[2], p[3], sb0);
          st_async4(sa2, h[0], h[1], h[2], h[3], sb2);
          st_async1(sa1, p[4], sb1);
          st_async1(sa3, h[4], sb3);
        }
      }
    }
  } else {
    asm volatile("setmaxnreg.inc.sync.aligned.u32 %0;" ::"n"(RG1));
    uint32_t wv[160];
    mbar_wait(sb + B_W + 8, 0);
    SLOG(4);
    {
      const uint32_t ld_off = ((lane >> 4) * 8 + (lane & 7)) * 128 + (((2 * warp + ((lane >> 3) & 1)) ^ (lane & 7)) << 4);
#pragma unroll
      for (int ks = 0; ks < 40; ks++) ldsm4t(wv + 4 * ks, sb + SM_WO + ks * 2048 + ld_off);
    }
    fence_async_smem();
    bar_arrive(6, 160);
    const uint64_t dH = prm.dH;
    uint32_t op[8];
    const uint32_t ob_off = SM_OB + (4 * rank + warp) * 256 + lane * 4;
    const uint32_t oa0 = pin(peer1 + ob_off, lane), ob0 = pin(peer1 + B_OB, lane), oa1 = pin(peer2 + ob_off, lane), ob1 = pin(peer2 + B_OB, lane);
    const uint32_t oa2 = pin(oa0 + 128, lane), ob2 = pin(ob0, lane), oa3 = pin(oa1 + 128, lane), ob3 = pin(ob1, lane);
    const uint32_t o_loc = pin(sb + ob_off, lane), rs_addr = pin(sb + SM_RS + (lane & 3) * 8, lane);
    const uint32_t tok_off = pin((cta * 1024 + 64 * warp + (lane ^ (lane >> 3))) * 16, lane), keep = pin((lane & 1) ? ~0u : ~1u, lane);
    const uint32_t pb_off = pin((8 * rank + 2 * warp) * 4096 + head * 128 + lane * 4, lane);
    const uint32_t ph_off = pin(72 * 4096 + 2 * warp * 12288 + cta * 64 + (lane & 2) * 3072 + (lane >> 2) * 8 + (lane & 1) * 4, lane);
    auto store_tok = [&](int m, int lane) {
      const uint32_t ls = prm.slot[m] & 127, sig = prm.slot[m] >> 16;
      uint4* dst = (uint4*)((char*)(g_oT + (size_t)((ls >> 2) * (96 * 1024) + (ls & 3) * 256)) + tok_off);
      dst[0] = make_uint4(op[0], op[1], op[2], op[3]);
      dst[32] = make_uint4(op[4], op[5], op[6], op[7]);
      __syncwarp();
      mbar_arrive_if(sig && lane == 0, sb + B_OTOK + (ls >> 6) * 8);
    };
#pragma unroll 1
    for (int n = 0; n < nslots; n++) {
      const uint32_t par = n & 1;
      const int lane = opaque(lane0);
      PROFA(warp == PW);
      float va[20];
      const bool alt = prm.slot[n] & 128;
      mbar_expect_if(warp == 0 && lane == 0, sb + B_PTOK, rank == 0 ? 1280 : 1920);
      bar_sync(2, 256);
#pragma unroll
      for (int g = 0; g < 10; g++) {
        wg_fence();
#pragma unroll
        for (int ks = 4 * g; ks < 4 * g + 4; ks++) { wg_rs40(va, wv[4 * ks], wv[4 * ks + 1], wv[4 * ks + 2], wv[4 * ks + 3], dadd(dH, hoff(ks)), ks != 0); }
        wg_commit();
        if (g >= 2 && !(g & 1)) {
          wg_wait<1>();
          if (lane == 0) mbar_arrive(sb + B_HEMPTY + 8 * (g / 2 - 1));
        }
        if (g == 1 ? !alt : g == 2 && alt) bar_sync(7, 256);
      }
      wg_wait<0>();
      reg_fence<20>(va);
      if (lane == 0) mbar_arrive(sb + B_HEMPTY + 32);
      PROF(10);
      uint32_t vf[10];
#pragma unroll
      for (int j = 0; j < 10; j++) {
        const int i = (j + 4) % 10;
        asm volatile("cvt.rn.bf16x2.f32 %0, %1, %2;" : "=r"(vf[i]) : "f"(va[2 * i + 1]), "f"(va[2 * i]));
        if (j == 5) mbar_wait(sb + B_W + 8, 0);
      }
      uint32_t z0, z1;
      asm volatile("shr.u32 %0, %2, 5; shr.u32 %1, %2, 6;" : "=r"(z0), "=r"(z1) : "r"(lane));
      const uint32_t info = prm.slot[n];
      const uint32_t tagbit = ~(info >> 1) & ~keep;
      char* const ring = (char*)(g_part + (size_t)((((info >> 5) & 2) + (info & 1)) * PART_RING));
      char* const pb = pin(ring + pb_off, lane);
      char* const ph = ring + ph_off;
      mbar_wait(sb + B_PMEM, par);
      float om[4];
      wg_fence();
      wg_rs8(om, vf[0], vf[1], vf[2], vf[3], prm.dP, 0);
      wg_rs8(om, vf[4], vf[5], vf[6], vf[7], dadd(prm.dP, 256), 1);
      wg_rs8(om, vf[8], vf[9], z0, z1, dadd(prm.dP, 512 - (128 << 16)), 1);
      wg_commit();
      {
        wg_wait<0>();
        reg_fence<4>(om);
        const uint32_t b0 = pack2(om[0], om[1]), b1 = pack2(om[2], om[3]);
        st_async1(oa0, b0, ob0);
        st_async1(oa1, b0, ob1);
        st_async1(oa2, b1, ob2);
        st_async1(oa3, b1, ob3);
        sts32(o_loc, b0);
        sts32(o_loc + 128, b1);
        fence_async_smem();
        __syncwarp();
        mbar_arrive_if(lane == 0, sb + B_OB);
      }
      PROF(11);
      {
        float c[8];
        mbar_wait(sb + B_PSUM, par);
        const uint2 rs = lds64(rs_addr);
        const float r0 = __uint_as_float(rs.x), r1 = __uint_as_float(rs.y);
        if (n == 0) { SLOG(5); mbar_wait(sb + B_W + 24, 0); SLOG(6); }
        mbar_wait(sb + B_OB, par);
        asm volatile("fence.proxy.async::generic.acquire.sync_restrict::shared::cluster.cluster;" ::: "memory");
        PROF(16);
        if ((info & 63) == NSEG - 1) {
          mbar_wait(sb + B_OPI + par * 8, (n >> 1) & 1);
          mbar_arrive_if(warp == 3 && lane == 0, sb + B_GATE);
#pragma unroll
          for (int p = 0; p < 6; p++) st_rlx1(pb + (p >> 1) * 98304 + (p & 1) * 4096, tagbit);
          st_rlx1(ph, tagbit);
          st_rlx1(ph + 12288, tagbit);
        } else {
#pragma unroll
        for (int p = 0; p < 4; p++) {
          float* const cur = c + 4 * (p & 1);
          float* const prv = c + 4 * (~p & 1);
          if (p == 2) mbar_wait(sb + B_OPI + par * 8, (n >> 1) & 1);
          wg_fence();
#pragma unroll
          for (int ks = 0; ks < (p < 3 ? 12 : 4); ks++) {
            wg_ss8(cur, dadd(prm.dWO, p * 24576 + ks * 2048), dadd(prm.dOB[p < 3 ? p : 3 + rank], ks * 256), ks != 0);
            if (p == 3 && ks == 3) mbar_arrive_if(warp == 3 && lane == 0, sb + B_GATE);
            if (p > 0 && ks == 3) {
              wg_commit();
              wg_wait<1>();
              reg_fence<4>(prv);
              st_tagged(pb + (p - 1) * 98304, prv[0] * r0, prv[1] * r1, keep, tagbit);
              st_tagged(pb + (p - 1) * 98304 + 4096, prv[2] * r0, prv[3] * r1, keep, tagbit);
            }
          }
          if (p < 3) wg_commit();
        }
        wg_wait<0>();
        reg_fence<4>(c + 4);
        st_tagged(ph, c[4] * r0, c[5] * r1, keep, tagbit);
        st_tagged(ph + 12288, c[6] * r0, c[7] * r1, keep, tagbit);
        }
        PROF(17);
      }
      mbar_wait(sb + B_PTOK, par);
      PROF(12);
      {
        float ot[16];
        wg_fence();
        wg_rs32(ot, vf[0], vf[1], vf[2], vf[3], dadd(prm.dP, 640), 0);
        wg_rs32(ot, vf[4], vf[5], vf[6], vf[7], dadd(prm.dP, 640 + 256), 1);
        wg_rs32(ot, vf[8], vf[9], z0, z1, dadd(prm.dP, 640 + 512 - (128 << 16)), 1);
        wg_commit();
        wg_wait<0>();
        reg_fence<16>(ot);
#pragma unroll
        for (int i = 0; i < 8; i++) op[(i & 1) * 4 + (i >> 1)] = pack2(ot[2 * i], ot[2 * i + 1]);
      }
      if (lane == 0) mbar_arrive(sb + B_OPD);
      PROF(13);
      if (info & 128) spin(prm.ds);
      store_tok(n, lane);
    }
  }
  } else if (wg == 2) {
    asm volatile("setmaxnreg.dec.sync.aligned.u32 %0;" ::"n"(RG2));
    asm volatile("barrier.cluster.wait.acquire.aligned;" ::: "memory");
    if (warp == 1) {
      const uint32_t depth = prm.pf & 7;
#pragma unroll 1
      for (uint32_t i = 0; i < 20 + depth; i++) {
        if (i >= depth) {
          const uint32_t j = i - depth;
          mbar_wait_wd(sb + B_PACE + 8 * (j & 3), (j >> 2) & 1);
          if (j % 5 == 4) mbar_arrive_if(lane == 0 && (j != 14 || depth == 1), sb + B_W + (j == 4 ? 0 : j == 9 ? 16 : j == 14 ? 8 : 24));
        }
        if (i >= 20) continue;
        const uint32_t m = i / 5, k = i % 5, bar = sb + B_PACE + 8 * (i & 3);
        if (i == 10) bar_sync(5, 160);
        if (i == 15) {
          if ((prm.pf & 8) && elect_one())
            for (int q = 0; q < 4; q++) tma_pf(&mapWo, (q / 3 * 3 + rank) * 64, head * DH + q % 3 * 64);
#pragma unroll 1
          for (uint32_t j = 16 - depth; j < 15; j++) mbar_wait_wd(sb + B_PACE + 8 * (j & 3), (j >> 2) & 1);
          mbar_arrive_if(lane == 0 && depth > 1, sb + B_W + 8);
          bar_sync(6, 160);
        }
        if (elect_one()) {
          mbar_expect(bar, 16384);
          if (m < 3) tma_2d(sb + (m == 1 ? SM_WK : SM_WO) + k * 16384, m == 0 ? &mapWq : m == 1 ? &mapWk : &mapWv, cta * 64, k * 128, bar);
          else
            for (uint32_t q = 2 * k; q < 2 * k + 2; q++)
              tma_2d(sb + SM_WO + q * 8192, &mapWo, q < 9 ? (q / 3 * 3 + rank) * 64 : 576, head * DH + (q < 9 ? q % 3 : rank) * 64, bar);
        }
      }
    }
    if (warp == 2 && cta < 80 && lane < 16)
      g_mem[(cta >> 4) * 2048 + (lane >> 3) * 1024 + prm.moff + (cta & 15) * 8 + (lane & 7)] = prm.mem0[(lane & 7) * 80 + cta];
    if (warp == 3) {
      bar_sync(10, 288);
      if (lane == 0) red_rel(&g_cnt[(C_XN + (cta >> 4)) * CSTRIDE], 8);
    }
    const uint32_t grp = warp == 1 ? 1 + rank : 4 - (rank >> 1);
    constexpr float SC = 0.07216878364870322f * 1.4426950408889634f;
    const bool split = cta >= 72;
    const uint32_t wd = split ? 72 * 16 + cta * 16 : cta * 32;
    const uint32_t src_off = pin(split ? 72 * 4096 + (cta - 72) * 6144 + warp * 1536 + (lane & 2) * 32 + (lane >> 2) * 8 + (lane & 1) * 4 : cta * 4096 + warp * 1024 + lane * 4, lane);
    const uint32_t dst_off = pin(((wd >> 9) * 8192 + prm.moff * 4 + (wd & 511) + lane) * 4, lane);
    const uint32_t red = pin(sb + SM_RED + (warp < 2 ? 0 : (warp - 1) * 256) + lane * 8, lane);
    const uint32_t fl = (warp & 2) * 8 + (lane >> 3) * 4 + (lane & 3), hf = lane & 4;
    const uint32_t s0 = pin(sb + SM_SR + fl * 16 + hf * 2, lane), s1 = pin(sb + fl * 4, lane), pd = pin(s1 + hf * 64, lane);
    const uint32_t even = pin(~lane & 1, lane);
    uint32_t nred = 0;
    const uint32_t arm = pin(warp == 0 && (lane == 5 || ((lane == 1 || lane == 2) && lane + rank != 3)) ? sb + B_SR + lane * 8 : 0, lane);
#pragma unroll 1
    for (int n = 0; n < nslots; n++) {
      const uint32_t par = n & 1;
      const int lane = opaque(lane0);
      PROFA(warp == PW2);
      const uint32_t info = prm.slot[n], s = info & 63, l = (info >> 6) & 1;
      {
        mbar_expect_if(arm, arm, lane == 5 ? 2048 : 1920);
        if (warp == 0 || warp == 3) {
          mbar_wait(sb + B_SR, par);
          PROF(4);
          const uint2 a0 = lds64(s0), a1 = lds64(s0 + 640), a2 = lds64(s0 + 1280);
          const uint32_t b0 = lds32(s1 + SM_SR + 512), b1 = lds32(s1 + SM_SR + 1152), b2 = lds32(s1 + SM_SR + 1792);
          float v[6];
          v[0] = blo(a0.x) + blo(a1.x) + blo(a2.x); v[1] = bhi(a0.x) + bhi(a1.x) + bhi(a2.x);
          v[2] = blo(a0.y) + blo(a1.y) + blo(a2.y); v[3] = bhi(a0.y) + bhi(a1.y) + bhi(a2.y);
          v[4] = blo(b0) + blo(b1) + blo(b2); v[5] = bhi(b0) + bhi(b1) + bhi(b2);
          float m = fmaxf(fmaxf(v[0], v[1]), fmaxf(v[2], v[3]));
          m = fmaxf(fmaxf(m, __shfl_xor_sync(~0u, m, 4)), fmaxf(v[4], v[5]));
          {
            const float m1 = __shfl_xor_sync(~0u, m, 1), m2 = __shfl_xor_sync(~0u, m, 2), m3 = __shfl_xor_sync(~0u, m, 3);
            m = fmaxf(fmaxf(m, m1), fmaxf(m2, m3));
          }
          const float ms = -m * SC;
#pragma unroll
          for (int i = 0; i < 6; i++) v[i] = ex2(fmaf(v[i], SC, ms));
          float sum = (v[0] + v[1]) + (v[2] + v[3]);
          const float so = __shfl_xor_sync(~0u, sum, 4);
          sts32(pd + SM_P, pack2(v[0], v[1]));
          sts32(pd + SM_P + 128, pack2(v[2], v[3]));
          sts32(s1 + SM_P + 512, pack2(v[4], v[5]));
          fence_async_smem();
          __syncwarp();
          mbar_arrive_if(lane == 0, sb + B_PMEM);
          PROF(5);
          sum += so + (v[4] + v[5]);
          {
            const float t1 = __shfl_xor_sync(~0u, sum, 1), t2 = __shfl_xor_sync(~0u, sum, 2), t3 = __shfl_xor_sync(~0u, sum, 3);
            sum = (sum + t1) + (t2 + t3);
          }
          float r;
          asm("rcp.approx.ftz.f32 %0, %1;" : "=f"(r) : "f"(sum));
          sts32(sb + SM_RS + (warp & 2) * 8 + (lane >> 3) * 4, __float_as_uint(r));
          __syncwarp();
          mbar_arrive_if(lane == 0, sb + B_PSUM);
        } else {
          if (warp + rank != 3) {
            const uint32_t src = sb + SM_SR + warp * 1920;
            mbar_wait(sb + B_SR + warp * 8, par);
            const uint4 a0 = lds128(src + lane * 16), a1 = lds128(src + 640 + lane * 16), a2 = lds128(src + 1280 + lane * 16);
            const uint32_t b0 = lds32(src + 512 + lane * 4), b1 = lds32(src + 1152 + lane * 4), b2 = lds32(src + 1792 + lane * 4);
            float v[10];
            v[0] = blo(a0.x) + blo(a1.x) + blo(a2.x); v[1] = bhi(a0.x) + bhi(a1.x) + bhi(a2.x);
            v[2] = blo(a0.y) + blo(a1.y) + blo(a2.y); v[3] = bhi(a0.y) + bhi(a1.y) + bhi(a2.y);
            v[4] = blo(a0.z) + blo(a1.z) + blo(a2.z); v[5] = bhi(a0.z) + bhi(a1.z) + bhi(a2.z);
            v[6] = blo(a0.w) + blo(a1.w) + blo(a2.w); v[7] = bhi(a0.w) + bhi(a1.w) + bhi(a2.w);
            v[8] = blo(b0) + blo(b1) + blo(b2); v[9] = bhi(b0) + bhi(b1) + bhi(b2);
            {
              const int lim = 6 + 2 * grp + (lane & 24) + ((lane >> 2) & 1) - 2 * (lane & 3);
#pragma unroll
              for (int i = 2; i < 10; i++) if ((i >> 1) * 8 + (i & 1) > lim) v[i] = -INFINITY;
            }
            float m = fmaxf(fmaxf(fmaxf(v[0], v[1]), fmaxf(v[2], v[3])), fmaxf(fmaxf(v[4], v[5]), fmaxf(v[6], v[7])));
            m = fmaxf(m, fmaxf(v[8], v[9]));
            {
              const float m1 = __shfl_xor_sync(~0u, m, 1), m2 = __shfl_xor_sync(~0u, m, 2), m3 = __shfl_xor_sync(~0u, m, 3);
              m = fmaxf(fmaxf(m, m1), fmaxf(m2, m3));
            }
            const float ms = -m * SC;
#pragma unroll
            for (int i = 0; i < 10; i++) v[i] = ex2(fmaf(v[i], SC, ms));
            float sum = ((v[0] + v[1]) + (v[2] + v[3])) + ((v[4] + v[5]) + (v[6] + v[7])) + (v[8] + v[9]);
            {
              const float s1 = __shfl_xor_sync(~0u, sum, 1), s2 = __shfl_xor_sync(~0u, sum, 2), s3 = __shfl_xor_sync(~0u, sum, 3);
              sum = (sum + s1) + (s2 + s3);
            }
            float r;
            asm("rcp.approx.ftz.f32 %0, %1;" : "=f"(r) : "f"(sum));
            {
              const uint32_t row = SM_P + grp * 640;
#pragma unroll
              for (int j = 0; j < 5; j++) sts32(sb + row + j * 128 + lane * 4, pack2(v[2 * j] * r, v[2 * j + 1] * r));
              fence_async_smem();
              __syncwarp();
              mbar_arrive_if(lane == 0, sb + B_PTOK);
              if (elect_one()) {
                bulk_s2s(peer1 + row, sb + row, 640, peer1 + B_PTOK);
                bulk_s2s(peer2 + row, sb + row, 640, peer2 + B_PTOK);
              }
            }
          }
        }
      }
      const uint32_t* const src = (const uint32_t*)((char*)(g_part + (size_t)((l * 2 + (s & 1)) * PART_RING)) + src_off);
      uint32_t* const dst = (uint32_t*)pin((char*)(g_mem + l * 1024 + (~s & 1) * 512) + dst_off, lane);
      {
        const uint32_t d1 = prm.d1[cta / 24 + ((info >> 5) & 4)];
        if (warp == 3) {
          mbar_wait(sb + B_OB, par);
          mbar_arrive_if(lane == 0, sb + B_GATE);
          sts32(sb + SM_TOPI + par * 4, clk());
          __syncwarp();
          mbar_arrive_if(lane == 0, sb + B_OPI + par * 8);
          TRACE(true, n, 0, gtl());
        }
        const bool reduce = cta < 88 && s != NSEG - 1;
        if (reduce || warp == 0) mbar_wait(sb + B_OPI + par * 8, (n >> 1) & 1);
        if (!reduce) continue;
        mbar_wait(sb + B_RFREE, (nred++ & 1) ^ 1);
        mbar_wait(sb + B_GATE, 1);
        if (d1) spin(d1);
      }
      {
        uint32_t g = 0;
        float2 u;
        PROF(14);
        if (!split) {
          u = poll_sum<8>(src, ~(s >> 1), even, g);
        } else {
          u = poll_sum<12>(src, ~(s >> 1), even, g);
          u.x += __shfl_xor_sync(~0u, u.x, 2);
          u.y += __shfl_xor_sync(~0u, u.y, 2);
        }
        PROF(18);
        if (warp != 1) {
          asm volatile("st.shared.v2.f32 [%0], {%1,%2};" ::"r"(red), "f"(u.x), "f"(u.y) : "memory");
          bar_arrive(3, 128);
        } else {
          bar_sync(3, 128);
          const uint2 o0 = lds64(red), o1 = lds64(red + 256), o2 = lds64(red + 512);
          const uint32_t w = movm(pack2((u.x + __uint_as_float(o0.x)) + (__uint_as_float(o1.x) + __uint_as_float(o2.x)),
                                        (u.y + __uint_as_float(o0.y)) + (__uint_as_float(o1.y) + __uint_as_float(o2.y))));
          if (!split || lane < 16) {
            st_rlx1(dst, w);
            st_rlx1(dst + ((s & 1) ? 2048 : -2048), ~0u);
          }
          mbar_arrive_if(lane == 0, sb + B_RFREE);
        }
        PROF(19);
        PROFV(2, g);
        TRACE(warp == 1, n, 1, gtl());
        TRACE(g, n, 2, g);
      }
    }
  } else {
    asm volatile("setmaxnreg.dec.sync.aligned.u32 %0;" ::"n"(RG3));
    asm volatile("barrier.cluster.wait.acquire.aligned;" ::: "memory");
    const uint32_t chk = lane * 32 + ((lane >> 2) << 2);
    const uint32_t bar = sb + B_MTRY + 8 * warp;
    uint32_t mph = 0, waited = 0, pub = 0, pph = 0, nsolo = 0;
    auto publish = [&](uint32_t upto) {
#pragma unroll 1
      for (; pub < upto; pub++) {
        const uint32_t e = prm.slot[pub], l = (e >> 6) & 1;
        if (warp == 3 && (e >> 16)) {
          mbar_wait_wd(sb + B_OTOK + l * 8, (pph >> l) & 1);
          pph ^= 1 << l;
          if (elect_one()) red_rel(&g_cnt[(e >> 16) * CSTRIDE], 1);
        }
      }
    };
#pragma unroll 1
    for (int m = 0; m < nslots; m++) {
      const uint32_t info = prm.slot[m], prod = (info >> 8) & 255, ls = info & 127;
      uint32_t g = 0;
#pragma unroll 1
      for (; waited < prod && waited + 1 < m; waited++) mbar_wait_wd(sb + B_OPI + (waited & 1) * 8, (waited >> 1) & 1);
      uint32_t t0 = lds32(sb + SM_TOPI + (~waited & 1) * 4);
      publish(waited);
      if ((ls & 3) == 0) {
        while (__any_sync(~0u, ld_acq(&g_cnt[(C_XN + (ls >> 2)) * CSTRIDE]) < XN_TARGET)) guard(g);
        fence_async_global();
      }
#pragma unroll 1
      for (uint32_t c = warp; c < 5; c += 4) {
        const uint32_t dst = sb + SM_H + c * 10240, full = sb + B_HFULL + 8 * c;
        const uint4* src = g_mem + (c * 2048 + (ls >> 6) * 1024 + (ls & 1) * 512 + prm.moff);
        const uint32_t d = prod ? prm.d2[(m - prod) * 5 + c] : 0;
        const uint4* tok = g_xn + (size_t)(ls * 2560 + c * 512);
        const uint32_t pp = (m & 1) ^ 1;
        const bool single = waited < prod;
        mbar_wait_wd(full, pp);
        const bool solo = m > 0 && prod == m;
        const uint32_t tokb = solo ? sb + B_PVI : full;
        if (solo && c < 4) mbar_wait_wd(tokb, (nsolo++ & 1) ^ 1);
        mbar_expect_if(lane < 2 && !(solo && c == 4 && lane == 0), lane ? bar : tokb, lane ? 2048 : 8192);
        if (!single) while (__any_sync(~0u, clk() - t0 < d)) {}
        if (c >= 2) mbar_wait_wd(sb + B_HEMPTY + 8 * c, pp);
        mbar_wait_wd(sb + (c < 2 ? B_HEMPTY + 8 * c : c == 2 && !single ? B_PMEM : B_OB), pp);
        if ((c != 2 || single) && !(solo && c == 4)) { if (elect_one()) bulk_g2s(dst + 2048, tok, 8192, tokb); }
        if (single) {
          mbar_wait_wd(sb + B_OPI + (waited & 1) * 8, (waited >> 1) & 1);
          waited++;
          t0 = lds32(sb + SM_TOPI + (~waited & 1) * 4);
          if (solo && c == 0 && elect_one()) {
            mbar_expect(tokb, 8192);
            bulk_g2s(dst + 4 * 10240 + 2048, tok + 2048, 8192, tokb);
          }
          publish(waited);
          while (__any_sync(~0u, clk() - t0 < d)) {}
        }
        else if (c < 2) spin(prm.dh);
        if (elect_one()) bulk_g2s(dst, src, 2048, bar);
        if (c == 2 && !single) {
          mbar_wait_wd(sb + B_OB, pp);
          if (elect_one()) bulk_g2s(dst + 2048, tok, 8192, full);
        }
        g = 0;
        while (true) {
          mbar_wait_wd(bar, mph);
          mph ^= 1;
          const uint32_t v0 = lds32(dst + chk), v1 = lds32(dst + chk + 1024);
          if (__all_sync(~0u, v0 != ~0u && v1 != ~0u)) break;
          if (elect_one()) {
            mbar_expect(bar, 2048);
            bulk_g2s(dst, src, 2048, bar);
          }
          guard(g);
        }
        mbar_arrive_if(lane == 0, full, solo ? 2 : 1);
        TRACE(c < 2, m, 3 + 2 * c, gtl());
        TRACE(c < 2, m, 4 + 2 * c, g);
      }
    }
    publish(nslots);
    if (warp == 0) mbar_wait_wd(sb + B_END, 0);
  }
  __syncwarp();
  if (wid != 12 && lane0 == 0) mbar_arrive(sb + B_END);
  cluster_sync();
}
__device__ uint32_t g_xa[NBLK * 10 * 4096];
__device__ uint32_t g_h[NBLK * 24 * 4096];

enum { T_A = 0, T_F1 = 1, T_U = 2, T_D = 3, T_F2 = 4, T_NONE = 7 };
__host__ __device__ constexpr int c_phase(int type, int lb) { return C_O + type * 32 + lb; }
constexpr int C_TICKET = c_phase(5, 0), C_EXIT = C_TICKET + 1, C_USED = C_HALF + 2 * NBLK;
constexpr int G_NST = 7;
constexpr uint32_t GS_RED = G_NST * 32768, GS_BAR = GS_RED + 1088, G_SMEM = GS_BAR + 224;
constexpr uint32_t GB_FULL = GS_BAR, GB_EMPTY = GS_BAR + 64, GB_ORD = GS_BAR + 128, GB_READY = GS_BAR + 144, GB_ACK = GS_BAR + 152, GB_GATE = GS_BAR + 160, GB_SIG = GS_BAR + 176, GB_SACK = GS_BAR + 192,
                   GS_SIG = GS_BAR + 208, GS_COL = GS_BAR + 216;
#define FPL 6
constexpr int NF = 16;
constexpr int G_EARLY = 36;
constexpr int G_LATE = 96, PL = 6, ML = 8, DL = 30, TL = 10;
constexpr int GRC = 112, GRP = 32;
constexpr uint32_t E_UP = 1u << 8, E_HALF = 1u << 28, E_GRP = 1u << 29, E_HAND = 1u << 30, E_EXCL = 1u << 31;

struct GParams {
  __nv_bfloat16* out;
  const uint32_t* x;
  int moff, gd;
  int pend;
  uint8_t perm[G_EARLY], first[9];
  uint8_t need[5][2 * NBLK];
  uint32_t tab[G_EARLY * (PL + ML + DL) + G_LATE * TL];
};
constexpr int EL = PL + ML + DL, TAB_TAIL = G_EARLY * EL;
struct GIter {
  int p, left, period;
  uint32_t e, type, lb, n0, kb0, nkb;
  bool gemm, valid;
  DI GIter(const GParams& prm, int col) {
    if (col < G_EARLY) { p = col * EL; left = PL; period = 0; }
    else { p = TAB_TAIL + (col - G_EARLY) * TL; left = TL; period = prm.pend; }
  }
  DI bool next(const GParams& prm, int col) {
    do {
      if (left == 0) {
        if (++period > prm.pend) return false;
        left = period < prm.pend ? ML : DL;
        if (period > 1 && period < prm.pend) p -= ML;
      }
      e = prm.tab[p++]; left--;
    } while ((e & 7) == T_NONE);
    const int b = (e >> 4) & 15, blk = period < prm.pend ? period - b : b;
    type = e & 7; valid = blk >= 0; lb = (e & 8) * 2 + (blk & 15); n0 = (e >> 9) & 127; kb0 = (e >> 16) & 127;
    gemm = type != T_F1 && type != T_F2;
    nkb = valid ? (e >> 23) & 31 : 0;
    return true;
  }
  DI int id_(int pend) const { return period < pend ? period * 10 + ML - left : 160 + DL - left; }
};

#define GLOG(nt, i, v)
template <int TA> DI void wg_ss128(float* d, uint64_t da, uint64_t db, int sc) {
  asm volatile("{.reg .pred p; setp.ne.b32 p, %66, 0;\n"
               "wgmma.mma_async.sync.aligned.m64n128k16.f32.bf16.bf16 "
               "{%0,%1,%2,%3,%4,%5,%6,%7,%8,%9,%10,%11,%12,%13,%14,%15,%16,%17,%18,%19,%20,%21,%22,%23,%24,%25,%26,%27,%28,%29,%30,%31,"
               "%32,%33,%34,%35,%36,%37,%38,%39,%40,%41,%42,%43,%44,%45,%46,%47,%48,%49,%50,%51,%52,%53,%54,%55,%56,%57,%58,%59,%60,%61,%62,%63}, "
               "%64, %65, p, 1, 1, %67, 1;}"
               : ACC16(d, 0), ACC16(d, 16), ACC16(d, 32), ACC16(d, 48) : "l"(da), "l"(db), "r"(sc), "n"(TA));
}

template <int TA> DI void g_mainloop(float* acc, uint32_t sb, uint32_t hand, uint32_t gate, int nkb, int cw, int lane, uint32_t st, uint32_t ph) {
  const uint64_t da0 = (TA ? mkdesc(SMEM0, 4096, 512, 2) : mkdesc(SMEM0, 128, 1024, 0)) + (cw >> 2) * 512;
  const uint64_t db0 = mkdesc(SMEM0 + 16384, 8192, 1024, 1);
  uint32_t prev = 0;
#pragma unroll 1
  for (int kb = 0; kb < nkb; kb++) {
    mbar_wait(sb + GB_FULL + 8 * st, ph);
    mbar_wait(gate, 1);
    const uint64_t da = da0 + st * 2048, db = db0 + st * 2048;
    wg_fence();
#pragma unroll
    for (int k = 0; k < 4; k++) wg_ss128<TA>(acc, da + k * (TA ? 64 : 16), db + k * 128, 1);
    wg_commit();
    mbar_arrive_if(hand && kb == nkb - 1 && lane == 0, hand);
    wg_wait<1>();
    mbar_arrive_if(kb > 0 && lane == 0, sb + GB_EMPTY + 8 * prev);
    prev = st;
    if (++st == G_NST) { st = 0; ph ^= 1; }
  }
  wg_wait<0>();
  reg_fence<64>(acc);
  mbar_arrive_if(lane == 0, sb + GB_EMPTY + 8 * prev);
}

__global__ void __launch_bounds__(640, 1)
g_kernel(const __grid_constant__ CUtensorMap mapWo, const __grid_constant__ CUtensorMap mapWg, const __grid_constant__ CUtensorMap mapWu,
         const __grid_constant__ CUtensorMap mapWd, const __grid_constant__ GParams prm) {
  const uint32_t sb = smem_base();
  const int wid = __shfl_sync(~0u, threadIdx.x >> 5, 0), lane = threadIdx.x & 31;
  if (threadIdx.x == 0) {
    if ((sb & 0x3FFFF) != SMEM0) __trap();
    {
      uint32_t sm; asm volatile("mov.u32 %0, %%smid;" : "=r"(sm));
      uint32_t* const tk = &g_cnt[C_TICKET * CSTRIDE];
      uint32_t c = atomicAdd(tk, 1);
      if (c < G_EARLY) {
        const uint32_t k = sm < 64 ? (sm >> 1) & 7 : sm < 120 ? 1 + ((sm - 64) >> 1) % 7 : sm < 124 ? 1 + ((sm >> 1) & 1) : 0;
        const uint32_t t = atomicAdd(tk + 1 + k, 1);
        atomicAdd(tk + 9, 1);
        if (t < prm.first[k + 1] - prm.first[k]) c = prm.perm[prm.first[k] + t];
        else {
          uint32_t o = atomicAdd(tk + 10, 1), g = 0;
          while (ld_acq(tk + 9) < G_EARLY) guard(g);
          for (int j = 0; j < 8; j++)
            for (uint32_t i = prm.first[j] + ld_acq(tk + 1 + j); i < prm.first[j + 1]; i++) if (o-- == 0) c = prm.perm[i];
        }
      }
      sts32(sb + GS_COL, c);
    }
    for (int i = 0; i < G_NST; i++) { mbar_init(sb + GB_FULL + 8 * i, 1); mbar_init(sb + GB_EMPTY + 8 * i, 8); }
    mbar_init(sb + GB_ORD, 8); mbar_init(sb + GB_ORD + 8, 8); mbar_init(sb + GB_READY, 1); mbar_init(sb + GB_ACK, 1);
    mbar_init(sb + GB_GATE, 1); mbar_init(sb + GB_GATE + 8, 1);
    mbar_init(sb + GB_SIG, 8); mbar_init(sb + GB_SIG + 8, 8); mbar_init(sb + GB_SACK, 1); mbar_init(sb + GB_SACK + 8, 1);
    fence_async_smem();
  }
  __syncthreads();
  const int col = __shfl_sync(~0u, lds32(sb + GS_COL), 0);

  if (wid >= 16) {
    GIter t(prm, col);
    asm volatile("setmaxnreg.dec.sync.aligned.u32 %0;" ::"n"(GRP));
    uint32_t st = 0, ph = 1, k = 0;
    if (wid == 16) {
      while (t.next(prm, col)) {
        const CUtensorMap* m0 = t.type == T_A ? &mapWo : t.type == T_U ? &mapWg : &mapWd;
        const CUtensorMap* m1 = t.type == T_U ? &mapWu : m0;
        const int c0 = t.type == T_U ? t.n0 * 64 : (t.n0 & 7) * 128, c1 = t.type == T_U ? c0 : c0 + 64;
        if ((t.e & (E_HALF | E_UP)) == E_UP) poll_ge(&g_cnt[c_phase(t.type, t.lb) * CSTRIDE], prm.need[t.type][t.lb]);
#pragma unroll 1
        for (uint32_t kb = t.kb0; kb < t.kb0 + t.nkb; kb++) {
          mbar_wait(sb + GB_EMPTY + 8 * st, ph);
          if (elect_one()) {
            const uint32_t full = sb + GB_FULL + 8 * st, dst = sb + st * 32768;
            mbar_expect(full, (t.e & E_HALF) ? 24576 : 32768);
            tma_2d(dst + 16384, m0, c0, kb * 64, full);
            tma_2d(dst + 24576, m1, c1, kb * 64, full);
          }
          if (++st == G_NST) { st = 0; ph ^= 1; }
        }
      }
    } else if (wid == 17) {
      while (t.next(prm, col)) {
        if (!t.nkb) continue;
        const char* asrc = t.type == T_A ? (const char*)g_oT + (size_t)t.lb * (96 * 16384)
                         : t.type == T_U ? (const char*)g_xa + (size_t)(t.lb & 15) * (10 * 16384) : (const char*)g_h + (size_t)(t.lb & 15) * (24 * 16384);
        const uint32_t up = (t.e & E_HALF) ? (t.e & E_UP) * 32 : 0;
        GLOG(t.id_(prm.pend), 1, gtime());
        mbar_wait(sb + GB_READY, k & 1);
        mbar_arrive_if(lane == 0, sb + GB_ACK);
        k++;
#pragma unroll 1
        for (uint32_t kb = t.kb0; kb < t.kb0 + t.nkb; kb++) {
          mbar_wait(sb + GB_EMPTY + 8 * st, ph);
          if (elect_one()) bulk_g2s(sb + st * 32768 + up, asrc + (size_t)kb * 16384 + up, (t.e & E_HALF) ? 8192 : 16384, sb + GB_FULL + 8 * st);
          if (++st == G_NST) { st = 0; ph ^= 1; }
        }
      }
    } else if (wid == 18) {
      while (t.next(prm, col)) {
        if (!t.nkb) continue;
        const bool lower = t.type == T_A && (t.e & (E_HALF | E_UP)) == E_HALF;
        poll_ge(&g_cnt[(lower ? C_HALF + t.lb : c_phase(t.type, t.lb)) * CSTRIDE], prm.need[t.type][t.lb]);
        fence_async_global();
        GLOG(t.id_(prm.pend), 2, gtime());
        mbar_wait(sb + GB_ACK, (k & 1) ^ 1);
        mbar_arrive_if(lane == 0, sb + GB_READY);
        k++;
      }
    } else {
      uint32_t live = 3, par = 0, g = 0;
      while (live) {
        const bool ev = lane < 2 && ((live >> lane) & 1) && mbar_test(sb + GB_SIG + 8 * lane, (par >> lane) & 1);
        const uint32_t evs = __ballot_sync(~0u, ev);
        if (!evs) { guard(g); __nanosleep(20); continue; }
        const uint32_t msg = ev ? lds32(sb + GS_SIG + 4 * lane) : 0;
        mbar_arrive_if(ev, sb + GB_SACK + 8 * lane);
        mbar_arrive_if(msg >> 31, sb + GB_GATE + 8 * lane);
        if (msg) red_rel(&g_cnt[(msg & 0xffff) * CSTRIDE], (msg >> 16) & 255);
        par ^= evs;
        live &= ~__ballot_sync(~0u, ev && !msg);
        g = 0;
      }
      asm volatile("griddepcontrol.wait;" ::: "memory");
      if (col < 80 && lane < 16) g_mem[(col >> 4) * 2048 + (lane >> 3) * 1024 + 512 + prm.moff + (col & 15) * 8 + (lane & 7)] = make_uint4(~0u, ~0u, ~0u, ~0u);
      uint32_t last = 0;
      if (lane == 0) last = atomicAdd(&g_cnt[C_EXIT * CSTRIDE], 1) == gridDim.x - 1;
      if (__shfl_sync(~0u, last, 0)) {
        g_cnt[C_TICKET * CSTRIDE + lane] = 0;
        for (int i = lane; i < C_USED; i += 32) g_cnt[i * CSTRIDE] = 0;
      }
    }
  } else {
    asm volatile("setmaxnreg.inc.sync.aligned.u32 %0;" ::"n"(GRC));
    const int cw = wid & 7, wk = wid >> 3;
    GIter t(prm, col);
    uint32_t pos = 0, seen = 0, waited = 0;
    uint32_t nsig = 0;
    auto signal = [&](uint32_t msg) {
      mbar_wait(sb + GB_SACK + 8 * wk, (nsig++ & 1) ^ 1);
      if (cw == 0) sts32(sb + GS_SIG + 4 * wk, msg);
      __syncwarp();
      mbar_arrive_if(lane == 0, sb + GB_SIG + 8 * wk);
    };
    if (col < G_EARLY) {
      spin(prm.gd);
#pragma unroll 1
      for (int rg = 96 + col * 2 + wk; rg < 256; rg += 2 * G_EARLY) {
        uint32_t a[10];
        const uint32_t* src = prm.x + (size_t)(rg * 8 + (lane >> 2)) * (DM / 2) + cw * 40 + (lane & 3);
#pragma unroll
        for (int i = 0; i < 10; i++) a[i] = __ldg(src + i * 4);
        first_ln(a, rg, sb + GS_RED + wk * 512, cw, lane, 1 + wk);
        signal((C_XN + (rg >> 4)) | ((XN_TARGET / NF) << 16));
        bar_sync(1 + wk, 256);
      }
    }
    while (t.next(prm, col)) {
      const uint32_t pos0 = pos;
      pos = (pos + t.nkb) % (2 * G_NST);
      if (((t.e >> 29) & 1) != wk) { seen += (t.e >> 30) & 1; continue; }
      const uint32_t type = t.type, blk = t.lb & 15, layer = t.lb >> 4, n0 = t.n0;
      if (cw == 0 && t.valid) GLOG(t.id_(prm.pend), 0, 0x80000000u | type | (t.lb << 3) | (n0 << 8) | (t.nkb << 16));
      if (!t.gemm) {
        if (!t.valid) continue;
        const int rg = blk * 16 + n0;
        float4 v[5];
        const int off = (n0 * 40 + cw * 5) * 32 + lane, npl = t.kb0;
        const uint2* src = acc_planes(t.lb, type == T_F2) + off;
        if (cw == 0) {
          poll_ge(&g_cnt[c_phase(type, t.lb) * CSTRIDE], prm.need[type][t.lb]);
          mbar_arrive_if((t.e & E_EXCL) && lane == 0, sb + GB_GATE + 8 * wk);
          GLOG(t.id_(prm.pend), 2, gtime()); GLOG(t.id_(prm.pend), 3, gtime());
        }
        bar_sync(1 + wk, 256);
        {
          const uint32_t eye = (lane >> 3) == (lane & 3) ? ((lane & 4) ? 0x3f800000u : 0x00003f80u) : 0u;
#pragma unroll
          for (int i = 0; i < 5; i++) v[i] = make_float4(0.f, 0.f, 0.f, 0.f);
#pragma unroll 1
          for (int p0 = 0; p0 < npl; p0 += FPL) {
            uint32_t r[FPL / 2][5][4];
#pragma unroll
            for (int p = 0; p < FPL; p++)
#pragma unroll
              for (int i = 0; i < 5; i++) {
                const uint2 w = p0 + p < npl ? __ldcg(src + (size_t)(p0 + p) * PLANE + i * 32) : make_uint2(0, 0);
                r[p >> 1][i][(p & 1) * 2] = w.x; r[p >> 1][i][(p & 1) * 2 + 1] = w.y;
              }
#pragma unroll
            for (int p = 0; p < FPL / 2; p++) {
              if (p0 + 2 * p >= npl) break;
              if (t.e & E_EXCL) {
#pragma unroll
                for (int i = 0; i < 5; i++) mma16816(&v[i].x, r[p][i], eye, eye);
              } else {
#pragma unroll
                for (int i = 0; i < 5; i++) {
                  const uint32_t* w = r[p][i];
                  v[i].x += blo(w[0]) + blo(w[2]); v[i].y += bhi(w[0]) + bhi(w[2]); v[i].z += blo(w[1]) + blo(w[3]); v[i].w += bhi(w[1]) + bhi(w[3]);
                }
              }
            }
          }
        }
        if (type == T_F2 && layer == 1) {
          uint2* dst = (uint2*)prm.out + (size_t)(rg * 8 + (lane >> 2)) * (DM / 4) + cw * 20 + (lane & 1) * 2 + ((lane >> 1) & 1);
#pragma unroll
          for (int i = 0; i < 5; i++) {
            const uint32_t a = pack2(v[i].x, v[i].y), b = pack2(v[i].z, v[i].w);
            const uint32_t o = __shfl_xor_sync(~0u, (lane & 1) ? a : b, 1);
            dst[i * 4] = (lane & 1) ? make_uint2(o, b) : make_uint2(a, o);
          }
        } else {
          uint2* nx = (type == T_F1 ? acc_planes(t.lb, 1) : acc_planes(NBLK + blk, 0)) + off;
#pragma unroll
          for (int i = 0; i < 5; i++) {
            const uint2 w = make_uint2(pack2(v[i].x, v[i].y), pack2(v[i].z, v[i].w));
            nx[i * 32] = w;
            v[i] = make_float4(blo(w.x), bhi(w.x), blo(w.y), bhi(w.y));
          }
          float mean, rstd;
          ln_stats(v, sb + GS_RED + wk * 512, cw, lane, 1 + wk, mean, rstd);
          if (type == T_F2) store_img<4, 2048>(xn_row_group(1, rg) + lane, v, cw, mean, rstd);
          else store_img<3, 4096>(g_xa + (size_t)(blk * 10 * 4096 + n0 * 256) + lane, v, cw, mean, rstd);
        }
      } else {
        float acc[64];
#pragma unroll
        for (int j = 0; j < 64; j++) acc[j] = 0.f;
        if (waited != seen) { mbar_wait(sb + GB_ORD + 8 * (wk ^ 1), waited & 1); waited++; }
        const uint32_t hand = (t.e & E_HAND) ? sb + GB_ORD + 8 * wk : 0;
        if (!t.valid) { mbar_arrive_if(hand && lane == 0, hand); continue; }
        if (cw == 0) GLOG(t.id_(prm.pend), 3, gtime());
        const uint32_t ph = pos0 >= G_NST, st = pos0 - ph * G_NST, early = (t.e & E_EXCL) ? 0 : hand;
        const bool idle = (t.e & E_HALF) && ((t.e >> 8) & 1) != (cw >> 2);
        if (idle) {
          uint32_t s2 = st, p2 = ph;
#pragma unroll 1
          for (uint32_t kb = 0; kb < t.nkb; kb++) {
            mbar_wait(sb + GB_FULL + 8 * s2, p2);
            mbar_arrive_if(lane == 0, sb + GB_EMPTY + 8 * s2);
            if (++s2 == G_NST) { s2 = 0; p2 ^= 1; }
          }
          mbar_arrive_if(early && lane == 0, early);
        } else if (type == T_A) g_mainloop<1>(acc, sb, early, sb + GB_GATE + 8 * (wk ^ 1), t.nkb, cw, lane, st, ph);
        else g_mainloop<0>(acc, sb, early, sb + GB_GATE + 8 * (wk ^ 1), t.nkb, cw, lane, st, ph);
        if (cw == 0) GLOG(t.id_(prm.pend), 4, gtime());
        if (idle) {
        } else if (type == T_U) {
          uint32_t* dst = g_h + (size_t)((blk * 24 + n0) * 4096 + cw * 512) + lane;
#pragma unroll
          for (int j = 0; j < 8; j++) {
            float h[4];
#pragma unroll
            for (int e = 0; e < 4; e++) {
              float th;
              asm("tanh.approx.f32 %0, %1;" : "=f"(th) : "f"(0.5f * acc[4 * j + e]));
              h[e] = acc[32 + 4 * j + e] * fmaf(th, 0.5f, 0.5f);
            }
            dst[j * 32] = pack2(h[0], h[1]);
            dst[j * 32 + 256] = pack2(h[2], h[3]);
          }
        } else {
          uint2* dst = acc_planes(t.lb, type == T_D) + (size_t)((1 + (n0 >> 3)) * PLANE + (2 * cw * 40 + (n0 & 7) * 8) * 32) + lane;
#pragma unroll
          for (int j = 0; j < 16; j++) {
            const float* a = acc + (j >> 1) * 8 + (j & 1) * 2;
            dst[(j >> 1) * 32 + (j & 1) * 1280] = make_uint2(pack2(a[0], a[1]), pack2(a[4], a[5]));
          }
        }
        mbar_arrive_if(hand != early && lane == 0, hand);
      }
      if (cw == 0) GLOG(t.id_(prm.pend), 5, gtime());
      if (cw == 0) GLOG(t.id_(prm.pend), 6, gtime());
      if (type == T_F2 && layer == 1) mbar_arrive_if((t.e & E_EXCL) && cw == 0 && lane == 0, sb + GB_GATE + 8 * wk);
      else
        signal((type != T_F2 ? c_phase(type + 1, t.lb) | (1 << 16) : (C_XN + NBLK + blk) | ((XN_TARGET / NF) << 16)) | (t.gemm ? 0 : t.e & E_EXCL));
    }
    signal(0);
  }
}

typedef CUresult (*EncodeFn)(CUtensorMap*, CUtensorMapDataType, cuuint32_t, void*, const cuuint64_t*, const cuuint64_t*, const cuuint32_t*,
                             const cuuint32_t*, CUtensorMapInterleave, CUtensorMapSwizzle, CUtensorMapL2promotion, CUtensorMapFloatOOBfill);
static CUtensorMap make_map(EncodeFn fn, const void* p, uint64_t inner, uint64_t outer, uint32_t bi, uint32_t bo, int promo = 3) {
  CUtensorMap m;
  cuuint64_t dims[2] = {inner, outer}, str[1] = {inner * 2};
  cuuint32_t box[2] = {bi, bo}, es[2] = {1, 1};
  fn(&m, CU_TENSOR_MAP_DATA_TYPE_BFLOAT16, 2, (void*)p, dims, str, box, es, CU_TENSOR_MAP_INTERLEAVE_NONE, CU_TENSOR_MAP_SWIZZLE_128B,
     (CUtensorMapL2promotion)promo, CU_TENSOR_MAP_FLOAT_OOB_FILL_NONE);
  return m;
}
struct Tune {
  int lag = 11, excl = 6, gonly = 0, xl = 1, ronly = 0, pn = 30;
  int da = 120, db = 350, dc = 650, dd = 650, d2 = 2170, p1 = 300, p2 = 800;
  int ea = 60, eb = 310, ec = 550, ed = 550, e2 = 2200, q1 = 200, q2 = 400, d3 = 60, moff = 192, ds = 400, dh = 60, pa = 0, pb = 0, pc = 0, pd = 0, pe = 0, pf = 0, pg = 0, ph = 0, wpf = 4, gd = 22000, dq = 300, sl = 18, pr = 2, pg2 = 3;
};
static void fill_r(RParams& p, const Tune& t, int lag, int n0, int n1) {
  r_fill_desc(p);
  p.nslots = 0; p.d3 = t.d3; p.pn = t.pn; p.moff = t.moff; p.ds = t.ds; p.dh = t.dh; p.dq = t.dq;
  for (int c = 0; c < 5; c++) { p.d2[c] = t.d2 + (c == 0 ? 0 : c < 3 ? t.p1 : t.p2); p.d2[5 + c] = t.e2 + (c == 0 ? 0 : c < 3 ? t.q1 : t.q2); }
  const int d1[8] = {t.da, t.db, t.dc, t.dd, t.ea, t.eb, t.ec, t.ed};
  for (int i = 0; i < 8; i++) p.d1[i] = d1[i];
  int last[2] = {0, 0}, n = 0;
  for (int s0 = 0; s0 < NSEG + lag; s0++)
    for (int l = 0; l < 2; l++) {
      const int s = l ? s0 - lag : s0;
      if (s < 0 || s >= NSEG) continue;
      if (n >= n0 && n < n1) { p.slot[p.nslots] = s | (l << 6) | (last[l] << 8) | (((s & 3) == 3 ? C_O + l * NBLK + s / 4 : s == (l ? 61 : 1) ? C_HALF + l * NBLK + s / 4 : 0) << 16); last[l] = ++p.nslots; }
      n++;
    }
  for (int i = 0; i + 1 < p.nslots; i++) if (((p.slot[i] ^ p.slot[i + 1]) >> 6) & 1) p.slot[i] |= 128;
}
static uint32_t g_entry(int grp, int type, int layer, int blk, int i, int ks) {
  int n0 = i, kb0 = 0, kb1 = type == T_U ? 10 : 0;
  if (type == T_F1 || type == T_F2) kb0 = kb1 = ks + 1;
  if (type == T_A || type == T_D) {
    const int KB = type == T_A ? 96 : 24, sp = i / 5;
    n0 = i % 5 | (sp << 3); kb0 = sp * KB / ks; kb1 = (sp + 1) * KB / ks;
  }
  return type | (layer << 3) | (blk << 4) | (n0 << 9) | (kb0 << 16) | ((kb1 - kb0) << 23) | (grp ? E_GRP : 0);
}
static bool g_is_gemm(uint32_t e) { return (e & 7) == T_A || (e & 7) == T_U || (e & 7) == T_D; }
static void g_handover(uint32_t* e, int len) {
  uint32_t next = 0;
  for (int i = len - 1; i >= 0; i--)
    if (g_is_gemm(e[i])) { if ((e[i] & E_GRP) != next) e[i] |= E_HAND; next = e[i] & E_GRP; }
}
static bool g_overflow = false;
struct GList {
  static void overflow() { g_overflow = true; }
  bool shared = false;
  GParams& g; uint32_t* tab; int ncol, stride, len, n[G_LATE], load[G_LATE], grp[G_LATE];
  GList(GParams& g_, uint32_t* t, int nc, int st, int l) : g(g_), tab(t), ncol(nc), stride(st), len(l) { for (int c = 0; c < nc; c++) { n[c] = load[c] = 0; grp[c] = 1; } }
  void add(int type, int lb, int ks, int c0, int c1, uint32_t flags = 0, int i0 = 0, int i1 = 999, int step = 1) {
    const int half = (flags & E_HALF) != 0, ln = type == T_F1 || type == T_F2;
    const int cnt = (type == T_U ? 24 : ln ? NF : 5 * ks) << half;
    if (type < T_F2) g.need[type + 1][lb] = cnt;
    int used[G_LATE] = {0};
    for (int i = i0; i < cnt && i < i1; i += step) {
      int best = c0;
      for (int c = c0; c < c1; c++) if (used[c] < used[best] || (used[c] == used[best] && load[c] < load[best])) best = c;
      used[best]++;
      if (!ln) grp[best] ^= 1;
      const uint32_t e = g_entry(grp[best], type, lb >> 4, lb & 15, i >> half, ks) | flags | (ln && !shared ? E_EXCL : 0) | ((i & half) ? E_UP : 0);
      if (n[best] >= len) { overflow(); return; }
      tab[best * stride + n[best]++] = e;
      load[best] += (((e >> 23) & 31) >> half) + 2;
    }
  }
  void put(int c, uint32_t e) { if (n[c] >= len) { overflow(); return; } tab[c * stride + n[c]++] = e; if (g_is_gemm(e)) grp[c] = (e & E_GRP) != 0; }
  void finish() { for (int c = 0; c < ncol; c++) g_handover(tab + c * stride, len); }
};
static void fill_g(GParams& g, const Tune& t, void* out) {
  g.out = (__nv_bfloat16*)out;  g.pend = NBLK - 2;
  for (int b = 0; b < 2 * NBLK; b++) {
    g.need[T_A][b] = 96; g.need[T_F1][b] = 20; g.need[T_U][b] = NF; g.need[T_D][b] = 32; g.need[T_F2][b] = 15;
  }
  {
    const uint8_t perm[G_EARLY] = {0, 1, 2, 3, 16, 17, 18, 19, 34, 35, 4, 20, 21, 15, 22, 23, 5, 6, 7, 8, 9, 24, 25, 26, 10, 11, 12, 13, 14, 27, 28, 29, 30, 31, 32, 33};
    const uint8_t first[9] = {0, 10, 13, 16, 20, 24, 28, 32, 36};
    const int* pk = &t.pa;
    for (int i = 0; i < G_EARLY; i++) g.perm[i] = t.pa ? (pk[i / 5] >> (6 * (i % 5))) & 63 : perm[i];
    for (int i = 0; i < 9; i++) g.first[i] = first[i];
  }
  for (uint32_t& e : g.tab) e = T_NONE;
  GList pr(g, g.tab, G_EARLY, EL, PL);
  pr.add(T_A, 0, 7, 1, 36, E_HALF, 0, 999, 2); pr.add(T_A, 0, 7, 1, 36, E_HALF, 1, 999, 2); pr.add(T_F1, 0, 7, 20, 36); pr.add(T_U, 0, 0, 12, 36);
  pr.add(T_D, 0, 3, 20, 36); pr.add(T_F2, 0, 3, 20, 36);
  pr.finish();
  const int d = 3;
  const uint32_t xa = (t.excl & 1) ? E_EXCL : 0, xu = (t.excl & 2) ? E_EXCL : 0, xd = (t.excl & 4) ? E_EXCL : 0;
  for (int c = 0; c < G_EARLY; c++) {
    uint32_t* e = g.tab + c * EL + PL;
    if (c < 20) {
      *e++ = g_entry(0, T_A, 0, 0, c, 4) | xa;
      if (c < NF) *e++ = g_entry(0, T_F1, 0, 0, c, 4) | ((t.xl & 1) ? E_EXCL : 0);
      *e++ = g_entry(1, T_A, 1, d, c, 4);
      if (c >= 20 - NF) *e++ = g_entry(1, T_F1, 1, d, c - (20 - NF), 4);
    } else {
      const int j = c - 20;
      const uint32_t hf = E_HALF | ((j & 1) ? E_UP : 0);
      *e++ = g_entry(0, T_U, 0, 0, j, 0);
      *e++ = g_entry(1, T_U, 0, 0, 16 + j / 2, 0) | hf | xu;
      *e++ = g_entry(0, T_U, 1, d + 1, 16 + j / 2, 0) | hf;
      if (j < 15) *e++ = g_entry(1, T_D, 0, 0, j, 3) | xd;
      *e++ = g_entry(1, T_F2, 0, 0, j, 3) | ((t.xl & 2) ? E_EXCL : 0);
      if (j < 15) *e++ = g_entry(0, T_D, 1, d + 1, j, 3);
      *e++ = g_entry(0, T_U, 1, d, j, 0);
      *e++ = g_entry(1, T_F2, 1, d + 1, j, 3);
    }
    g_handover(g.tab + c * EL + PL, ML);
  }
  GList dr(g, g.tab + PL + ML, G_EARLY, EL, DL);
  GList tl(g, g.tab + TAB_TAIL, G_LATE, TL, TL);
  const int L1 = NBLK;
  auto ufull = [&](int lb, uint32_t fl) { dr.add(T_U, lb, 0, 20, 36, fl, 0, 16); g.need[T_D][lb] = 32; };
  auto uhalf = [&](int lb, int c0, uint32_t fl) { dr.add(T_U, lb, 0, c0, 36, E_HALF | fl, 32); g.need[T_D][lb] = 32; };
  for (int c = 0; c < G_EARLY; c++)
    for (int i = 0; i < ML; i++) {
      uint32_t e = g.tab[c * EL + PL + i] & ~E_HAND;
      const uint32_t ty = e & 7;
      if (ty == T_NONE || ((e & 8) && (ty == T_F2 || (ty == T_U && !(e & E_HALF))))) continue;
      e = (e & ~0xf0u) | (14 - ((e >> 4) & 15)) << 4;
      dr.put(c, e | (ty == T_F2 ? E_EXCL : 0));
    }
  dr.add(T_A, 15, 4, 0, 20, E_EXCL);
  dr.add(T_F1, 15, 4, 4, 20);
  dr.add(T_U, 15, 0, 12, 36, E_EXCL);
  for (int c = 0; c < 20; c++) {
    const int tile = c % 5, sp = c / 5, len = tile < 2 ? (96 - t.sl) / 3 : 48 - t.sl, nl = tile < 2 ? 3 : 2;
    const int k0 = sp <= nl ? sp * len : nl * len + t.sl, nk = sp < nl ? len : sp == 3 ? 96 - k0 : t.sl;
    dr.put(c, (g_entry(dr.grp[c] ^ 1, T_A, 1, 12, c, 4) & ~0x0fff0000u) | k0 << 16 | nk << 23);
  }
  dr.add(T_F1, L1 + 12, 4, 0, 16);
  dr.add(T_A, L1 + 13, 4, 0, 20);
  dr.add(T_D, 15, 3, 20, 36, E_EXCL); dr.add(T_F2, 15, 3, 20, 36);
  ufull(L1 + 11, 0); uhalf(L1 + 11, 20, 0);
  dr.add(T_A, L1 + 14, 4, 0, 20, E_EXCL);
  dr.add(T_F1, L1 + 13, 4, 0, 20);
  dr.add(T_D, L1 + 11, 3, 20, 36);
  ufull(L1 + 12, E_UP); uhalf(L1 + 12, 12, E_EXCL);
  dr.add(T_A, L1 + 15, 7, 0, 35, E_HALF | E_EXCL, 0, 999, 2); dr.add(T_A, L1 + 15, 7, 0, 35, E_HALF | E_EXCL, 1, 999, 2);
  dr.add(T_F1, L1 + 15, 7, 20, 36);
  dr.add(T_F2, L1 + 10, 3, 0, 20);
  dr.shared = true; dr.add(T_F2, L1 + 11, 3, 4, 20); dr.shared = false;
  dr.add(T_D, L1 + 13, 3, 4, 20, E_UP);
  dr.add(T_F2, L1 + 12, 3, 0, 20);
  dr.finish();
  tl.add(T_D, L1 + 12, 3, 72, G_LATE);
  tl.add(T_U, L1 + 13, 0, 24, 48, E_EXCL);
  tl.add(T_F1, L1 + 14, 4, 0, 48);
  tl.add(T_U, L1 + 14, 0, 0, 24);
  tl.add(T_D, L1 + 14, 4, 0, 48, E_HALF | E_EXCL);
  tl.add(T_U, L1 + 15, 0, 48, G_LATE, E_HALF);
  tl.add(T_D, L1 + 15, 4, 48, G_LATE, E_HALF);
  tl.add(T_F2, L1 + 13, 3, 48, 72);
  tl.add(T_F2, L1 + 14, 4, 0, 48);
  tl.add(T_F2, L1 + 15, 4, 48, G_LATE);
  tl.finish();
}
static void launch_all(void* const* d_in, void* d_out, const Tune& t, cudaStream_t st) {
  static EncodeFn fn = nullptr;
  if (!fn) {
    void* f = nullptr;
    cudaDriverEntryPointQueryResult qr;
    cudaGetDriverEntryPoint("cuTensorMapEncodeTiled", &f, cudaEnableDefault, &qr);
    fn = (EncodeFn)f;
    cudaFuncSetAttribute(r_kernel, cudaFuncAttributeMaxDynamicSharedMemorySize, R_SMEM);
    cudaFuncSetAttribute(g_kernel, cudaFuncAttributeMaxDynamicSharedMemorySize, G_SMEM);
  }
  const CUtensorMap mq = make_map(fn, d_in[2], HD, DM, 64, 128, t.pr), mk = make_map(fn, d_in[3], HD, DM, 64, 128, t.pr), mv = make_map(fn, d_in[4], HD, DM, 64, 128, t.pr),
                    mo = make_map(fn, d_in[5], DM, HD, 64, 64, t.pg2), mg = make_map(fn, d_in[8], FF, DM, 64, 64, t.pg2), mu = make_map(fn, d_in[9], FF, DM, 64, 64, t.pg2),
                    md = make_map(fn, d_in[10], DM, FF, 64, 64, t.pg2);
  auto launch_r = [&](int lag, int n0, int n1) {
    RParams p;
    fill_r(p, t, lag, n0, n1);
    for (int i = 0; i < 4; i++) p.w[i] = (const char*)d_in[2 + i];
    p.mem0 = (const uint4*)d_in[1]; p.x = (const uint32_t*)d_in[0]; p.pf = t.wpf;
    cudaLaunchConfig_t cfg = {};
    cfg.gridDim = dim3(3, NH); cfg.blockDim = dim3(512); cfg.dynamicSmemBytes = R_SMEM; cfg.stream = st;
    cudaLaunchAttribute at[1];
    at[0].id = cudaLaunchAttributeClusterDimension; at[0].val.clusterDim.x = 3; at[0].val.clusterDim.y = 1; at[0].val.clusterDim.z = 1;
    cfg.attrs = at; cfg.numAttrs = 1;
    cudaLaunchKernelEx(&cfg, r_kernel, mq, mk, mv, mo, p);
  };
  auto launch_g = [&](const GParams& g, bool pdl) {
    cudaLaunchConfig_t cfg = {};
    cfg.gridDim = dim3(132); cfg.blockDim = dim3(640); cfg.dynamicSmemBytes = G_SMEM; cfg.stream = st;
    cudaLaunchAttribute at[2];
    at[0].id = cudaLaunchAttributeProgrammaticStreamSerialization; at[0].val.programmaticStreamSerializationAllowed = 1;
    cfg.attrs = at; cfg.numAttrs = pdl ? 1 : 0;
    cudaLaunchKernelEx(&cfg, g_kernel, mo, mg, mu, md, g);
  };
  GParams g;
  fill_g(g, t, d_out);
  g.moff = t.moff; g.gd = t.gd; g.x = (const uint32_t*)d_in[0];
  launch_r(t.lag, 0, 2 * NSEG);
  launch_g(g, true);
}

extern "C" void kernel_launch(void* const* d_in, const int* in_sizes, int n_in, void* d_out, int out_size) {
  launch_all(d_in, d_out, Tune(), cudaStreamPerThread);
}
```

```cpp
#include <cuda_runtime.h>
#include <cuda_bf16.h>
#include <cuda.h>
#include <stdint.h>
#include <stdlib.h>

constexpr int SEQ = 2048, DM = 640, NH = 32, DH = 192, HD = NH * DH, FF = 1536;
constexpr int NSEG = 64, SEGL = 32, NMEM = 8;
constexpr int NBLK = 16;

#define DI __device__ __forceinline__

DI uint32_t smem_base() {
  extern __shared__ __align__(1024) unsigned char smem_raw[];
  uint32_t a;
  asm volatile("{.reg .u64 t; cvta.to.shared.u64 t, %1; cvt.u32.u64 %0, t;}" : "=r"(a) : "l"(smem_raw));
  return a;
}
DI uint32_t mapa(uint32_t a, uint32_t r) {
  uint32_t o;
  asm("mapa.shared::cluster.u32 %0, %1, %2;" : "=r"(o) : "r"(a), "r"(r));
  return o;
}
DI void mbar_init(uint32_t bar, uint32_t cnt) { asm volatile("mbarrier.init.shared::cta.b64 [%0], %1;" ::"r"(bar), "r"(cnt) : "memory"); }
DI void mbar_arrive(uint32_t bar) { asm volatile("mbarrier.arrive.shared::cta.b64 _, [%0];" ::"r"(bar) : "memory"); }
DI void mbar_expect(uint32_t bar, uint32_t tx) { asm volatile("mbarrier.arrive.expect_tx.shared::cta.b64 _, [%0], %1;" ::"r"(bar), "r"(tx) : "memory"); }
DI void mbar_arrive_if(bool p, uint32_t bar) { asm volatile("{.reg .pred p; setp.ne.b32 p, %1, 0; @p mbarrier.arrive.shared::cta.b64 _, [%0];}" ::"r"(bar), "r"((int)p) : "memory"); }
DI void mbar_arrive_if(bool p, uint32_t bar, uint32_t cnt) {
  asm volatile("{.reg .pred p; setp.ne.b32 p, %1, 0; @p mbarrier.arrive.shared::cta.b64 _, [%0], %2;}" ::"r"(bar), "r"((int)p), "r"(cnt) : "memory");
}
DI void mbar_expect_if(bool p, uint32_t bar, uint32_t tx) {
  asm volatile("{.reg .pred p; setp.ne.b32 p, %2, 0; @p mbarrier.arrive.expect_tx.shared::cta.b64 _, [%0], %1;}" ::"r"(bar), "r"(tx), "r"((int)p) : "memory");
}
DI bool mbar_test(uint32_t bar, uint32_t par) {
  uint32_t ok;
  asm volatile("{.reg .pred p; mbarrier.test_wait.parity.shared::cta.b64 p, [%1], %2; selp.u32 %0, 1, 0, p;}" : "=r"(ok) : "r"(bar), "r"(par) : "memory");
  return ok;
}
DI void mbar_wait(uint32_t bar, uint32_t par) {
  asm volatile(
      "{.reg .pred p;\n"
      "LOOP:\n"
      "mbarrier.try_wait.parity.shared::cta.b64 p, [%0], %1;\n"
      "@!p bra LOOP;\n}" ::"r"(bar), "r"(par) : "memory");
}
DI void mbar_wait_wd(uint32_t bar, uint32_t par) {
  asm volatile(
      "{.reg .pred p; .reg .u32 c;\n"
      "mov.u32 c, 0;\n"
      "LOOP:\n"
      "mbarrier.try_wait.parity.shared::cta.b64 p, [%0], %1;\n"
      "@p bra DONE;\n"
      "add.u32 c, c, 1;\n"
      "setp.lt.u32 p, c, 4000000;\n"
      "@p bra LOOP;\n"
      "trap;\n"
      "DONE:\n}" ::"r"(bar), "r"(par) : "memory");
}
DI void fence_async_smem() { asm volatile("fence.proxy.async.shared::cta;" ::: "memory"); }
DI void fence_async_global() { asm volatile("fence.proxy.async.global;" ::: "memory"); }
DI void bar_sync(int id, int n) { asm volatile("bar.sync %0, %1;" ::"r"(id), "r"(n) : "memory"); }
DI void bar_arrive(int id, int n) { asm volatile("bar.arrive %0, %1;" ::"r"(id), "r"(n) : "memory"); }
DI void cluster_sync() { asm volatile("barrier.cluster.arrive.release.aligned; barrier.cluster.wait.acquire.aligned;" ::: "memory"); }
DI bool elect_one() {
  uint32_t p;
  asm volatile("{.reg .pred p; elect.sync _|p, 0xffffffff; selp.u32 %0, 1, 0, p;}" : "=r"(p));
  return p;
}
DI void bulk_g2s(uint32_t dst, const void* src, uint32_t bytes, uint32_t bar) {
  asm volatile("cp.async.bulk.shared::cluster.global.mbarrier::complete_tx::bytes [%0], [%1], %2, [%3];" ::"r"(dst), "l"(src), "r"(bytes), "r"(bar) : "memory");
}
DI void bulk_s2s(uint32_t dst, uint32_t src, uint32_t bytes, uint32_t bar) {
  asm volatile("cp.async.bulk.shared::cluster.shared::cta.mbarrier::complete_tx::bytes [%0], [%1], %2, [%3];" ::"r"(dst), "r"(src), "r"(bytes), "r"(bar) : "memory");
}
DI void tma_2d(uint32_t dst, const CUtensorMap* map, int c0, int c1, uint32_t bar) {
  asm volatile("cp.async.bulk.tensor.2d.shared::cluster.global.mbarrier::complete_tx::bytes [%0], [%1, {%3, %4}], [%2];" ::"r"(dst), "l"(map), "r"(bar), "r"(c0), "r"(c1) : "memory");
}
DI void st_async4(uint32_t a, uint32_t x, uint32_t y, uint32_t z, uint32_t w, uint32_t bar) {
  asm volatile("st.async.shared::cluster.mbarrier::complete_tx::bytes.v4.b32 [%0], {%1,%2,%3,%4}, [%5];" ::"r"(a), "r"(x), "r"(y), "r"(z), "r"(w), "r"(bar) : "memory");
}
DI void st_async1(uint32_t a, uint32_t x, uint32_t bar) {
  asm volatile("st.async.shared::cluster.mbarrier::complete_tx::bytes.b32 [%0], %1, [%2];" ::"r"(a), "r"(x), "r"(bar) : "memory");
}
DI void sts32(uint32_t a, uint32_t x) { asm volatile("st.shared.b32 [%0], %1;" ::"r"(a), "r"(x) : "memory"); }
DI void sts128(uint32_t a, uint4 v) { asm volatile("st.shared.v4.b32 [%0], {%1,%2,%3,%4};" ::"r"(a), "r"(v.x), "r"(v.y), "r"(v.z), "r"(v.w) : "memory"); }
DI uint32_t lds32(uint32_t a) { uint32_t v; asm volatile("ld.shared.b32 %0, [%1];" : "=r"(v) : "r"(a) : "memory"); return v; }
DI uint2 lds64(uint32_t a) { uint2 v; asm volatile("ld.shared.v2.b32 {%0,%1}, [%2];" : "=r"(v.x), "=r"(v.y) : "r"(a) : "memory"); return v; }
DI uint4 lds128(uint32_t a) { uint4 v; asm volatile("ld.shared.v4.b32 {%0,%1,%2,%3}, [%4];" : "=r"(v.x), "=r"(v.y), "=r"(v.z), "=r"(v.w) : "r"(a) : "memory"); return v; }
DI void stsm4(uint32_t a, uint32_t r0, uint32_t r1, uint32_t r2, uint32_t r3) {
  asm volatile("stmatrix.sync.aligned.m8n8.x4.shared.b16 [%0], {%1,%2,%3,%4};" ::"r"(a), "r"(r0), "r"(r1), "r"(r2), "r"(r3) : "memory");
}
DI void stsm2(uint32_t a, uint32_t r0, uint32_t r1) {
  asm volatile("stmatrix.sync.aligned.m8n8.x2.shared.b16 [%0], {%1,%2};" ::"r"(a), "r"(r0), "r"(r1) : "memory");
}
DI uint32_t movm(uint32_t a) { uint32_t d; asm volatile("movmatrix.sync.aligned.m8n8.trans.b16 %0, %1;" : "=r"(d) : "r"(a)); return d; }
DI uint32_t pack2(float lo, float hi) { uint32_t d; asm("cvt.rn.bf16x2.f32 %0, %1, %2;" : "=r"(d) : "f"(hi), "f"(lo)); return d; }
DI void st_rlx1(void* p, uint32_t x) { asm volatile("st.relaxed.gpu.global.u32 [%0], %1;" ::"l"(p), "r"(x) : "memory"); }
DI uint32_t ld_acq(const uint32_t* p) { uint32_t v; asm volatile("ld.acquire.gpu.global.u32 %0, [%1];" : "=r"(v) : "l"(p) : "memory"); return v; }
DI uint32_t ld_rlx(const uint32_t* p) { uint32_t v; asm volatile("ld.relaxed.gpu.global.u32 %0, [%1];" : "=r"(v) : "l"(p) : "memory"); return v; }
DI void red_rel(uint32_t* p, uint32_t v) { asm volatile("red.release.gpu.global.add.u32 [%0], %1;" ::"l"(p), "r"(v) : "memory"); }
DI void guard(uint32_t& g) { asm volatile("{.reg .pred p; add.u32 %0, %0, 1; setp.gt.u32 p, %0, 8000000; @p trap;}" : "+r"(g)); }
DI void poll_ge(const uint32_t* p, uint32_t target) {
  asm volatile(
      "{.reg .pred p; .reg .u32 v;\n"
      "LOOP:\n"
      "ld.acquire.gpu.global.u32 v, [%0];\n"
      "setp.lt.u32 p, v, %1;\n"
      "vote.sync.any.pred p, p, 0xffffffff;\n"
      "@p bra.uni LOOP;\n}" ::"l"(p), "r"(target) : "memory");
}
DI float ex2(float x) { float y; asm("ex2.approx.ftz.f32 %0, %1;" : "=f"(y) : "f"(x)); return y; }

DI void wg_fence() { asm volatile("wgmma.fence.sync.aligned;" ::: "memory"); }
DI void wg_commit() { asm volatile("wgmma.commit_group.sync.aligned;" ::: "memory"); }
template <int N> DI void wg_wait() { asm volatile("wgmma.wait_group.sync.aligned %0;" ::"n"(N) : "memory"); }
template <int N> DI void reg_fence(float* d) {
#pragma unroll
  for (int i = 0; i < N; i++) asm volatile("" : "+f"(d[i])::"memory");
}
__host__ __device__ constexpr uint64_t mkdesc(uint32_t addr, uint32_t lbo, uint32_t sbo, uint32_t sw) {
  return (uint64_t)((addr & 0x3FFFF) >> 4) | ((uint64_t)(lbo >> 4) << 16) | ((uint64_t)(sbo >> 4) << 32) | ((uint64_t)sw << 62);
}

#define ACC4(d, o) "+f"(d[o]), "+f"(d[o + 1]), "+f"(d[o + 2]), "+f"(d[o + 3])
#define ACC16(d, o) ACC4(d, o), ACC4(d, o + 4), ACC4(d, o + 8), ACC4(d, o + 12)
#define ACC20(d) ACC16(d, 0), ACC4(d, 16)

template <int TA, int TB> DI void wg_ss40(float* d, uint64_t da, uint64_t db, int sc) {
  asm volatile("{.reg .pred p; setp.ne.b32 p, %22, 0;\n"
               "wgmma.mma_async.sync.aligned.m64n40k16.f32.bf16.bf16 {%0,%1,%2,%3,%4,%5,%6,%7,%8,%9,%10,%11,%12,%13,%14,%15,%16,%17,%18,%19}, %20, %21, p, 1, 1, %23, %24;}"
               : ACC20(d) : "l"(da), "l"(db), "r"(sc), "n"(TA), "n"(TB));
}
DI void wg_rs40(float* d, uint32_t a0, uint32_t a1, uint32_t a2, uint32_t a3, uint64_t db, int sc) {
  asm volatile("{.reg .pred p; setp.ne.b32 p, %25, 0;\n"
               "wgmma.mma_async.sync.aligned.m64n40k16.f32.bf16.bf16 {%0,%1,%2,%3,%4,%5,%6,%7,%8,%9,%10,%11,%12,%13,%14,%15,%16,%17,%18,%19}, {%20,%21,%22,%23}, %24, p, 1, 1, 0;}"
               : ACC20(d) : "r"(a0), "r"(a1), "r"(a2), "r"(a3), "l"(db), "r"(sc));
}
DI void wg_rs32(float* d, uint32_t a0, uint32_t a1, uint32_t a2, uint32_t a3, uint64_t db, int sc) {
  asm volatile("{.reg .pred p; setp.ne.b32 p, %21, 0;\n"
               "wgmma.mma_async.sync.aligned.m64n32k16.f32.bf16.bf16 {%0,%1,%2,%3,%4,%5,%6,%7,%8,%9,%10,%11,%12,%13,%14,%15}, {%16,%17,%18,%19}, %20, p, 1, 1, 0;}"
               : ACC16(d, 0) : "r"(a0), "r"(a1), "r"(a2), "r"(a3), "l"(db), "r"(sc));
}
DI void wg_ss32k(float* d, uint64_t da, uint64_t db, int sc) {
  asm volatile("{.reg .pred p; setp.ne.b32 p, %18, 0;\n"
               "wgmma.mma_async.sync.aligned.m64n32k16.f32.bf16.bf16 {%0,%1,%2,%3,%4,%5,%6,%7,%8,%9,%10,%11,%12,%13,%14,%15}, %16, %17, p, 1, 1, 1, 0;}"
               : ACC16(d, 0) : "l"(da), "l"(db), "r"(sc));
}
DI void wg_ss8k(float* d, uint64_t da, uint64_t db, int sc) {
  asm volatile("{.reg .pred p; setp.ne.b32 p, %6, 0;\n"
               "wgmma.mma_async.sync.aligned.m64n8k16.f32.bf16.bf16 {%0,%1,%2,%3}, %4, %5, p, 1, 1, 1, 0;}"
               : ACC4(d, 0) : "l"(da), "l"(db), "r"(sc));
}
DI void wg_rs8(float* d, uint32_t a0, uint32_t a1, uint32_t a2, uint32_t a3, uint64_t db, int sc) {
  asm volatile("{.reg .pred p; setp.ne.b32 p, %9, 0;\n"
               "wgmma.mma_async.sync.aligned.m64n8k16.f32.bf16.bf16 {%0,%1,%2,%3}, {%4,%5,%6,%7}, %8, p, 1, 1, 0;}"
               : ACC4(d, 0) : "r"(a0), "r"(a1), "r"(a2), "r"(a3), "l"(db), "r"(sc));
}
DI void mma16816(float* c, const uint32_t* a, uint32_t b0, uint32_t b1) {
  asm volatile("mma.sync.aligned.m16n8k16.row.col.f32.bf16.bf16.f32 {%0,%1,%2,%3}, {%4,%5,%6,%7}, {%8,%9}, {%0,%1,%2,%3};"
               : ACC4(c, 0) : "r"(a[0]), "r"(a[1]), "r"(a[2]), "r"(a[3]), "r"(b0), "r"(b1));
}
DI void wg_ss8(float* d, uint64_t da, uint64_t db, int sc) {
  asm volatile("{.reg .pred p; setp.ne.b32 p, %6, 0;\n"
               "wgmma.mma_async.sync.aligned.m64n8k16.f32.bf16.bf16 {%0,%1,%2,%3}, %4, %5, p, 1, 1, 1, 1;}"
               : ACC4(d, 0) : "l"(da), "l"(db), "r"(sc));
}
__device__ uint4 g_xn[2 * NSEG * 10 * 256];
__device__ uint4 g_oT[2 * NBLK * 96 * 1024];
constexpr int PART_RING = 96 * 256;
__device__ uint4 g_part[4 * PART_RING];
#define P4 ~0u, ~0u, ~0u, ~0u
#define P16 P4, P4, P4, P4
#define P256 P16, P16, P16, P16, P16, P16, P16, P16, P16, P16, P16, P16, P16, P16, P16, P16
#define P2K P256, P256, P256, P256, P256, P256, P256, P256
#define P8K P2K, P2K, P2K, P2K
__device__ __align__(8192) uint32_t g_mem32[5 * 2 * 2 * 2048] = {P8K, P8K, P8K, P8K, P8K};
#define g_mem ((uint4*)g_mem32)
constexpr int C_XN = 0;
constexpr int C_O = C_XN + 2 * NBLK;
constexpr int C_HALF = C_O + 6 * 2 * NBLK;
constexpr int C_TOTAL = 512;
constexpr int CSTRIDE = 32;
__device__ uint32_t g_cnt[C_TOTAL * CSTRIDE];
constexpr uint32_t XN_TARGET = 128;

#define TRACE(c, n, i, v)
#define SLOG(i)
#define PROF(i)
#define PROFA(c)
#define PROFV(i, v)

constexpr uint32_t SMEM0 = 1024;
constexpr uint32_t SM_WK = 0, SM_WO = 81920, SM_H = 163840, SM_QT = 215040, QSTR = 1056  , SM_KT = SM_QT + 5 * QSTR + 1024,
                   SM_SR = SM_KT + 5120  , SM_PROF = SM_SR + 5760, R_SMEM = 232448,
                   SM_RED = SM_QT + 1024, SM_BAR = SM_RED + 768;
constexpr uint32_t SM_P = SM_KT, SM_OB = SM_QT + 3200;
constexpr uint32_t B_HFULL = SM_BAR, B_HEMPTY = SM_BAR + 40, B_MTRY = SM_BAR + 80, B_W = SM_BAR + 112, B_SR = B_W + 32,
                   B_PMEM = B_SR + 24, B_PTOK = B_SR + 32, B_OB = B_SR + 40, B_OPD = B_SR + 48, B_RFREE = B_SR + 56,
                   B_GATE = B_SR + 64, B_PSUM = B_SR + 72, B_END = B_SR + 80, B_TOK = B_SR + 88,
                   B_OPI = B_SR + 96, B_OTOK = B_SR + 112, SM_TOPI = B_SR + 128, B_PACE = SM_TOPI + 8,
                   SM_RS = SM_QT + 2 * QSTR + 1024;
static_assert(B_PACE + 32 <= SM_QT + 2 * QSTR, "barriers must fit the unused q row group");

struct RParams {
  uint64_t dH, dHt, dWK, dWO, dQT, dKT, dP, dOB[6];
  const uint4* mem0;
  const uint32_t* x;
  int pf;
  int nslots, d3, pn, moff, ds, dh, dq;
  int d2[10], d1[8];
  uint32_t slot[2 * NSEG];
};
static void r_fill_desc(RParams& p) {
  p.dH = mkdesc(SMEM0 + SM_H, 128, 2048, 0);
  p.dHt = mkdesc(SMEM0 + SM_H + 2048, 128, 2048, 0);
  p.dWK = mkdesc(SMEM0 + SM_WK, 1024, 1024, 1);
  p.dWO = mkdesc(SMEM0 + SM_WO, 1024, 1024, 1);
  for (int i = 0; i < 6; i++) p.dOB[i] = mkdesc(SMEM0 + SM_OB + (i < 3 ? 0 : (i - 3) * 1024), 128, 128, 0);
  p.dQT = mkdesc(SMEM0 + SM_QT, 128, QSTR, 0);
  p.dKT = mkdesc(SMEM0 + SM_KT, 128, 1024, 0);
  p.dP = mkdesc(SMEM0 + SM_P, 128, 640, 0);
}
DI uint64_t dadd(uint64_t d, int bytes) {
  uint64_t r;
  asm volatile("add.u64 %0, %1, %2;" : "=l"(r) : "l"(d), "l"((long long)(bytes / 16)));
  return r;
}
template <int BYTES> DI void dstep(uint64_t& d) { asm volatile("add.u64 %0, %0, %1;" : "+l"(d) : "n"((long long)(BYTES / 16))); }
__host__ __device__ constexpr int hoff(int ks) { return (ks >> 3) * 10240 + (ks & 7) * 256; }

DI int opaque(int v) { asm volatile("" : "+r"(v)); return v; }
DI uint32_t pin(uint32_t v, int lane) { return __shfl_sync(~0u, v + (lane >> 5), lane); }
DI char* pin(char* p, int lane) { return (char*)__shfl_sync(~0u, (unsigned long long)p, lane); }
DI float blo(uint32_t w) { return __uint_as_float(w << 16); }
DI float bhi(uint32_t w) { return __uint_as_float(w & 0xffff0000u); }
#define RG0 232
#define RG1 216
#define RG2 40
#define RG3 24
DI void ldsm4t(uint32_t* r, uint32_t a) {
  asm volatile("ldmatrix.sync.aligned.m8n8.x4.trans.shared.b16 {%0,%1,%2,%3}, [%4];" : "=r"(r[0]), "=r"(r[1]), "=r"(r[2]), "=r"(r[3]) : "r"(a) : "memory");
}
DI void st_tagged(void* p, float a, float b, uint32_t keep, uint32_t tagbit) {
  asm volatile("{.reg .b32 t; cvt.rn.bf16x2.f32 t, %2, %1; lop3.b32 t, t, %3, %4, 0xea; st.relaxed.gpu.global.b32 [%0], t;}" ::"l"(p), "f"(a), "f"(b),
               "r"(keep), "r"(tagbit) : "memory");
}
DI uint32_t lop_bad(uint32_t a, uint32_t b, uint32_t m) { uint32_t d; asm("lop3.b32 %0, %1, %2, %3, 0x7e;" : "=r"(d) : "r"(a), "r"(b), "r"(m)); return d; }
DI uint32_t lop_or3(uint32_t a, uint32_t b, uint32_t c) { uint32_t d; asm("lop3.b32 %0, %1, %2, %3, 0xfe;" : "=r"(d) : "r"(a), "r"(b), "r"(c)); return d; }
DI uint32_t clk() { uint32_t t; asm volatile("mov.u32 %0, %%clock;" : "=r"(t)); return t; }
DI void spin(uint32_t cyc) { const uint32_t t0 = clk(); while (__any_sync(~0u, clk() - t0 < cyc)) {} }
template <int NL> DI float2 poll_sum(const uint32_t* src, uint32_t tag, uint32_t even, uint32_t& g) {
  uint32_t r[NL];
  while (true) {
#pragma unroll
    for (int i = 0; i < NL; i++) r[i] = ld_rlx(src + i * 32);
    uint32_t bad = lop_or3(lop_bad(r[0], r[1], tag), lop_bad(r[2], r[3], tag), lop_bad(r[4], r[5], tag));
    if (NL == 12) bad = lop_or3(bad, lop_bad(r[6], r[7], tag), lop_bad(r[8], r[9], tag));
    asm volatile("lop3.b32 %0, %0, %1, %2, 0xa8;" : "+r"(bad) : "r"(lop_bad(r[NL - 2], r[NL - 1], tag)), "r"(even));
    if (!__any_sync(~0u, bad)) break;
    g++;
  }
  float x[NL / 2], y[NL / 2];
#pragma unroll
  for (int i = 0; i < NL / 2; i++) { x[i] = blo(r[2 * i]) + blo(r[2 * i + 1]); y[i] = bhi(r[2 * i]) + bhi(r[2 * i + 1]); }
  float2 u = make_float2((x[0] + x[1]) + (x[2] + x[3]), (y[0] + y[1]) + (y[2] + y[3]));
  if (NL == 12) { u.x += x[4] + x[5]; u.y += y[4] + y[5]; }
  return u;
}

constexpr int PLANE = 16 * 40 * 32, MAXPL = 13;
__device__ uint2 g_acc[(size_t)2 * NBLK * 2 * MAXPL * PLANE];
DI uint2* acc_planes(int lb, int d) { return g_acc + (size_t)((lb * 2 + d) * MAXPL) * PLANE; }
DI void ln_stats(const float4* v, uint32_t red, int warp, int lane, int bar, float& mean, float& rstd) {
  float s = 0.f;
#pragma unroll
  for (int i = 0; i < 5; i++) s += (v[i].x + v[i].y) + (v[i].z + v[i].w);
  s += __shfl_xor_sync(~0u, s, 1);
  s += __shfl_xor_sync(~0u, s, 2);
  s *= 1.f / 80;
  float q = 0.f;
#pragma unroll
  for (int i = 0; i < 5; i++) q += ((v[i].x - s) * (v[i].x - s) + (v[i].y - s) * (v[i].y - s)) + ((v[i].z - s) * (v[i].z - s) + (v[i].w - s) * (v[i].w - s));
  q += __shfl_xor_sync(~0u, q, 1);
  q += __shfl_xor_sync(~0u, q, 2);
  if ((lane & 3) == 0) asm volatile("st.shared.v2.f32 [%0], {%1,%2};" ::"r"(red + lane * 16 + warp * 8), "f"(s), "f"(q) : "memory");
  bar_sync(bar, 256);
  const uint4 t = lds128(red + lane * 16);
  const float m0 = __uint_as_float(t.x), m1 = __uint_as_float(t.z);
  mean = m0 + m1;
  mean += __shfl_xor_sync(~0u, mean, 1);
  mean += __shfl_xor_sync(~0u, mean, 2);
  mean *= 0.125f;
  q = __uint_as_float(t.y) + __uint_as_float(t.w) + 80.f * ((m0 - mean) * (m0 - mean) + (m1 - mean) * (m1 - mean));
  q += __shfl_xor_sync(~0u, q, 1);
  q += __shfl_xor_sync(~0u, q, 2);
  rstd = rsqrtf(q * (1.f / DM) + 1e-5f);
}
template <int SH, int STR> DI void store_img(uint32_t* dst, const float4* v, int warp, float mean, float rstd) {
#pragma unroll
  for (int i = 0; i < 5; i++) {
    const int U = 10 * warp + 2 * i;
    uint32_t* p = dst + (U >> SH) * STR + (U & ((1 << SH) - 1)) * 32;
    p[0] = pack2((v[i].x - mean) * rstd, (v[i].y - mean) * rstd);
    p[32] = pack2((v[i].z - mean) * rstd, (v[i].w - mean) * rstd);
  }
}
DI uint32_t* xn_row_group(int layer, int rg) { return (uint32_t*)(g_xn + (size_t)((layer * NSEG + (rg >> 2)) * 2560 + (rg & 3) * 128)); }

DI void first_ln(const uint32_t* a, int rg, uint32_t red, int warp, int lane, int bar) {
  float4 v[5];
#pragma unroll
  for (int i = 0; i < 5; i++) {
    v[i] = make_float4(blo(a[2 * i]), bhi(a[2 * i]), blo(a[2 * i + 1]), bhi(a[2 * i + 1]));
    acc_planes(rg >> 4, 0)[((rg & 15) * 40 + warp * 5 + i) * 32 + lane] = make_uint2(a[2 * i], a[2 * i + 1]);
  }
  float mean, rstd;
  ln_stats(v, red, warp, lane, bar, mean, rstd);
  store_img<4, 2048>(xn_row_group(0, rg) + lane, v, warp, mean, rstd);
}
#define QK_P0 32
#define QK_KB 0
struct QKOrder { int op[76]; };
__host__ __device__ constexpr QKOrder qk_order() {
  QKOrder o = {};
  int n = 0, k = 0, q = 0;
  for (; k < QK_P0; k++, q++) { o.op[n++] = 64 | k; o.op[n++] = q; }
  for (int i = 0; i < QK_KB; i++) o.op[n++] = 64 | k++;
  for (int i = 0; i < -QK_KB; i++) o.op[n++] = q++;
  const int nk = 40 - k, nq = 36 - q;
  for (int i = 0, dk = 0, dq = 0; i < nk + nq; i++) {
    if (dq * nk <= dk * nq + (QK_KB ? 0 : -nq) && dq < nq) { o.op[n++] = q++; dq++; } else if (dk < nk) { o.op[n++] = 64 | k++; dk++; } else { o.op[n++] = q++; dq++; }
  }
  return o;
}
__global__ void __launch_bounds__(512, 1)
r_kernel(const __grid_constant__ CUtensorMap mapWq, const __grid_constant__ CUtensorMap mapWk, const __grid_constant__ CUtensorMap mapWv,
         const __grid_constant__ CUtensorMap mapWo, const __grid_constant__ RParams prm) {
  const uint32_t sb = smem_base();
  const int wid = __shfl_sync(~0u, threadIdx.x >> 5, 0);
  const int lane0 = __shfl_sync(~0u, threadIdx.x & 31, threadIdx.x & 31);
  const int lane = lane0;
  const int warp = wid & 3, wg = wid >> 2;
  const uint32_t rank = blockIdx.x, head = blockIdx.y, cta = head * 3 + rank;
  const uint32_t peer1 = mapa(sb, rank == 2 ? 0 : rank + 1), peer2 = mapa(sb, rank == 0 ? 2 : rank - 1);
  const int nslots = prm.nslots;

  SLOG(0);
  if (threadIdx.x == 384) {
    if ((sb & 0x3FFFF) != SMEM0) __trap();
    for (int c = 0; c < 5; c++) { mbar_init(sb + B_HFULL + 8 * c, 2); mbar_init(sb + B_HEMPTY + 8 * c, c == 4 ? 8 : 4); }
    for (int c = 0; c < 11; c++) mbar_init(sb + B_MTRY + 8 * c, 1);
    mbar_init(sb + B_PTOK, rank == 0 ? 3 : 2); mbar_init(sb + B_OB, 5); mbar_init(sb + B_OPD, 4);
    mbar_init(sb + B_OPI, 1); mbar_init(sb + B_OPI + 8, 1); mbar_init(sb + B_RFREE, 1); mbar_init(sb + B_GATE, 1); mbar_init(sb + B_PMEM, 2); mbar_init(sb + B_PSUM, 2); mbar_init(sb + B_TOK, 5); mbar_init(sb + B_OTOK, 4); mbar_init(sb + B_OTOK + 8, 4); mbar_init(sb + B_END, 15);
    for (int c = 0; c < 4; c++) mbar_init(sb + B_PACE + 8 * c, 1);
    asm volatile("fence.mbarrier_init.release.cluster;" ::: "memory");
    fence_async_smem();
  }
  asm volatile("griddepcontrol.launch_dependents;");
  asm volatile("barrier.cluster.arrive.release.aligned;" ::: "memory");

  if (wg < 2) {
  {
    uint32_t xa[10];
    const uint32_t* src = prm.x + (size_t)(cta * 8 + (lane >> 2)) * (DM / 2) + wid * 40 + (lane & 3);
#pragma unroll
    for (int i = 0; i < 10; i++) xa[i] = __ldg(src + i * 4);
    asm volatile("barrier.cluster.wait.acquire.aligned;" ::: "memory");
    first_ln(xa, cta, sb + SM_SR, wid, lane, 8);
    bar_arrive(10, 288);
  }
  if (wg == 0) {
    asm volatile("setmaxnreg.inc.sync.aligned.u32 %0;" ::"n"(RG0));
    uint32_t wq[160];
    SLOG(1);
    mbar_wait(sb + B_W, 0);
    SLOG(2);
    {
      const uint32_t ld_off = ((lane >> 4) * 8 + (lane & 7)) * 128 + (((2 * warp + ((lane >> 3) & 1)) ^ (lane & 7)) << 4);
#pragma unroll
      for (int ks = 0; ks < 40; ks++) ldsm4t(wq + 4 * ks, sb + SM_WO + ks * 2048 + ld_off);
    }
    fence_async_smem();
    bar_arrive(5, 160);
    mbar_wait(sb + B_W + 16, 0);
    SLOG(3);
    const uint32_t st_addr = pin(sb + SM_QT + (lane >> 4) * 1024 + (2 * warp + ((lane >> 3) & 1)) * 128 + (lane & 7) * 16, lane);
    const uint32_t sq_addr = pin(sb + SM_QT + (2 + (lane & 3)) * QSTR + warp * 256 + (lane >> 2) * 16, lane);
    const uint32_t to_lo = warp == 0 ? peer1 : mapa(sb, warp == 2 ? 2 : 0), to_hi = warp == 0 ? peer2 : mapa(sb, warp == 1 ? 1 : 0);
    const uint32_t sr_off = SM_SR + warp * 1920 + rank * 640, sr_bar = B_SR + warp * 8;
    const uint32_t sa0 = pin(to_lo + sr_off + lane * 16, lane), sb0 = pin(to_lo + sr_bar, lane), sa1 = pin(to_lo + sr_off + 512 + lane * 4, lane), sb1 = pin(sb0, lane);
    const uint32_t sa2 = pin(to_hi + sr_off + lane * 16, lane), sb2 = pin(to_hi + sr_bar, lane), sa3 = pin(to_hi + sr_off + 512 + lane * 4, lane), sb3 = pin(sb2, lane);
    uint32_t nsolo = 0;
#pragma unroll 1
    for (int n = 0; n < nslots; n++) {
      const uint32_t par = n & 1;
      PROFA(warp == PW);
      const bool alt = prm.slot[n] & 128;
      auto next = [&](uint64_t& d, int ks) { if ((ks & 7) == 7) dstep<10240 - 7 * 256>(d); else dstep<256>(d); };
      auto store_k = [&](const float* ka) {
        stsm2(st_addr + (SM_KT - SM_QT), pack2(ka[0], ka[1]), pack2(ka[2], ka[3]));
        stsm4(st_addr + (SM_KT - SM_QT) + 1024, pack2(ka[4], ka[5]), pack2(ka[6], ka[7]), pack2(ka[8], ka[9]), pack2(ka[10], ka[11]));
        stsm4(st_addr + (SM_KT - SM_QT) + 3072, pack2(ka[12], ka[13]), pack2(ka[14], ka[15]), pack2(ka[16], ka[17]), pack2(ka[18], ka[19]));
      };
      auto store_qt = [&](const float* q) {
        sts128(sq_addr, make_uint4(pack2(q[0], q[1]), pack2(q[4], q[5]), pack2(q[8], q[9]), pack2(q[12], q[13])));
        sts128(sq_addr + 128, make_uint4(pack2(q[2], q[3]), pack2(q[6], q[7]), pack2(q[10], q[11]), pack2(q[14], q[15])));
      };
      if (n > 0 && ((prm.slot[n] >> 8) & 255) == n) {
        {
          float qt[16];
          uint64_t rh = prm.dHt;
          mbar_wait(sb + B_OPI + (par ^ 1) * 8, ((n - 1) >> 1) & 1);
          mbar_wait(sb + B_GATE, 1);
          spin(prm.dq);
          mbar_wait(sb + B_TOK, nsolo++ & 1);
          float kt[16];
          uint64_t rk = prm.dWK;
          wg_fence();
#pragma unroll
          for (int ks = 0; ks < 40; ks++) {
            wg_ss32k(kt, rk, rh, ks != 0);
            wg_rs32(qt, wq[4 * ks], wq[4 * ks + 1], wq[4 * ks + 2], wq[4 * ks + 3], rh, ks != 0);
            if (ks < 39) { dstep<2048>(rk); next(rh, ks); }
          }
          wg_commit();
          mbar_wait(sb + B_OPD, par ^ 1);
          wg_wait<0>();
          reg_fence<16>(qt); reg_fence<16>(kt);
          store_qt(qt);
          stsm4(st_addr + (SM_KT - SM_QT) + 1024, pack2(kt[0], kt[1]), pack2(kt[2], kt[3]), pack2(kt[4], kt[5]), pack2(kt[6], kt[7]));
          stsm4(st_addr + (SM_KT - SM_QT) + 3072, pack2(kt[8], kt[9]), pack2(kt[10], kt[11]), pack2(kt[12], kt[13]), pack2(kt[14], kt[15]));
        }
        float qm[4], km[4];
        uint64_t rk = prm.dWK, rh = prm.dH;
        bool ok = false;
#pragma unroll
        for (int g = 0; g < 20; g++) {
          if ((g & 3) == 0 && !ok) mbar_wait(sb + B_HFULL + 2 * g, par);
          if (g == 0) PROF(0);
          if ((g & 3) == 3 && g < 19) ok = mbar_test(sb + B_HFULL + 2 * (g + 1), par);
          if ((g & 3) == 0) wg_fence();
#pragma unroll
          for (int ks = 2 * g; ks < 2 * g + 2; ks++) {
            wg_ss8k(km, rk, rh, ks != 0);
            wg_rs8(qm, wq[4 * ks], wq[4 * ks + 1], wq[4 * ks + 2], wq[4 * ks + 3], rh, ks != 0);
            if (ks < 39) { dstep<2048>(rk); next(rh, ks); }
          }
          if (g == 18) wg_commit();
        }
        wg_commit();
        wg_wait<1>();
        bar_arrive(2, 256);
        wg_wait<0>();
        reg_fence<4>(qm); reg_fence<4>(km);
        PROF(9);
        stsm2(st_addr + (SM_KT - SM_QT), pack2(km[0], km[1]), pack2(km[2], km[3]));
        stsm2(st_addr, pack2(qm[0], qm[1]), pack2(qm[2], qm[3]));
      } else {
      float qa[20], ka[20];
      uint64_t rk = prm.dWK, rh = prm.dH, rq;
      auto K = [&](int ks) { wg_ss40<1, 0>(ka, rk, rh, ks != 0); };
      auto Q = [&](int ks, uint64_t db) { wg_rs40(qa, wq[4 * ks], wq[4 * ks + 1], wq[4 * ks + 2], wq[4 * ks + 3], db, ks != 0); };
      constexpr QKOrder ord = qk_order();
      auto first = [&](int g, int c) { for (int i = 0; i < 76; i++) if ((ord.op[i] & 63) >> 3 == c) return i >> 2 == g; return false; };
      bool ok = true;
      mbar_wait(sb + B_HFULL, par);
#pragma unroll
      for (int g = 0; g < 19; g++) {
        if (!ok) {
#pragma unroll
          for (int c = 1; c < 5; c++) if (first(g, c)) mbar_wait(sb + B_HFULL + 8 * c, par);
          mbar_wait(sb + B_GATE, 1);
        }
        if (g == 0) PROF(0);
        if (g < 18) ok = mbar_test(sb + B_GATE, 1);
#pragma unroll
        for (int c = 1; c < 5; c++) if (first(g + 1, c)) ok &= mbar_test(sb + B_HFULL + 8 * c, par);
        wg_fence();
#pragma unroll
        for (int i = 4 * g; i < 4 * g + 4; i++) {
          const int ks = ord.op[i] & 63;
          if (i < 2 * QK_P0) {
            if (ord.op[i] & 64) K(ks);
            else { Q(ks, rh); dstep<2048>(rk); next(rh, ks); if (i == 2 * QK_P0 - 1) rq = rh; }
          } else if (ord.op[i] & 64) { K(ks); if (ks < 39) { dstep<2048>(rk); next(rh, ks); } }
          else { Q(ks, rq); next(rq, ks); }
        }
        if (g == 17) wg_commit();
      }
      wg_commit();
#pragma unroll
      for (int ks = 36; ks < 40; ks++) { Q(ks, rq); if (ks < 39) dstep<256>(rq); }
      wg_commit();
      wg_wait<2>();
      if (alt) bar_arrive(2, 256);
      mbar_wait(sb + B_OPD, par ^ 1);
      wg_wait<1>();
      if (!alt) bar_arrive(2, 256);
      reg_fence<20>(ka);
      store_k(ka);
      wg_wait<0>();
      reg_fence<20>(qa);
      PROF(9);
      stsm2(st_addr, pack2(qa[0], qa[1]), pack2(qa[2], qa[3]));
      store_qt(qa + 4);
      }
      mbar_arrive_if(lane == 0, sb + B_HEMPTY + 32);
      fence_async_smem();
      bar_sync(1, 128);
      PROF(1);
      float qa[20];
      wg_fence();
#pragma unroll
      for (int k = 0; k < 4; k++) wg_ss40<1, 1>(qa, dadd(prm.dQT, k * 256), dadd(prm.dKT, k * 256), k != 0);
      wg_commit();
      bar_arrive(7, 256);
      wg_wait<0>();
      reg_fence<20>(qa);
      PROF(3);
      if (warp < 3) {
        uint32_t p[5];
#pragma unroll
        for (int j = 0; j < 5; j++) p[j] = pack2(qa[4 * j], qa[4 * j + 1]);
        if (warp == 0) {
          st_async4(sa0, p[0], p[1], p[2], p[3], sb0);
          st_async4(sa2, p[0], p[1], p[2], p[3], sb2);
          st_async1(sa1, p[4], sb1);
          st_async1(sa3, p[4], sb3);
          sts128(sb + sr_off + lane * 16, make_uint4(p[0], p[1], p[2], p[3]));
          sts32(sb + sr_off + 512 + lane * 4, p[4]);
          __syncwarp();
          mbar_expect_if(lane == 0, sb + B_SR, 1280);
        } else {
          uint32_t h[5];
#pragma unroll
          for (int j = 0; j < 5; j++) h[j] = pack2(qa[4 * j + 2], qa[4 * j + 3]);
          spin(prm.d3);
          st_async4(sa0, p[0], p[1], p[2], p[3], sb0);
          st_async4(sa2, h[0], h[1], h[2], h[3], sb2);
          st_async1(sa1, p[4], sb1);
          st_async1(sa3, h[4], sb3);
        }
      }
    }
  } else {
    asm volatile("setmaxnreg.inc.sync.aligned.u32 %0;" ::"n"(RG1));
    uint32_t wv[160];
    mbar_wait(sb + B_W + 8, 0);
    SLOG(4);
    {
      const uint32_t ld_off = ((lane >> 4) * 8 + (lane & 7)) * 128 + (((2 * warp + ((lane >> 3) & 1)) ^ (lane & 7)) << 4);
#pragma unroll
      for (int ks = 0; ks < 40; ks++) ldsm4t(wv + 4 * ks, sb + SM_WO + ks * 2048 + ld_off);
    }
    fence_async_smem();
    bar_arrive(6, 160);
    const uint64_t dH = prm.dH;
    uint32_t op[8];
    const uint32_t ob_off = SM_OB + (4 * rank + warp) * 256 + lane * 4;
    const uint32_t oa0 = pin(peer1 + ob_off, lane), ob0 = pin(peer1 + B_OB, lane), oa1 = pin(peer2 + ob_off, lane), ob1 = pin(peer2 + B_OB, lane);
    const uint32_t oa2 = pin(oa0 + 128, lane), ob2 = pin(ob0, lane), oa3 = pin(oa1 + 128, lane), ob3 = pin(ob1, lane);
    const uint32_t o_loc = pin(sb + ob_off, lane), rs_addr = pin(sb + SM_RS + (lane & 3) * 8, lane);
    const uint32_t tok_off = pin((cta * 1024 + 64 * warp + (lane ^ (lane >> 3))) * 16, lane), keep = pin((lane & 1) ? ~0u : ~1u, lane);
    const uint32_t pb_off = pin((8 * rank + 2 * warp) * 4096 + head * 128 + lane * 4, lane);
    const uint32_t ph_off = pin(72 * 4096 + 2 * warp * 12288 + cta * 64 + (lane & 2) * 3072 + (lane >> 2) * 8 + (lane & 1) * 4, lane);
    auto store_tok = [&](int m, int lane) {
      const uint32_t ls = prm.slot[m] & 127, sig = prm.slot[m] >> 16;
      uint4* dst = (uint4*)((char*)(g_oT + (size_t)((ls >> 2) * (96 * 1024) + (ls & 3) * 256)) + tok_off);
      dst[0] = make_uint4(op[0], op[1], op[2], op[3]);
      dst[32] = make_uint4(op[4], op[5], op[6], op[7]);
      __syncwarp();
      mbar_arrive_if(sig && lane == 0, sb + B_OTOK + (ls >> 6) * 8);
    };
#pragma unroll 1
    for (int n = 0; n < nslots; n++) {
      const uint32_t par = n & 1;
      const int lane = opaque(lane0);
      PROFA(warp == PW);
      float va[20];
      const bool alt = prm.slot[n] & 128;
      mbar_expect_if(warp == 0 && lane == 0, sb + B_PTOK, rank == 0 ? 1280 : 1920);
      bar_sync(2, 256);
#pragma unroll
      for (int g = 0; g < 10; g++) {
        wg_fence();
#pragma unroll
        for (int ks = 4 * g; ks < 4 * g + 4; ks++) { wg_rs40(va, wv[4 * ks], wv[4 * ks + 1], wv[4 * ks + 2], wv[4 * ks + 3], dadd(dH, hoff(ks)), ks != 0); }
        wg_commit();
        if (g >= 2 && !(g & 1)) {
          wg_wait<1>();
          if (lane == 0) mbar_arrive(sb + B_HEMPTY + 8 * (g / 2 - 1));
        }
        if (g == 1 ? !alt : g == 2 && alt) bar_sync(7, 256);
      }
      wg_wait<0>();
      reg_fence<20>(va);
      if (lane == 0) mbar_arrive(sb + B_HEMPTY + 32);
      PROF(10);
      uint32_t vf[10];
#pragma unroll
      for (int j = 0; j < 10; j++) {
        const int i = (j + 4) % 10;
        asm volatile("cvt.rn.bf16x2.f32 %0, %1, %2;" : "=r"(vf[i]) : "f"(va[2 * i + 1]), "f"(va[2 * i]));
        if (j == 5) mbar_wait(sb + B_W + 8, 0);
      }
      uint32_t z0, z1;
      asm volatile("shr.u32 %0, %2, 5; shr.u32 %1, %2, 6;" : "=r"(z0), "=r"(z1) : "r"(lane));
      const uint32_t info = prm.slot[n];
      const uint32_t tagbit = ~(info >> 1) & ~keep;
      char* const ring = (char*)(g_part + (size_t)((((info >> 5) & 2) + (info & 1)) * PART_RING));
      char* const pb = pin(ring + pb_off, lane);
      char* const ph = ring + ph_off;
      mbar_wait(sb + B_PMEM, par);
      float om[4];
      wg_fence();
      wg_rs8(om, vf[0], vf[1], vf[2], vf[3], prm.dP, 0);
      wg_rs8(om, vf[4], vf[5], vf[6], vf[7], dadd(prm.dP, 256), 1);
      wg_rs8(om, vf[8], vf[9], z0, z1, dadd(prm.dP, 512 - (128 << 16)), 1);
      wg_commit();
      {
        wg_wait<0>();
        reg_fence<4>(om);
        const uint32_t b0 = pack2(om[0], om[1]), b1 = pack2(om[2], om[3]);
        st_async1(oa0, b0, ob0);
        st_async1(oa1, b0, ob1);
        st_async1(oa2, b1, ob2);
        st_async1(oa3, b1, ob3);
        sts32(o_loc, b0);
        sts32(o_loc + 128, b1);
        fence_async_smem();
        __syncwarp();
        mbar_arrive_if(lane == 0, sb + B_OB);
      }
      PROF(11);
      {
        float c[8];
        mbar_wait(sb + B_PSUM, par);
        const uint2 rs = lds64(rs_addr);
        const float r0 = __uint_as_float(rs.x), r1 = __uint_as_float(rs.y);
        if (n == 0) { SLOG(5); mbar_wait(sb + B_W + 24, 0); SLOG(6); }
        mbar_wait(sb + B_OB, par);
        asm volatile("fence.proxy.async::generic.acquire.sync_restrict::shared::cluster.cluster;" ::: "memory");
        PROF(16);
        if ((info & 63) == NSEG - 1) {
          mbar_wait(sb + B_OPI + par * 8, (n >> 1) & 1);
          mbar_arrive_if(warp == 3 && lane == 0, sb + B_GATE);
#pragma unroll
          for (int p = 0; p < 6; p++) st_rlx1(pb + (p >> 1) * 98304 + (p & 1) * 4096, tagbit);
          st_rlx1(ph, tagbit);
          st_rlx1(ph + 12288, tagbit);
        } else {
#pragma unroll
        for (int p = 0; p < 4; p++) {
          float* const cur = c + 4 * (p & 1);
          float* const prv = c + 4 * (~p & 1);
          if (p == 2) mbar_wait(sb + B_OPI + par * 8, (n >> 1) & 1);
          wg_fence();
#pragma unroll
          for (int ks = 0; ks < (p < 3 ? 12 : 4); ks++) {
            wg_ss8(cur, dadd(prm.dWO, p * 24576 + ks * 2048), dadd(prm.dOB[p < 3 ? p : 3 + rank], ks * 256), ks != 0);
            if (p == 3 && ks == 3) mbar_arrive_if(warp == 3 && lane == 0, sb + B_GATE);
            if (p > 0 && ks == 3) {
              wg_commit();
              wg_wait<1>();
              reg_fence<4>(prv);
              st_tagged(pb + (p - 1) * 98304, prv[0] * r0, prv[1] * r1, keep, tagbit);
              st_tagged(pb + (p - 1) * 98304 + 4096, prv[2] * r0, prv[3] * r1, keep, tagbit);
            }
          }
          if (p < 3) wg_commit();
        }
        wg_wait<0>();
        reg_fence<4>(c + 4);
        st_tagged(ph, c[4] * r0, c[5] * r1, keep, tagbit);
        st_tagged(ph + 12288, c[6] * r0, c[7] * r1, keep, tagbit);
        }
        PROF(17);
      }
      mbar_wait(sb + B_PTOK, par);
      PROF(12);
      {
        float ot[16];
        wg_fence();
        wg_rs32(ot, vf[0], vf[1], vf[2], vf[3], dadd(prm.dP, 640), 0);
        wg_rs32(ot, vf[4], vf[5], vf[6], vf[7], dadd(prm.dP, 640 + 256), 1);
        wg_rs32(ot, vf[8], vf[9], z0, z1, dadd(prm.dP, 640 + 512 - (128 << 16)), 1);
        wg_commit();
        wg_wait<0>();
        reg_fence<16>(ot);
#pragma unroll
        for (int i = 0; i < 8; i++) op[(i & 1) * 4 + (i >> 1)] = pack2(ot[2 * i], ot[2 * i + 1]);
      }
      if (lane == 0) mbar_arrive(sb + B_OPD);
      PROF(13);
      if (info & 128) spin(prm.ds);
      store_tok(n, lane);
    }
  }
  } else if (wg == 2) {
    asm volatile("setmaxnreg.dec.sync.aligned.u32 %0;" ::"n"(RG2));
    asm volatile("barrier.cluster.wait.acquire.aligned;" ::: "memory");
    if (warp == 1) {
      const uint32_t depth = prm.pf;
#pragma unroll 1
      for (uint32_t i = 0; i < 20 + depth; i++) {
        if (i >= depth) {
          const uint32_t j = i - depth;
          mbar_wait_wd(sb + B_PACE + 8 * (j & 3), (j >> 2) & 1);
          if (j % 5 == 4) mbar_arrive_if(lane == 0 && (j != 14 || depth == 1), sb + B_W + (j == 4 ? 0 : j == 9 ? 16 : j == 14 ? 8 : 24));
        }
        if (i >= 20) continue;
        const uint32_t m = i / 5, k = i % 5, bar = sb + B_PACE + 8 * (i & 3);
        if (i == 10) bar_sync(5, 160);
        if (i == 15) {
#pragma unroll 1
          for (uint32_t j = 16 - depth; j < 15; j++) mbar_wait_wd(sb + B_PACE + 8 * (j & 3), (j >> 2) & 1);
          mbar_arrive_if(lane == 0 && depth > 1, sb + B_W + 8);
          bar_sync(6, 160);
        }
        if (elect_one()) {
          mbar_expect(bar, 16384);
          if (m < 3) tma_2d(sb + (m == 1 ? SM_WK : SM_WO) + k * 16384, m == 0 ? &mapWq : m == 1 ? &mapWk : &mapWv, cta * 64, k * 128, bar);
          else
            for (uint32_t q = 2 * k; q < 2 * k + 2; q++)
              tma_2d(sb + SM_WO + q * 8192, &mapWo, q < 9 ? (q / 3 * 3 + rank) * 64 : 576, head * DH + (q < 9 ? q % 3 : rank) * 64, bar);
        }
      }
    }
    if (warp == 2 && cta < 80 && lane < 16)
      g_mem[(cta >> 4) * 2048 + (lane >> 3) * 1024 + prm.moff + (cta & 15) * 8 + (lane & 7)] = prm.mem0[(lane & 7) * 80 + cta];
    if (warp == 3) {
      bar_sync(10, 288);
      if (lane == 0) red_rel(&g_cnt[(C_XN + (cta >> 4)) * CSTRIDE], 8);
    }
    const uint32_t grp = warp == 1 ? 1 + rank : 4 - (rank >> 1);
    constexpr float SC = 0.07216878364870322f * 1.4426950408889634f;
    const bool split = cta >= 72;
    const uint32_t wd = split ? 72 * 16 + cta * 16 : cta * 32;
    const uint32_t src_off = pin(split ? 72 * 4096 + (cta - 72) * 6144 + warp * 1536 + (lane & 2) * 32 + (lane >> 2) * 8 + (lane & 1) * 4 : cta * 4096 + warp * 1024 + lane * 4, lane);
    const uint32_t dst_off = pin(((wd >> 9) * 8192 + prm.moff * 4 + (wd & 511) + lane) * 4, lane);
    const uint32_t red = pin(sb + SM_RED + (warp < 2 ? 0 : (warp - 1) * 256) + lane * 8, lane);
    const uint32_t fl = (warp & 2) * 8 + (lane >> 3) * 4 + (lane & 3), hf = lane & 4;
    const uint32_t s0 = pin(sb + SM_SR + fl * 16 + hf * 2, lane), s1 = pin(sb + fl * 4, lane), pd = pin(s1 + hf * 64, lane);
    const uint32_t even = pin(~lane & 1, lane);
    uint32_t nred = 0;
    const uint32_t arm = pin(warp == 0 && (lane == 5 || ((lane == 1 || lane == 2) && lane + rank != 3)) ? sb + B_SR + lane * 8 : 0, lane);
#pragma unroll 1
    for (int n = 0; n < nslots; n++) {
      const uint32_t par = n & 1;
      const int lane = opaque(lane0);
      PROFA(warp == PW2);
      const uint32_t info = prm.slot[n], s = info & 63, l = (info >> 6) & 1;
      {
        mbar_expect_if(arm, arm, lane == 5 ? 2048 : 1920);
        if (warp == 0 || warp == 3) {
          mbar_wait(sb + B_SR, par);
          PROF(4);
          const uint2 a0 = lds64(s0), a1 = lds64(s0 + 640), a2 = lds64(s0 + 1280);
          const uint32_t b0 = lds32(s1 + SM_SR + 512), b1 = lds32(s1 + SM_SR + 1152), b2 = lds32(s1 + SM_SR + 1792);
          float v[6];
          v[0] = blo(a0.x) + blo(a1.x) + blo(a2.x); v[1] = bhi(a0.x) + bhi(a1.x) + bhi(a2.x);
          v[2] = blo(a0.y) + blo(a1.y) + blo(a2.y); v[3] = bhi(a0.y) + bhi(a1.y) + bhi(a2.y);
          v[4] = blo(b0) + blo(b1) + blo(b2); v[5] = bhi(b0) + bhi(b1) + bhi(b2);
          float m = fmaxf(fmaxf(v[0], v[1]), fmaxf(v[2], v[3]));
          m = fmaxf(fmaxf(m, __shfl_xor_sync(~0u, m, 4)), fmaxf(v[4], v[5]));
          {
            const float m1 = __shfl_xor_sync(~0u, m, 1), m2 = __shfl_xor_sync(~0u, m, 2), m3 = __shfl_xor_sync(~0u, m, 3);
            m = fmaxf(fmaxf(m, m1), fmaxf(m2, m3));
          }
          const float ms = -m * SC;
#pragma unroll
          for (int i = 0; i < 6; i++) v[i] = ex2(fmaf(v[i], SC, ms));
          float sum = (v[0] + v[1]) + (v[2] + v[3]);
          const float so = __shfl_xor_sync(~0u, sum, 4);
          sts32(pd + SM_P, pack2(v[0], v[1]));
          sts32(pd + SM_P + 128, pack2(v[2], v[3]));
          sts32(s1 + SM_P + 512, pack2(v[4], v[5]));
          fence_async_smem();
          __syncwarp();
          mbar_arrive_if(lane == 0, sb + B_PMEM);
          PROF(5);
          sum += so + (v[4] + v[5]);
          {
            const float t1 = __shfl_xor_sync(~0u, sum, 1), t2 = __shfl_xor_sync(~0u, sum, 2), t3 = __shfl_xor_sync(~0u, sum, 3);
            sum = (sum + t1) + (t2 + t3);
          }
          float r;
          asm("rcp.approx.ftz.f32 %0, %1;" : "=f"(r) : "f"(sum));
          sts32(sb + SM_RS + (warp & 2) * 8 + (lane >> 3) * 4, __float_as_uint(r));
          __syncwarp();
          mbar_arrive_if(lane == 0, sb + B_PSUM);
        } else {
          if (warp + rank != 3) {
            const uint32_t src = sb + SM_SR + warp * 1920;
            mbar_wait(sb + B_SR + warp * 8, par);
            const uint4 a0 = lds128(src + lane * 16), a1 = lds128(src + 640 + lane * 16), a2 = lds128(src + 1280 + lane * 16);
            const uint32_t b0 = lds32(src + 512 + lane * 4), b1 = lds32(src + 1152 + lane * 4), b2 = lds32(src + 1792 + lane * 4);
            float v[10];
            v[0] = blo(a0.x) + blo(a1.x) + blo(a2.x); v[1] = bhi(a0.x) + bhi(a1.x) + bhi(a2.x);
            v[2] = blo(a0.y) + blo(a1.y) + blo(a2.y); v[3] = bhi(a0.y) + bhi(a1.y) + bhi(a2.y);
            v[4] = blo(a0.z) + blo(a1.z) + blo(a2.z); v[5] = bhi(a0.z) + bhi(a1.z) + bhi(a2.z);
            v[6] = blo(a0.w) + blo(a1.w) + blo(a2.w); v[7] = bhi(a0.w) + bhi(a1.w) + bhi(a2.w);
            v[8] = blo(b0) + blo(b1) + blo(b2); v[9] = bhi(b0) + bhi(b1) + bhi(b2);
            {
              const int lim = 6 + 2 * grp + (lane & 24) + ((lane >> 2) & 1) - 2 * (lane & 3);
#pragma unroll
              for (int i = 2; i < 10; i++) if ((i >> 1) * 8 + (i & 1) > lim) v[i] = -INFINITY;
            }
            float m = fmaxf(fmaxf(fmaxf(v[0], v[1]), fmaxf(v[2], v[3])), fmaxf(fmaxf(v[4], v[5]), fmaxf(v[6], v[7])));
            m = fmaxf(m, fmaxf(v[8], v[9]));
            {
              const float m1 = __shfl_xor_sync(~0u, m, 1), m2 = __shfl_xor_sync(~0u, m, 2), m3 = __shfl_xor_sync(~0u, m, 3);
              m = fmaxf(fmaxf(m, m1), fmaxf(m2, m3));
            }
            const float ms = -m * SC;
#pragma unroll
            for (int i = 0; i < 10; i++) v[i] = ex2(fmaf(v[i], SC, ms));
            float sum = ((v[0] + v[1]) + (v[2] + v[3])) + ((v[4] + v[5]) + (v[6] + v[7])) + (v[8] + v[9]);
            {
              const float s1 = __shfl_xor_sync(~0u, sum, 1), s2 = __shfl_xor_sync(~0u, sum, 2), s3 = __shfl_xor_sync(~0u, sum, 3);
              sum = (sum + s1) + (s2 + s3);
            }
            float r;
            asm("rcp.approx.ftz.f32 %0, %1;" : "=f"(r) : "f"(sum));
            {
              const uint32_t row = SM_P + grp * 640;
#pragma unroll
              for (int j = 0; j < 5; j++) sts32(sb + row + j * 128 + lane * 4, pack2(v[2 * j] * r, v[2 * j + 1] * r));
              fence_async_smem();
              __syncwarp();
              mbar_arrive_if(lane == 0, sb + B_PTOK);
              if (elect_one()) {
                bulk_s2s(peer1 + row, sb + row, 640, peer1 + B_PTOK);
                bulk_s2s(peer2 + row, sb + row, 640, peer2 + B_PTOK);
              }
            }
          }
        }
      }
      const uint32_t* const src = (const uint32_t*)((char*)(g_part + (size_t)((l * 2 + (s & 1)) * PART_RING)) + src_off);
      uint32_t* const dst = (uint32_t*)pin((char*)(g_mem + l * 1024 + (~s & 1) * 512) + dst_off, lane);
      {
        const uint32_t d1 = prm.d1[cta / 24 + ((info >> 5) & 4)];
        if (warp == 3) {
          mbar_wait(sb + B_OB, par);
          mbar_arrive_if(lane == 0, sb + B_GATE);
          sts32(sb + SM_TOPI + par * 4, clk());
          __syncwarp();
          mbar_arrive_if(lane == 0, sb + B_OPI + par * 8);
          TRACE(true, n, 0, gtl());
        }
        const bool reduce = cta < 88 && s != NSEG - 1;
        if (reduce || warp == 0) mbar_wait(sb + B_OPI + par * 8, (n >> 1) & 1);
        if (!reduce) continue;
        mbar_wait(sb + B_RFREE, (nred++ & 1) ^ 1);
        mbar_wait(sb + B_GATE, 1);
        if (d1) spin(d1);
      }
      {
        uint32_t g = 0;
        float2 u;
        PROF(14);
        if (!split) {
          u = poll_sum<8>(src, ~(s >> 1), even, g);
        } else {
          u = poll_sum<12>(src, ~(s >> 1), even, g);
          u.x += __shfl_xor_sync(~0u, u.x, 2);
          u.y += __shfl_xor_sync(~0u, u.y, 2);
        }
        PROF(18);
        if (warp != 1) {
          asm volatile("st.shared.v2.f32 [%0], {%1,%2};" ::"r"(red), "f"(u.x), "f"(u.y) : "memory");
          bar_arrive(3, 128);
        } else {
          bar_sync(3, 128);
          const uint2 o0 = lds64(red), o1 = lds64(red + 256), o2 = lds64(red + 512);
          const uint32_t w = movm(pack2((u.x + __uint_as_float(o0.x)) + (__uint_as_float(o1.x) + __uint_as_float(o2.x)),
                                        (u.y + __uint_as_float(o0.y)) + (__uint_as_float(o1.y) + __uint_as_float(o2.y))));
          if (!split || lane < 16) {
            st_rlx1(dst, w);
            st_rlx1(dst + ((s & 1) ? 2048 : -2048), ~0u);
          }
          mbar_arrive_if(lane == 0, sb + B_RFREE);
        }
        PROF(19);
        PROFV(2, g);
        TRACE(warp == 1, n, 1, gtl());
        TRACE(g, n, 2, g);
      }
    }
  } else {
    asm volatile("setmaxnreg.dec.sync.aligned.u32 %0;" ::"n"(RG3));
    asm volatile("barrier.cluster.wait.acquire.aligned;" ::: "memory");
    const uint32_t chk = lane * 32 + ((lane >> 2) << 2);
    const uint32_t bar = sb + B_MTRY + 8 * warp;
    uint32_t mph = 0, waited = 0, pub = 0, pph = 0, nsolo = 0;
    auto publish = [&](uint32_t upto) {
#pragma unroll 1
      for (; pub < upto; pub++) {
        const uint32_t e = prm.slot[pub], l = (e >> 6) & 1;
        if (warp == 3 && (e >> 16)) {
          mbar_wait_wd(sb + B_OTOK + l * 8, (pph >> l) & 1);
          pph ^= 1 << l;
          if (elect_one()) red_rel(&g_cnt[(e >> 16) * CSTRIDE], 1);
        }
      }
    };
#pragma unroll 1
    for (int m = 0; m < nslots; m++) {
      const uint32_t info = prm.slot[m], prod = (info >> 8) & 255, ls = info & 127;
      uint32_t g = 0;
#pragma unroll 1
      for (; waited < prod && waited + 1 < m; waited++) mbar_wait_wd(sb + B_OPI + (waited & 1) * 8, (waited >> 1) & 1);
      uint32_t t0 = lds32(sb + SM_TOPI + (~waited & 1) * 4);
      publish(waited);
      if ((ls & 3) == 0) {
        while (__any_sync(~0u, ld_acq(&g_cnt[(C_XN + (ls >> 2)) * CSTRIDE]) < XN_TARGET)) guard(g);
        fence_async_global();
      }
#pragma unroll 1
      for (uint32_t c = warp; c < 5; c += 4) {
        const uint32_t dst = sb + SM_H + c * 10240, full = sb + B_HFULL + 8 * c;
        const uint4* src = g_mem + (c * 2048 + (ls >> 6) * 1024 + (ls & 1) * 512 + prm.moff);
        const uint32_t d = prod ? prm.d2[(m - prod) * 5 + c] : 0;
        const uint4* tok = g_xn + (size_t)(ls * 2560 + c * 512);
        const uint32_t pp = (m & 1) ^ 1;
        const bool single = waited < prod;
        mbar_wait_wd(full, pp);
        const bool solo = m > 0 && prod == m;
        const uint32_t tokb = solo ? sb + B_TOK : full;
        if (solo && c < 4) mbar_wait_wd(tokb, (nsolo++ & 1) ^ 1);
        mbar_expect_if(lane < 2 && !(solo && c == 4 && lane == 0), lane ? bar : tokb, lane ? 2048 : 8192);
        if (!single) while (__any_sync(~0u, clk() - t0 < d)) {}
        if (c >= 2) mbar_wait_wd(sb + B_HEMPTY + 8 * c, pp);
        mbar_wait_wd(sb + (c < 2 ? B_HEMPTY + 8 * c : c == 2 && !single ? B_PMEM : B_OB), pp);
        if ((c != 2 || single) && !(solo && c == 4)) { if (elect_one()) bulk_g2s(dst + 2048, tok, 8192, tokb); }
        if (single) {
          mbar_wait_wd(sb + B_OPI + (waited & 1) * 8, (waited >> 1) & 1);
          waited++;
          t0 = lds32(sb + SM_TOPI + (~waited & 1) * 4);
          if (solo && c == 0 && elect_one()) {
            mbar_expect(tokb, 8192);
            bulk_g2s(dst + 4 * 10240 + 2048, tok + 2048, 8192, tokb);
          }
          publish(waited);
          while (__any_sync(~0u, clk() - t0 < d)) {}
        }
        else if (c < 2) spin(prm.dh);
        if (elect_one()) bulk_g2s(dst, src, 2048, bar);
        if (c == 2 && !single) {
          mbar_wait_wd(sb + B_OB, pp);
          if (elect_one()) bulk_g2s(dst + 2048, tok, 8192, full);
        }
        g = 0;
        while (true) {
          mbar_wait_wd(bar, mph);
          mph ^= 1;
          const uint32_t v0 = lds32(dst + chk), v1 = lds32(dst + chk + 1024);
          if (__all_sync(~0u, v0 != ~0u && v1 != ~0u)) break;
          if (elect_one()) {
            mbar_expect(bar, 2048);
            bulk_g2s(dst, src, 2048, bar);
          }
          guard(g);
        }
        mbar_arrive_if(lane == 0, full, solo ? 2 : 1);
        TRACE(c < 2, m, 3 + 2 * c, gtl());
        TRACE(c < 2, m, 4 + 2 * c, g);
      }
    }
    publish(nslots);
    if (warp == 0) mbar_wait_wd(sb + B_END, 0);
  }
  __syncwarp();
  if (wid != 12 && lane0 == 0) mbar_arrive(sb + B_END);
  cluster_sync();
}
__device__ uint32_t g_xa[NBLK * 10 * 4096];
__device__ uint32_t g_h[NBLK * 24 * 4096];

enum { T_A = 0, T_F1 = 1, T_U = 2, T_D = 3, T_F2 = 4, T_NONE = 7 };
__host__ __device__ constexpr int c_phase(int type, int lb) { return C_O + type * 32 + lb; }
constexpr int C_TICKET = c_phase(5, 0), C_EXIT = C_TICKET + 1, C_USED = C_HALF + 2 * NBLK;
constexpr int G_NST = 7;
constexpr uint32_t GS_RED = G_NST * 32768, GS_BAR = GS_RED + 1088, G_SMEM = GS_BAR + 224;
constexpr uint32_t GB_FULL = GS_BAR, GB_EMPTY = GS_BAR + 64, GB_ORD = GS_BAR + 128, GB_READY = GS_BAR + 144, GB_ACK = GS_BAR + 152, GB_GATE = GS_BAR + 160, GB_SIG = GS_BAR + 176, GB_SACK = GS_BAR + 192,
                   GS_SIG = GS_BAR + 208, GS_COL = GS_BAR + 216;
#define FPL 6
constexpr int NF = 16;
constexpr int G_EARLY = 36;
constexpr int G_LATE = 96, PL = 6, ML = 8, DL = 30, TL = 10;
constexpr int GRC = 112, GRP = 32;
constexpr uint32_t E_UP = 1u << 8, E_HALF = 1u << 28, E_GRP = 1u << 29, E_HAND = 1u << 30, E_EXCL = 1u << 31;

struct GParams {
  __nv_bfloat16* out;
  const uint32_t* x;
  int moff, gd;
  int pend;
  uint8_t perm[G_EARLY], first[9];
  uint8_t need[5][2 * NBLK];
  uint32_t tab[G_EARLY * (PL + ML + DL) + G_LATE * TL];
};
constexpr int EL = PL + ML + DL, TAB_TAIL = G_EARLY * EL;
struct GIter {
  int p, left, period;
  uint32_t e, type, lb, n0, kb0, nkb;
  bool gemm, valid;
  DI GIter(const GParams& prm, int col) {
    if (col < G_EARLY) { p = col * EL; left = PL; period = 0; }
    else { p = TAB_TAIL + (col - G_EARLY) * TL; left = TL; period = prm.pend; }
  }
  DI bool next(const GParams& prm, int col) {
    do {
      if (left == 0) {
        if (++period > prm.pend) return false;
        left = period < prm.pend ? ML : DL;
        if (period > 1 && period < prm.pend) p -= ML;
      }
      e = prm.tab[p++]; left--;
    } while ((e & 7) == T_NONE);
    const int b = (e >> 4) & 15, blk = period < prm.pend ? period - b : b;
    type = e & 7; valid = blk >= 0; lb = (e & 8) * 2 + (blk & 15); n0 = (e >> 9) & 127; kb0 = (e >> 16) & 127;
    gemm = type != T_F1 && type != T_F2;
    nkb = valid ? (e >> 23) & 31 : 0;
    return true;
  }
  DI int id_(int pend) const { return period < pend ? period * 10 + ML - left : 160 + DL - left; }
};

#define GLOG(nt, i, v)
template <int TA> DI void wg_ss128(float* d, uint64_t da, uint64_t db, int sc) {
  asm volatile("{.reg .pred p; setp.ne.b32 p, %66, 0;\n"
               "wgmma.mma_async.sync.aligned.m64n128k16.f32.bf16.bf16 "
               "{%0,%1,%2,%3,%4,%5,%6,%7,%8,%9,%10,%11,%12,%13,%14,%15,%16,%17,%18,%19,%20,%21,%22,%23,%24,%25,%26,%27,%28,%29,%30,%31,"
               "%32,%33,%34,%35,%36,%37,%38,%39,%40,%41,%42,%43,%44,%45,%46,%47,%48,%49,%50,%51,%52,%53,%54,%55,%56,%57,%58,%59,%60,%61,%62,%63}, "
               "%64, %65, p, 1, 1, %67, 1;}"
               : ACC16(d, 0), ACC16(d, 16), ACC16(d, 32), ACC16(d, 48) : "l"(da), "l"(db), "r"(sc), "n"(TA));
}

template <int TA> DI void g_mainloop(float* acc, uint32_t sb, uint32_t hand, uint32_t gate, int nkb, int cw, int lane, uint32_t st, uint32_t ph) {
  const uint64_t da0 = (TA ? mkdesc(SMEM0, 4096, 512, 2) : mkdesc(SMEM0, 128, 1024, 0)) + (cw >> 2) * 512;
  const uint64_t db0 = mkdesc(SMEM0 + 16384, 8192, 1024, 1);
  uint32_t prev = 0;
#pragma unroll 1
  for (int kb = 0; kb < nkb; kb++) {
    mbar_wait(sb + GB_FULL + 8 * st, ph);
    mbar_wait(gate, 1);
    const uint64_t da = da0 + st * 2048, db = db0 + st * 2048;
    wg_fence();
#pragma unroll
    for (int k = 0; k < 4; k++) wg_ss128<TA>(acc, da + k * (TA ? 64 : 16), db + k * 128, 1);
    wg_commit();
    mbar_arrive_if(hand && kb == nkb - 1 && lane == 0, hand);
    wg_wait<1>();
    mbar_arrive_if(kb > 0 && lane == 0, sb + GB_EMPTY + 8 * prev);
    prev = st;
    if (++st == G_NST) { st = 0; ph ^= 1; }
  }
  wg_wait<0>();
  reg_fence<64>(acc);
  mbar_arrive_if(lane == 0, sb + GB_EMPTY + 8 * prev);
}

__global__ void __launch_bounds__(640, 1)
g_kernel(const __grid_constant__ CUtensorMap mapWo, const __grid_constant__ CUtensorMap mapWg, const __grid_constant__ CUtensorMap mapWu,
         const __grid_constant__ CUtensorMap mapWd, const __grid_constant__ GParams prm) {
  const uint32_t sb = smem_base();
  const int wid = __shfl_sync(~0u, threadIdx.x >> 5, 0), lane = threadIdx.x & 31;
  if (threadIdx.x == 0) {
    if ((sb & 0x3FFFF) != SMEM0) __trap();
    {
      uint32_t sm; asm volatile("mov.u32 %0, %%smid;" : "=r"(sm));
      uint32_t* const tk = &g_cnt[C_TICKET * CSTRIDE];
      uint32_t c = atomicAdd(tk, 1);
      if (c < G_EARLY) {
        const uint32_t k = sm < 64 ? (sm >> 1) & 7 : sm < 120 ? 1 + ((sm - 64) >> 1) % 7 : sm < 124 ? 1 + ((sm >> 1) & 1) : 0;
        const uint32_t t = atomicAdd(tk + 1 + k, 1);
        atomicAdd(tk + 9, 1);
        if (t < prm.first[k + 1] - prm.first[k]) c = prm.perm[prm.first[k] + t];
        else {
          uint32_t o = atomicAdd(tk + 10, 1), g = 0;
          while (ld_acq(tk + 9) < G_EARLY) guard(g);
          for (int j = 0; j < 8; j++)
            for (uint32_t i = prm.first[j] + ld_acq(tk + 1 + j); i < prm.first[j + 1]; i++) if (o-- == 0) c = prm.perm[i];
        }
      }
      sts32(sb + GS_COL, c);
    }
    for (int i = 0; i < G_NST; i++) { mbar_init(sb + GB_FULL + 8 * i, 1); mbar_init(sb + GB_EMPTY + 8 * i, 8); }
    mbar_init(sb + GB_ORD, 8); mbar_init(sb + GB_ORD + 8, 8); mbar_init(sb + GB_READY, 1); mbar_init(sb + GB_ACK, 1);
    mbar_init(sb + GB_GATE, 1); mbar_init(sb + GB_GATE + 8, 1);
    mbar_init(sb + GB_SIG, 8); mbar_init(sb + GB_SIG + 8, 8); mbar_init(sb + GB_SACK, 1); mbar_init(sb + GB_SACK + 8, 1);
    fence_async_smem();
  }
  __syncthreads();
  const int col = __shfl_sync(~0u, lds32(sb + GS_COL), 0);

  if (wid >= 16) {
    GIter t(prm, col);
    asm volatile("setmaxnreg.dec.sync.aligned.u32 %0;" ::"n"(GRP));
    uint32_t st = 0, ph = 1, k = 0;
    if (wid == 16) {
      while (t.next(prm, col)) {
        const CUtensorMap* m0 = t.type == T_A ? &mapWo : t.type == T_U ? &mapWg : &mapWd;
        const CUtensorMap* m1 = t.type == T_U ? &mapWu : m0;
        const int c0 = t.type == T_U ? t.n0 * 64 : (t.n0 & 7) * 128, c1 = t.type == T_U ? c0 : c0 + 64;
        if ((t.e & (E_HALF | E_UP)) == E_UP) poll_ge(&g_cnt[c_phase(t.type, t.lb) * CSTRIDE], prm.need[t.type][t.lb]);
#pragma unroll 1
        for (uint32_t kb = t.kb0; kb < t.kb0 + t.nkb; kb++) {
          mbar_wait(sb + GB_EMPTY + 8 * st, ph);
          if (elect_one()) {
            const uint32_t full = sb + GB_FULL + 8 * st, dst = sb + st * 32768;
            mbar_expect(full, (t.e & E_HALF) ? 24576 : 32768);
            tma_2d(dst + 16384, m0, c0, kb * 64, full);
            tma_2d(dst + 24576, m1, c1, kb * 64, full);
          }
          if (++st == G_NST) { st = 0; ph ^= 1; }
        }
      }
    } else if (wid == 17) {
      while (t.next(prm, col)) {
        if (!t.nkb) continue;
        const char* asrc = t.type == T_A ? (const char*)g_oT + (size_t)t.lb * (96 * 16384)
                         : t.type == T_U ? (const char*)g_xa + (size_t)(t.lb & 15) * (10 * 16384) : (const char*)g_h + (size_t)(t.lb & 15) * (24 * 16384);
        const uint32_t up = (t.e & E_HALF) ? (t.e & E_UP) * 32 : 0;
        GLOG(t.id_(prm.pend), 1, gtime());
        mbar_wait(sb + GB_READY, k & 1);
        mbar_arrive_if(lane == 0, sb + GB_ACK);
        k++;
#pragma unroll 1
        for (uint32_t kb = t.kb0; kb < t.kb0 + t.nkb; kb++) {
          mbar_wait(sb + GB_EMPTY + 8 * st, ph);
          if (elect_one()) bulk_g2s(sb + st * 32768 + up, asrc + (size_t)kb * 16384 + up, (t.e & E_HALF) ? 8192 : 16384, sb + GB_FULL + 8 * st);
          if (++st == G_NST) { st = 0; ph ^= 1; }
        }
      }
    } else if (wid == 18) {
      while (t.next(prm, col)) {
        if (!t.nkb) continue;
        const bool lower = t.type == T_A && (t.e & (E_HALF | E_UP)) == E_HALF;
        poll_ge(&g_cnt[(lower ? C_HALF + t.lb : c_phase(t.type, t.lb)) * CSTRIDE], prm.need[t.type][t.lb]);
        fence_async_global();
        GLOG(t.id_(prm.pend), 2, gtime());
        mbar_wait(sb + GB_ACK, (k & 1) ^ 1);
        mbar_arrive_if(lane == 0, sb + GB_READY);
        k++;
      }
    } else {
      uint32_t live = 3, par = 0, g = 0;
      while (live) {
        const bool ev = lane < 2 && ((live >> lane) & 1) && mbar_test(sb + GB_SIG + 8 * lane, (par >> lane) & 1);
        const uint32_t evs = __ballot_sync(~0u, ev);
        if (!evs) { guard(g); __nanosleep(20); continue; }
        const uint32_t msg = ev ? lds32(sb + GS_SIG + 4 * lane) : 0;
        mbar_arrive_if(ev, sb + GB_SACK + 8 * lane);
        mbar_arrive_if(msg >> 31, sb + GB_GATE + 8 * lane);
        if (msg) red_rel(&g_cnt[(msg & 0xffff) * CSTRIDE], (msg >> 16) & 255);
        par ^= evs;
        live &= ~__ballot_sync(~0u, ev && !msg);
        g = 0;
      }
      asm volatile("griddepcontrol.wait;" ::: "memory");
      if (col < 80 && lane < 16) g_mem[(col >> 4) * 2048 + (lane >> 3) * 1024 + 512 + prm.moff + (col & 15) * 8 + (lane & 7)] = make_uint4(~0u, ~0u, ~0u, ~0u);
      uint32_t last = 0;
      if (lane == 0) last = atomicAdd(&g_cnt[C_EXIT * CSTRIDE], 1) == gridDim.x - 1;
      if (__shfl_sync(~0u, last, 0)) {
        g_cnt[C_TICKET * CSTRIDE + lane] = 0;
        for (int i = lane; i < C_USED; i += 32) g_cnt[i * CSTRIDE] = 0;
      }
    }
  } else {
    asm volatile("setmaxnreg.inc.sync.aligned.u32 %0;" ::"n"(GRC));
    const int cw = wid & 7, wk = wid >> 3;
    GIter t(prm, col);
    uint32_t pos = 0, seen = 0, waited = 0;
    uint32_t nsig = 0;
    auto signal = [&](uint32_t msg) {
      mbar_wait(sb + GB_SACK + 8 * wk, (nsig++ & 1) ^ 1);
      if (cw == 0) sts32(sb + GS_SIG + 4 * wk, msg);
      __syncwarp();
      mbar_arrive_if(lane == 0, sb + GB_SIG + 8 * wk);
    };
    if (col < G_EARLY) {
      spin(prm.gd);
#pragma unroll 1
      for (int rg = 96 + col * 2 + wk; rg < 256; rg += 2 * G_EARLY) {
        uint32_t a[10];
        const uint32_t* src = prm.x + (size_t)(rg * 8 + (lane >> 2)) * (DM / 2) + cw * 40 + (lane & 3);
#pragma unroll
        for (int i = 0; i < 10; i++) a[i] = __ldg(src + i * 4);
        first_ln(a, rg, sb + GS_RED + wk * 512, cw, lane, 1 + wk);
        signal((C_XN + (rg >> 4)) | ((XN_TARGET / NF) << 16));
        bar_sync(1 + wk, 256);
      }
    }
    while (t.next(prm, col)) {
      const uint32_t pos0 = pos;
      pos = (pos + t.nkb) % (2 * G_NST);
      if (((t.e >> 29) & 1) != wk) { seen += (t.e >> 30) & 1; continue; }
      const uint32_t type = t.type, blk = t.lb & 15, layer = t.lb >> 4, n0 = t.n0;
      if (cw == 0 && t.valid) GLOG(t.id_(prm.pend), 0, 0x80000000u | type | (t.lb << 3) | (n0 << 8) | (t.nkb << 16));
      if (!t.gemm) {
        if (!t.valid) continue;
        const int rg = blk * 16 + n0;
        float4 v[5];
        const int off = (n0 * 40 + cw * 5) * 32 + lane, npl = t.kb0;
        const uint2* src = acc_planes(t.lb, type == T_F2) + off;
        if (cw == 0) {
          poll_ge(&g_cnt[c_phase(type, t.lb) * CSTRIDE], prm.need[type][t.lb]);
          mbar_arrive_if((t.e & E_EXCL) && lane == 0, sb + GB_GATE + 8 * wk);
          GLOG(t.id_(prm.pend), 2, gtime()); GLOG(t.id_(prm.pend), 3, gtime());
        }
        bar_sync(1 + wk, 256);
        {
          const uint32_t eye = (lane >> 3) == (lane & 3) ? ((lane & 4) ? 0x3f800000u : 0x00003f80u) : 0u;
#pragma unroll
          for (int i = 0; i < 5; i++) v[i] = make_float4(0.f, 0.f, 0.f, 0.f);
#pragma unroll 1
          for (int p0 = 0; p0 < npl; p0 += FPL) {
            uint32_t r[FPL / 2][5][4];
#pragma unroll
            for (int p = 0; p < FPL; p++)
#pragma unroll
              for (int i = 0; i < 5; i++) {
                const uint2 w = p0 + p < npl ? __ldcg(src + (size_t)(p0 + p) * PLANE + i * 32) : make_uint2(0, 0);
                r[p >> 1][i][(p & 1) * 2] = w.x; r[p >> 1][i][(p & 1) * 2 + 1] = w.y;
              }
#pragma unroll
            for (int p = 0; p < FPL / 2; p++) {
              if (p0 + 2 * p >= npl) break;
              if (t.e & E_EXCL) {
#pragma unroll
                for (int i = 0; i < 5; i++) mma16816(&v[i].x, r[p][i], eye, eye);
              } else {
#pragma unroll
                for (int i = 0; i < 5; i++) {
                  const uint32_t* w = r[p][i];
                  v[i].x += blo(w[0]) + blo(w[2]); v[i].y += bhi(w[0]) + bhi(w[2]); v[i].z += blo(w[1]) + blo(w[3]); v[i].w += bhi(w[1]) + bhi(w[3]);
                }
              }
            }
          }
        }
        if (type == T_F2 && layer == 1) {
          uint2* dst = (uint2*)prm.out + (size_t)(rg * 8 + (lane >> 2)) * (DM / 4) + cw * 20 + (lane & 1) * 2 + ((lane >> 1) & 1);
#pragma unroll
          for (int i = 0; i < 5; i++) {
            const uint32_t a = pack2(v[i].x, v[i].y), b = pack2(v[i].z, v[i].w);
            const uint32_t o = __shfl_xor_sync(~0u, (lane & 1) ? a : b, 1);
            dst[i * 4] = (lane & 1) ? make_uint2(o, b) : make_uint2(a, o);
          }
        } else {
          uint2* nx = (type == T_F1 ? acc_planes(t.lb, 1) : acc_planes(NBLK + blk, 0)) + off;
#pragma unroll
          for (int i = 0; i < 5; i++) {
            const uint2 w = make_uint2(pack2(v[i].x, v[i].y), pack2(v[i].z, v[i].w));
            nx[i * 32] = w;
            v[i] = make_float4(blo(w.x), bhi(w.x), blo(w.y), bhi(w.y));
          }
          float mean, rstd;
          ln_stats(v, sb + GS_RED + wk * 512, cw, lane, 1 + wk, mean, rstd);
          if (type == T_F2) store_img<4, 2048>(xn_row_group(1, rg) + lane, v, cw, mean, rstd);
          else store_img<3, 4096>(g_xa + (size_t)(blk * 10 * 4096 + n0 * 256) + lane, v, cw, mean, rstd);
        }
      } else {
        float acc[64];
#pragma unroll
        for (int j = 0; j < 64; j++) acc[j] = 0.f;
        if (waited != seen) { mbar_wait(sb + GB_ORD + 8 * (wk ^ 1), waited & 1); waited++; }
        const uint32_t hand = (t.e & E_HAND) ? sb + GB_ORD + 8 * wk : 0;
        if (!t.valid) { mbar_arrive_if(hand && lane == 0, hand); continue; }
        if (cw == 0) GLOG(t.id_(prm.pend), 3, gtime());
        const uint32_t ph = pos0 >= G_NST, st = pos0 - ph * G_NST, early = (t.e & E_EXCL) ? 0 : hand;
        const bool idle = (t.e & E_HALF) && ((t.e >> 8) & 1) != (cw >> 2);
        if (idle) {
          uint32_t s2 = st, p2 = ph;
#pragma unroll 1
          for (uint32_t kb = 0; kb < t.nkb; kb++) {
            mbar_wait(sb + GB_FULL + 8 * s2, p2);
            mbar_arrive_if(lane == 0, sb + GB_EMPTY + 8 * s2);
            if (++s2 == G_NST) { s2 = 0; p2 ^= 1; }
          }
          mbar_arrive_if(early && lane == 0, early);
        } else if (type == T_A) g_mainloop<1>(acc, sb, early, sb + GB_GATE + 8 * (wk ^ 1), t.nkb, cw, lane, st, ph);
        else g_mainloop<0>(acc, sb, early, sb + GB_GATE + 8 * (wk ^ 1), t.nkb, cw, lane, st, ph);
        if (cw == 0) GLOG(t.id_(prm.pend), 4, gtime());
        if (idle) {
        } else if (type == T_U) {
          uint32_t* dst = g_h + (size_t)((blk * 24 + n0) * 4096 + cw * 512) + lane;
#pragma unroll
          for (int j = 0; j < 8; j++) {
            float h[4];
#pragma unroll
            for (int e = 0; e < 4; e++) {
              float th;
              asm("tanh.approx.f32 %0, %1;" : "=f"(th) : "f"(0.5f * acc[4 * j + e]));
              h[e] = acc[32 + 4 * j + e] * fmaf(th, 0.5f, 0.5f);
            }
            dst[j * 32] = pack2(h[0], h[1]);
            dst[j * 32 + 256] = pack2(h[2], h[3]);
          }
        } else {
          uint2* dst = acc_planes(t.lb, type == T_D) + (size_t)((1 + (n0 >> 3)) * PLANE + (2 * cw * 40 + (n0 & 7) * 8) * 32) + lane;
#pragma unroll
          for (int j = 0; j < 16; j++) {
            const float* a = acc + (j >> 1) * 8 + (j & 1) * 2;
            dst[(j >> 1) * 32 + (j & 1) * 1280] = make_uint2(pack2(a[0], a[1]), pack2(a[4], a[5]));
          }
        }
        mbar_arrive_if(hand != early && lane == 0, hand);
      }
      if (cw == 0) GLOG(t.id_(prm.pend), 5, gtime());
      if (cw == 0) GLOG(t.id_(prm.pend), 6, gtime());
      if (type == T_F2 && layer == 1) mbar_arrive_if((t.e & E_EXCL) && cw == 0 && lane == 0, sb + GB_GATE + 8 * wk);
      else
        signal((type != T_F2 ? c_phase(type + 1, t.lb) | (1 << 16) : (C_XN + NBLK + blk) | ((XN_TARGET / NF) << 16)) | (t.gemm ? 0 : t.e & E_EXCL));
    }
    signal(0);
  }
}

typedef CUresult (*EncodeFn)(CUtensorMap*, CUtensorMapDataType, cuuint32_t, void*, const cuuint64_t*, const cuuint64_t*, const cuuint32_t*,
                             const cuuint32_t*, CUtensorMapInterleave, CUtensorMapSwizzle, CUtensorMapL2promotion, CUtensorMapFloatOOBfill);
static CUtensorMap make_map(EncodeFn fn, const void* p, uint64_t inner, uint64_t outer, uint32_t bi, uint32_t bo, int promo = 3) {
  CUtensorMap m;
  cuuint64_t dims[2] = {inner, outer}, str[1] = {inner * 2};
  cuuint32_t box[2] = {bi, bo}, es[2] = {1, 1};
  fn(&m, CU_TENSOR_MAP_DATA_TYPE_BFLOAT16, 2, (void*)p, dims, str, box, es, CU_TENSOR_MAP_INTERLEAVE_NONE, CU_TENSOR_MAP_SWIZZLE_128B,
     (CUtensorMapL2promotion)promo, CU_TENSOR_MAP_FLOAT_OOB_FILL_NONE);
  return m;
}
struct Tune {
  int lag = 11, excl = 6, gonly = 0, xl = 1, ronly = 0, pn = 30;
  int da = 120, db = 350, dc = 650, dd = 650, d2 = 2170, p1 = 300, p2 = 800;
  int ea = 60, eb = 310, ec = 550, ed = 550, e2 = 2200, q1 = 200, q2 = 400, d3 = 60, moff = 192, ds = 400, dh = 60, pa = 0, pb = 0, pc = 0, pd = 0, pe = 0, pf = 0, pg = 0, ph = 0, wpf = 4, gd = 22000, dq = 300, sl = 18, pr = 2, pg2 = 3;
};
static void fill_r(RParams& p, const Tune& t, int lag, int n0, int n1) {
  r_fill_desc(p);
  p.nslots = 0; p.d3 = t.d3; p.pn = t.pn; p.moff = t.moff; p.ds = t.ds; p.dh = t.dh; p.dq = t.dq;
  for (int c = 0; c < 5; c++) { p.d2[c] = t.d2 + (c == 0 ? 0 : c < 3 ? t.p1 : t.p2); p.d2[5 + c] = t.e2 + (c == 0 ? 0 : c < 3 ? t.q1 : t.q2); }
  const int d1[8] = {t.da, t.db, t.dc, t.dd, t.ea, t.eb, t.ec, t.ed};
  for (int i = 0; i < 8; i++) p.d1[i] = d1[i];
  int last[2] = {0, 0}, n = 0;
  for (int s0 = 0; s0 < NSEG + lag; s0++)
    for (int l = 0; l < 2; l++) {
      const int s = l ? s0 - lag : s0;
      if (s < 0 || s >= NSEG) continue;
      if (n >= n0 && n < n1) { p.slot[p.nslots] = s | (l << 6) | (last[l] << 8) | (((s & 3) == 3 ? C_O + l * NBLK + s / 4 : s == (l ? 61 : 1) ? C_HALF + l * NBLK + s / 4 : 0) << 16); last[l] = ++p.nslots; }
      n++;
    }
  for (int i = 0; i + 1 < p.nslots; i++) if (((p.slot[i] ^ p.slot[i + 1]) >> 6) & 1) p.slot[i] |= 128;
}
static uint32_t g_entry(int grp, int type, int layer, int blk, int i, int ks) {
  int n0 = i, kb0 = 0, kb1 = type == T_U ? 10 : 0;
  if (type == T_F1 || type == T_F2) kb0 = kb1 = ks + 1;
  if (type == T_A || type == T_D) {
    const int KB = type == T_A ? 96 : 24, sp = i / 5;
    n0 = i % 5 | (sp << 3); kb0 = sp * KB / ks; kb1 = (sp + 1) * KB / ks;
  }
  return type | (layer << 3) | (blk << 4) | (n0 << 9) | (kb0 << 16) | ((kb1 - kb0) << 23) | (grp ? E_GRP : 0);
}
static bool g_is_gemm(uint32_t e) { return (e & 7) == T_A || (e & 7) == T_U || (e & 7) == T_D; }
static void g_handover(uint32_t* e, int len) {
  uint32_t next = 0;
  for (int i = len - 1; i >= 0; i--)
    if (g_is_gemm(e[i])) { if ((e[i] & E_GRP) != next) e[i] |= E_HAND; next = e[i] & E_GRP; }
}
static bool g_overflow = false;
struct GList {
  static void overflow() { g_overflow = true; }
  bool shared = false;
  GParams& g; uint32_t* tab; int ncol, stride, len, n[G_LATE], load[G_LATE], grp[G_LATE];
  GList(GParams& g_, uint32_t* t, int nc, int st, int l) : g(g_), tab(t), ncol(nc), stride(st), len(l) { for (int c = 0; c < nc; c++) { n[c] = load[c] = 0; grp[c] = 1; } }
  void add(int type, int lb, int ks, int c0, int c1, uint32_t flags = 0, int i0 = 0, int i1 = 999, int step = 1) {
    const int half = (flags & E_HALF) != 0, ln = type == T_F1 || type == T_F2;
    const int cnt = (type == T_U ? 24 : ln ? NF : 5 * ks) << half;
    if (type < T_F2) g.need[type + 1][lb] = cnt;
    int used[G_LATE] = {0};
    for (int i = i0; i < cnt && i < i1; i += step) {
      int best = c0;
      for (int c = c0; c < c1; c++) if (used[c] < used[best] || (used[c] == used[best] && load[c] < load[best])) best = c;
      used[best]++;
      if (!ln) grp[best] ^= 1;
      const uint32_t e = g_entry(grp[best], type, lb >> 4, lb & 15, i >> half, ks) | flags | (ln && !shared ? E_EXCL : 0) | ((i & half) ? E_UP : 0);
      if (n[best] >= len) { overflow(); return; }
      tab[best * stride + n[best]++] = e;
      load[best] += (((e >> 23) & 31) >> half) + 2;
    }
  }
  void put(int c, uint32_t e) { if (n[c] >= len) { overflow(); return; } tab[c * stride + n[c]++] = e; if (g_is_gemm(e)) grp[c] = (e & E_GRP) != 0; }
  void finish() { for (int c = 0; c < ncol; c++) g_handover(tab + c * stride, len); }
};
static void fill_g(GParams& g, const Tune& t, void* out) {
  g.out = (__nv_bfloat16*)out;  g.pend = NBLK - 2;
  for (int b = 0; b < 2 * NBLK; b++) {
    g.need[T_A][b] = 96; g.need[T_F1][b] = 20; g.need[T_U][b] = NF; g.need[T_D][b] = 32; g.need[T_F2][b] = 15;
  }
  {
    const uint8_t perm[G_EARLY] = {0, 1, 2, 3, 16, 17, 18, 19, 34, 35, 4, 20, 21, 15, 22, 23, 5, 6, 7, 8, 9, 24, 25, 26, 10, 11, 12, 13, 14, 27, 28, 29, 30, 31, 32, 33};
    const uint8_t first[9] = {0, 10, 13, 16, 20, 24, 28, 32, 36};
    const int* pk = &t.pa;
    for (int i = 0; i < G_EARLY; i++) g.perm[i] = t.pa ? (pk[i / 5] >> (6 * (i % 5))) & 63 : perm[i];
    for (int i = 0; i < 9; i++) g.first[i] = first[i];
  }
  for (uint32_t& e : g.tab) e = T_NONE;
  GList pr(g, g.tab, G_EARLY, EL, PL);
  pr.add(T_A, 0, 7, 1, 36, E_HALF, 0, 999, 2); pr.add(T_A, 0, 7, 1, 36, E_HALF, 1, 999, 2); pr.add(T_F1, 0, 7, 20, 36); pr.add(T_U, 0, 0, 12, 36);
  pr.add(T_D, 0, 3, 20, 36); pr.add(T_F2, 0, 3, 20, 36);
  pr.finish();
  const int d = 3;
  const uint32_t xa = (t.excl & 1) ? E_EXCL : 0, xu = (t.excl & 2) ? E_EXCL : 0, xd = (t.excl & 4) ? E_EXCL : 0;
  for (int c = 0; c < G_EARLY; c++) {
    uint32_t* e = g.tab + c * EL + PL;
    if (c < 20) {
      *e++ = g_entry(0, T_A, 0, 0, c, 4) | xa;
      if (c < NF) *e++ = g_entry(0, T_F1, 0, 0, c, 4) | ((t.xl & 1) ? E_EXCL : 0);
      *e++ = g_entry(1, T_A, 1, d, c, 4);
      if (c >= 20 - NF) *e++ = g_entry(1, T_F1, 1, d, c - (20 - NF), 4);
    } else {
      const int j = c - 20;
      const uint32_t hf = E_HALF | ((j & 1) ? E_UP : 0);
      *e++ = g_entry(0, T_U, 0, 0, j, 0);
      *e++ = g_entry(1, T_U, 0, 0, 16 + j / 2, 0) | hf | xu;
      *e++ = g_entry(0, T_U, 1, d + 1, 16 + j / 2, 0) | hf;
      if (j < 15) *e++ = g_entry(1, T_D, 0, 0, j, 3) | xd;
      *e++ = g_entry(1, T_F2, 0, 0, j, 3) | ((t.xl & 2) ? E_EXCL : 0);
      if (j < 15) *e++ = g_entry(0, T_D, 1, d + 1, j, 3);
      *e++ = g_entry(0, T_U, 1, d, j, 0);
      *e++ = g_entry(1, T_F2, 1, d + 1, j, 3);
    }
    g_handover(g.tab + c * EL + PL, ML);
  }
  GList dr(g, g.tab + PL + ML, G_EARLY, EL, DL);
  GList tl(g, g.tab + TAB_TAIL, G_LATE, TL, TL);
  const int L1 = NBLK;
  auto ufull = [&](int lb, uint32_t fl) { dr.add(T_U, lb, 0, 20, 36, fl, 0, 16); g.need[T_D][lb] = 32; };
  auto uhalf = [&](int lb, int c0, uint32_t fl) { dr.add(T_U, lb, 0, c0, 36, E_HALF | fl, 32); g.need[T_D][lb] = 32; };
  for (int c = 0; c < G_EARLY; c++)
    for (int i = 0; i < ML; i++) {
      uint32_t e = g.tab[c * EL + PL + i] & ~E_HAND;
      const uint32_t ty = e & 7;
      if (ty == T_NONE || ((e & 8) && (ty == T_F2 || (ty == T_U && !(e & E_HALF))))) continue;
      e = (e & ~0xf0u) | (14 - ((e >> 4) & 15)) << 4;
      dr.put(c, e | (ty == T_F2 ? E_EXCL : 0));
    }
  dr.add(T_A, 15, 4, 0, 20, E_EXCL);
  dr.add(T_F1, 15, 4, 4, 20);
  dr.add(T_U, 15, 0, 12, 36, E_EXCL);
  for (int c = 0; c < 20; c++) {
    const int tile = c % 5, sp = c / 5, len = tile < 2 ? (96 - t.sl) / 3 : 48 - t.sl, nl = tile < 2 ? 3 : 2;
    const int k0 = sp <= nl ? sp * len : nl * len + t.sl, nk = sp < nl ? len : sp == 3 ? 96 - k0 : t.sl;
    dr.put(c, (g_entry(dr.grp[c] ^ 1, T_A, 1, 12, c, 4) & ~0x0fff0000u) | k0 << 16 | nk << 23);
  }
  dr.add(T_F1, L1 + 12, 4, 0, 16);
  dr.add(T_A, L1 + 13, 4, 0, 20);
  dr.add(T_D, 15, 3, 20, 36, E_EXCL); dr.add(T_F2, 15, 3, 20, 36);
  ufull(L1 + 11, 0); uhalf(L1 + 11, 20, 0);
  dr.add(T_A, L1 + 14, 4, 0, 20, E_EXCL);
  dr.add(T_F1, L1 + 13, 4, 0, 20);
  dr.add(T_D, L1 + 11, 3, 20, 36);
  ufull(L1 + 12, E_UP); uhalf(L1 + 12, 12, E_EXCL);
  dr.add(T_A, L1 + 15, 7, 0, 35, E_HALF | E_EXCL, 0, 999, 2); dr.add(T_A, L1 + 15, 7, 0, 35, E_HALF | E_EXCL, 1, 999, 2);
  dr.add(T_F1, L1 + 15, 7, 20, 36);
  dr.add(T_F2, L1 + 10, 3, 0, 20);
  dr.shared = true; dr.add(T_F2, L1 + 11, 3, 4, 20); dr.shared = false;
  dr.add(T_D, L1 + 13, 3, 4, 20, E_UP);
  dr.add(T_F2, L1 + 12, 3, 0, 20);
  dr.finish();
  tl.add(T_D, L1 + 12, 3, 72, G_LATE);
  tl.add(T_U, L1 + 13, 0, 24, 48, E_EXCL);
  tl.add(T_F1, L1 + 14, 4, 0, 48);
  tl.add(T_U, L1 + 14, 0, 0, 24);
  tl.add(T_D, L1 + 14, 4, 0, 48, E_HALF | E_EXCL);
  tl.add(T_U, L1 + 15, 0, 48, G_LATE, E_HALF);
  tl.add(T_D, L1 + 15, 4, 48, G_LATE, E_HALF);
  tl.add(T_F2, L1 + 13, 3, 48, 72);
  tl.add(T_F2, L1 + 14, 4, 0, 48);
  tl.add(T_F2, L1 + 15, 4, 48, G_LATE);
  tl.finish();
}
static void launch_all(void* const* d_in, void* d_out, const Tune& t, cudaStream_t st) {
  static EncodeFn fn = nullptr;
  if (!fn) {
    void* f = nullptr;
    cudaDriverEntryPointQueryResult qr;
    cudaGetDriverEntryPoint("cuTensorMapEncodeTiled", &f, cudaEnableDefault, &qr);
    fn = (EncodeFn)f;
    cudaFuncSetAttribute(r_kernel, cudaFuncAttributeMaxDynamicSharedMemorySize, R_SMEM);
    cudaFuncSetAttribute(g_kernel, cudaFuncAttributeMaxDynamicSharedMemorySize, G_SMEM);
  }
  const CUtensorMap mq = make_map(fn, d_in[2], HD, DM, 64, 128, t.pr), mk = make_map(fn, d_in[3], HD, DM, 64, 128, t.pr), mv = make_map(fn, d_in[4], HD, DM, 64, 128, t.pr),
                    mo = make_map(fn, d_in[5], DM, HD, 64, 64, t.pg2), mg = make_map(fn, d_in[8], FF, DM, 64, 64, t.pg2), mu = make_map(fn, d_in[9], FF, DM, 64, 64, t.pg2),
                    md = make_map(fn, d_in[10], DM, FF, 64, 64, t.pg2);
  auto launch_r = [&](int lag, int n0, int n1) {
    RParams p;
    fill_r(p, t, lag, n0, n1);
    p.mem0 = (const uint4*)d_in[1]; p.x = (const uint32_t*)d_in[0]; p.pf = t.wpf;
    cudaLaunchConfig_t cfg = {};
    cfg.gridDim = dim3(3, NH); cfg.blockDim = dim3(512); cfg.dynamicSmemBytes = R_SMEM; cfg.stream = st;
    cudaLaunchAttribute at[1];
    at[0].id = cudaLaunchAttributeClusterDimension; at[0].val.clusterDim.x = 3; at[0].val.clusterDim.y = 1; at[0].val.clusterDim.z = 1;
    cfg.attrs = at; cfg.numAttrs = 1;
    cudaLaunchKernelEx(&cfg, r_kernel, mq, mk, mv, mo, p);
  };
  auto launch_g = [&](const GParams& g, bool pdl) {
    cudaLaunchConfig_t cfg = {};
    cfg.gridDim = dim3(132); cfg.blockDim = dim3(640); cfg.dynamicSmemBytes = G_SMEM; cfg.stream = st;
    cudaLaunchAttribute at[2];
    at[0].id = cudaLaunchAttributeProgrammaticStreamSerialization; at[0].val.programmaticStreamSerializationAllowed = 1;
    cfg.attrs = at; cfg.numAttrs = pdl ? 1 : 0;
    cudaLaunchKernelEx(&cfg, g_kernel, mo, mg, mu, md, g);
  };
  GParams g;
  fill_g(g, t, d_out);
  g.moff = t.moff; g.gd = t.gd; g.x = (const uint32_t*)d_in[0];
  launch_r(t.lag, 0, 2 * NSEG);
  launch_g(g, true);
}

extern "C" void kernel_launch(void* const* d_in, const int* in_sizes, int n_in, void* d_out, int out_size) {
  launch_all(d_in, d_out, Tune(), cudaStreamPerThread);
}
```

```cpp
#include <cuda_runtime.h>
#include <cuda_bf16.h>
#include <cuda.h>
#include <stdint.h>
#include <stdlib.h>

constexpr int SEQ = 2048, DM = 640, NH = 32, DH = 192, HD = NH * DH, FF = 1536;
constexpr int NSEG = 64, SEGL = 32, NMEM = 8;
constexpr int NBLK = 16;

#define DI __device__ __forceinline__

DI uint32_t smem_base() {
  extern __shared__ __align__(1024) unsigned char smem_raw[];
  uint32_t a;
  asm volatile("{.reg .u64 t; cvta.to.shared.u64 t, %1; cvt.u32.u64 %0, t;}" : "=r"(a) : "l"(smem_raw));
  return a;
}
DI uint32_t mapa(uint32_t a, uint32_t r) {
  uint32_t o;
  asm("mapa.shared::cluster.u32 %0, %1, %2;" : "=r"(o) : "r"(a), "r"(r));
  return o;
}
DI void mbar_init(uint32_t bar, uint32_t cnt) { asm volatile("mbarrier.init.shared::cta.b64 [%0], %1;" ::"r"(bar), "r"(cnt) : "memory"); }
DI void mbar_arrive(uint32_t bar) { asm volatile("mbarrier.arrive.shared::cta.b64 _, [%0];" ::"r"(bar) : "memory"); }
DI void mbar_expect(uint32_t bar, uint32_t tx) { asm volatile("mbarrier.arrive.expect_tx.shared::cta.b64 _, [%0], %1;" ::"r"(bar), "r"(tx) : "memory"); }
DI void mbar_arrive_if(bool p, uint32_t bar) { asm volatile("{.reg .pred p; setp.ne.b32 p, %1, 0; @p mbarrier.arrive.shared::cta.b64 _, [%0];}" ::"r"(bar), "r"((int)p) : "memory"); }
DI void mbar_arrive_if(bool p, uint32_t bar, uint32_t cnt) {
  asm volatile("{.reg .pred p; setp.ne.b32 p, %1, 0; @p mbarrier.arrive.shared::cta.b64 _, [%0], %2;}" ::"r"(bar), "r"((int)p), "r"(cnt) : "memory");
}
DI void mbar_expect_if(bool p, uint32_t bar, uint32_t tx) {
  asm volatile("{.reg .pred p; setp.ne.b32 p, %2, 0; @p mbarrier.arrive.expect_tx.shared::cta.b64 _, [%0], %1;}" ::"r"(bar), "r"(tx), "r"((int)p) : "memory");
}
DI bool mbar_test(uint32_t bar, uint32_t par) {
  uint32_t ok;
  asm volatile("{.reg .pred p; mbarrier.test_wait.parity.shared::cta.b64 p, [%1], %2; selp.u32 %0, 1, 0, p;}" : "=r"(ok) : "r"(bar), "r"(par) : "memory");
  return ok;
}
DI void mbar_wait(uint32_t bar, uint32_t par) {
  asm volatile(
      "{.reg .pred p;\n"
      "LOOP:\n"
      "mbarrier.try_wait.parity.shared::cta.b64 p, [%0], %1;\n"
      "@!p bra LOOP;\n}" ::"r"(bar), "r"(par) : "memory");
}
DI void mbar_wait_wd(uint32_t bar, uint32_t par) {
  asm volatile(
      "{.reg .pred p; .reg .u32 c;\n"
      "mov.u32 c, 0;\n"
      "LOOP:\n"
      "mbarrier.try_wait.parity.shared::cta.b64 p, [%0], %1;\n"
      "@p bra DONE;\n"
      "add.u32 c, c, 1;\n"
      "setp.lt.u32 p, c, 4000000;\n"
      "@p bra LOOP;\n"
      "trap;\n"
      "DONE:\n}" ::"r"(bar), "r"(par) : "memory");
}
DI void fence_async_smem() { asm volatile("fence.proxy.async.shared::cta;" ::: "memory"); }
DI void fence_async_global() { asm volatile("fence.proxy.async.global;" ::: "memory"); }
DI void bar_sync(int id, int n) { asm volatile("bar.sync %0, %1;" ::"r"(id), "r"(n) : "memory"); }
DI void bar_arrive(int id, int n) { asm volatile("bar.arrive %0, %1;" ::"r"(id), "r"(n) : "memory"); }
DI void cluster_sync() { asm volatile("barrier.cluster.arrive.release.aligned; barrier.cluster.wait.acquire.aligned;" ::: "memory"); }
DI bool elect_one() {
  uint32_t p;
  asm volatile("{.reg .pred p; elect.sync _|p, 0xffffffff; selp.u32 %0, 1, 0, p;}" : "=r"(p));
  return p;
}
DI void bulk_g2s(uint32_t dst, const void* src, uint32_t bytes, uint32_t bar) {
  asm volatile("cp.async.bulk.shared::cluster.global.mbarrier::complete_tx::bytes [%0], [%1], %2, [%3];" ::"r"(dst), "l"(src), "r"(bytes), "r"(bar) : "memory");
}
DI void bulk_s2s(uint32_t dst, uint32_t src, uint32_t bytes, uint32_t bar) {
  asm volatile("cp.async.bulk.shared::cluster.shared::cta.mbarrier::complete_tx::bytes [%0], [%1], %2, [%3];" ::"r"(dst), "r"(src), "r"(bytes), "r"(bar) : "memory");
}
DI void tma_2d(uint32_t dst, const CUtensorMap* map, int c0, int c1, uint32_t bar) {
  asm volatile("cp.async.bulk.tensor.2d.shared::cluster.global.mbarrier::complete_tx::bytes [%0], [%1, {%3, %4}], [%2];" ::"r"(dst), "l"(map), "r"(bar), "r"(c0), "r"(c1) : "memory");
}
DI void st_async4(uint32_t a, uint32_t x, uint32_t y, uint32_t z, uint32_t w, uint32_t bar) {
  asm volatile("st.async.shared::cluster.mbarrier::complete_tx::bytes.v4.b32 [%0], {%1,%2,%3,%4}, [%5];" ::"r"(a), "r"(x), "r"(y), "r"(z), "r"(w), "r"(bar) : "memory");
}
DI void st_async1(uint32_t a, uint32_t x, uint32_t bar) {
  asm volatile("st.async.shared::cluster.mbarrier::complete_tx::bytes.b32 [%0], %1, [%2];" ::"r"(a), "r"(x), "r"(bar) : "memory");
}
DI void sts32(uint32_t a, uint32_t x) { asm volatile("st.shared.b32 [%0], %1;" ::"r"(a), "r"(x) : "memory"); }
DI void sts128(uint32_t a, uint4 v) { asm volatile("st.shared.v4.b32 [%0], {%1,%2,%3,%4};" ::"r"(a), "r"(v.x), "r"(v.y), "r"(v.z), "r"(v.w) : "memory"); }
DI uint32_t lds32(uint32_t a) { uint32_t v; asm volatile("ld.shared.b32 %0, [%1];" : "=r"(v) : "r"(a) : "memory"); return v; }
DI uint2 lds64(uint32_t a) { uint2 v; asm volatile("ld.shared.v2.b32 {%0,%1}, [%2];" : "=r"(v.x), "=r"(v.y) : "r"(a) : "memory"); return v; }
DI uint4 lds128(uint32_t a) { uint4 v; asm volatile("ld.shared.v4.b32 {%0,%1,%2,%3}, [%4];" : "=r"(v.x), "=r"(v.y), "=r"(v.z), "=r"(v.w) : "r"(a) : "memory"); return v; }
DI void stsm4(uint32_t a, uint32_t r0, uint32_t r1, uint32_t r2, uint32_t r3) {
  asm volatile("stmatrix.sync.aligned.m8n8.x4.shared.b16 [%0], {%1,%2,%3,%4};" ::"r"(a), "r"(r0), "r"(r1), "r"(r2), "r"(r3) : "memory");
}
DI void stsm2(uint32_t a, uint32_t r0, uint32_t r1) {
  asm volatile("stmatrix.sync.aligned.m8n8.x2.shared.b16 [%0], {%1,%2};" ::"r"(a), "r"(r0), "r"(r1) : "memory");
}
DI uint32_t movm(uint32_t a) { uint32_t d; asm volatile("movmatrix.sync.aligned.m8n8.trans.b16 %0, %1;" : "=r"(d) : "r"(a)); return d; }
DI uint32_t pack2(float lo, float hi) { uint32_t d; asm("cvt.rn.bf16x2.f32 %0, %1, %2;" : "=r"(d) : "f"(hi), "f"(lo)); return d; }
DI void st_rlx1(void* p, uint32_t x) { asm volatile("st.relaxed.gpu.global.u32 [%0], %1;" ::"l"(p), "r"(x) : "memory"); }
DI uint32_t ld_acq(const uint32_t* p) { uint32_t v; asm volatile("ld.acquire.gpu.global.u32 %0, [%1];" : "=r"(v) : "l"(p) : "memory"); return v; }
DI uint32_t ld_rlx(const uint32_t* p) { uint32_t v; asm volatile("ld.relaxed.gpu.global.u32 %0, [%1];" : "=r"(v) : "l"(p) : "memory"); return v; }
DI void red_rel(uint32_t* p, uint32_t v) { asm volatile("red.release.gpu.global.add.u32 [%0], %1;" ::"l"(p), "r"(v) : "memory"); }
DI void guard(uint32_t& g) { asm volatile("{.reg .pred p; add.u32 %0, %0, 1; setp.gt.u32 p, %0, 8000000; @p trap;}" : "+r"(g)); }
DI void poll_ge(const uint32_t* p, uint32_t target) {
  asm volatile(
      "{.reg .pred p; .reg .u32 v;\n"
      "LOOP:\n"
      "ld.acquire.gpu.global.u32 v, [%0];\n"
      "setp.lt.u32 p, v, %1;\n"
      "vote.sync.any.pred p, p, 0xffffffff;\n"
      "@p bra.uni LOOP;\n}" ::"l"(p), "r"(target) : "memory");
}
DI float ex2(float x) { float y; asm("ex2.approx.ftz.f32 %0, %1;" : "=f"(y) : "f"(x)); return y; }

DI void wg_fence() { asm volatile("wgmma.fence.sync.aligned;" ::: "memory"); }
DI void wg_commit() { asm volatile("wgmma.commit_group.sync.aligned;" ::: "memory"); }
template <int N> DI void wg_wait() { asm volatile("wgmma.wait_group.sync.aligned %0;" ::"n"(N) : "memory"); }
template <int N> DI void reg_fence(float* d) {
#pragma unroll
  for (int i = 0; i < N; i++) asm volatile("" : "+f"(d[i])::"memory");
}
__host__ __device__ constexpr uint64_t mkdesc(uint32_t addr, uint32_t lbo, uint32_t sbo, uint32_t sw) {
  return (uint64_t)((addr & 0x3FFFF) >> 4) | ((uint64_t)(lbo >> 4) << 16) | ((uint64_t)(sbo >> 4) << 32) | ((uint64_t)sw << 62);
}

#define ACC4(d, o) "+f"(d[o]), "+f"(d[o + 1]), "+f"(d[o + 2]), "+f"(d[o + 3])
#define ACC16(d, o) ACC4(d, o), ACC4(d, o + 4), ACC4(d, o + 8), ACC4(d, o + 12)
#define ACC20(d) ACC16(d, 0), ACC4(d, 16)

template <int TA, int TB> DI void wg_ss40(float* d, uint64_t da, uint64_t db, int sc) {
  asm volatile("{.reg .pred p; setp.ne.b32 p, %22, 0;\n"
               "wgmma.mma_async.sync.aligned.m64n40k16.f32.bf16.bf16 {%0,%1,%2,%3,%4,%5,%6,%7,%8,%9,%10,%11,%12,%13,%14,%15,%16,%17,%18,%19}, %20, %21, p, 1, 1, %23, %24;}"
               : ACC20(d) : "l"(da), "l"(db), "r"(sc), "n"(TA), "n"(TB));
}
DI void wg_rs40(float* d, uint32_t a0, uint32_t a1, uint32_t a2, uint32_t a3, uint64_t db, int sc) {
  asm volatile("{.reg .pred p; setp.ne.b32 p, %25, 0;\n"
               "wgmma.mma_async.sync.aligned.m64n40k16.f32.bf16.bf16 {%0,%1,%2,%3,%4,%5,%6,%7,%8,%9,%10,%11,%12,%13,%14,%15,%16,%17,%18,%19}, {%20,%21,%22,%23}, %24, p, 1, 1, 0;}"
               : ACC20(d) : "r"(a0), "r"(a1), "r"(a2), "r"(a3), "l"(db), "r"(sc));
}
DI void wg_rs32(float* d, uint32_t a0, uint32_t a1, uint32_t a2, uint32_t a3, uint64_t db, int sc) {
  asm volatile("{.reg .pred p; setp.ne.b32 p, %21, 0;\n"
               "wgmma.mma_async.sync.aligned.m64n32k16.f32.bf16.bf16 {%0,%1,%2,%3,%4,%5,%6,%7,%8,%9,%10,%11,%12,%13,%14,%15}, {%16,%17,%18,%19}, %20, p, 1, 1, 0;}"
               : ACC16(d, 0) : "r"(a0), "r"(a1), "r"(a2), "r"(a3), "l"(db), "r"(sc));
}
DI void wg_ss32k(float* d, uint64_t da, uint64_t db, int sc) {
  asm volatile("{.reg .pred p; setp.ne.b32 p, %18, 0;\n"
               "wgmma.mma_async.sync.aligned.m64n32k16.f32.bf16.bf16 {%0,%1,%2,%3,%4,%5,%6,%7,%8,%9,%10,%11,%12,%13,%14,%15}, %16, %17, p, 1, 1, 1, 0;}"
               : ACC16(d, 0) : "l"(da), "l"(db), "r"(sc));
}
DI void wg_ss8k(float* d, uint64_t da, uint64_t db, int sc) {
  asm volatile("{.reg .pred p; setp.ne.b32 p, %6, 0;\n"
               "wgmma.mma_async.sync.aligned.m64n8k16.f32.bf16.bf16 {%0,%1,%2,%3}, %4, %5, p, 1, 1, 1, 0;}"
               : ACC4(d, 0) : "l"(da), "l"(db), "r"(sc));
}
DI void wg_rs8(float* d, uint32_t a0, uint32_t a1, uint32_t a2, uint32_t a3, uint64_t db, int sc) {
  asm volatile("{.reg .pred p; setp.ne.b32 p, %9, 0;\n"
               "wgmma.mma_async.sync.aligned.m64n8k16.f32.bf16.bf16 {%0,%1,%2,%3}, {%4,%5,%6,%7}, %8, p, 1, 1, 0;}"
               : ACC4(d, 0) : "r"(a0), "r"(a1), "r"(a2), "r"(a3), "l"(db), "r"(sc));
}
DI void mma16816(float* c, const uint32_t* a, uint32_t b0, uint32_t b1) {
  asm volatile("mma.sync.aligned.m16n8k16.row.col.f32.bf16.bf16.f32 {%0,%1,%2,%3}, {%4,%5,%6,%7}, {%8,%9}, {%0,%1,%2,%3};"
               : ACC4(c, 0) : "r"(a[0]), "r"(a[1]), "r"(a[2]), "r"(a[3]), "r"(b0), "r"(b1));
}
DI void wg_ss8(float* d, uint64_t da, uint64_t db, int sc) {
  asm volatile("{.reg .pred p; setp.ne.b32 p, %6, 0;\n"
               "wgmma.mma_async.sync.aligned.m64n8k16.f32.bf16.bf16 {%0,%1,%2,%3}, %4, %5, p, 1, 1, 1, 1;}"
               : ACC4(d, 0) : "l"(da), "l"(db), "r"(sc));
}
__device__ __align__(4096) uint4 g_xn[2 * NSEG * 10 * 256];
__device__ __align__(4096) uint4 g_oT[2 * NBLK * 96 * 1024];
constexpr int PART_RING = 96 * 256;
__device__ __align__(4096) uint4 g_part[4 * PART_RING];
#define P4 ~0u, ~0u, ~0u, ~0u
#define P16 P4, P4, P4, P4
#define P256 P16, P16, P16, P16, P16, P16, P16, P16, P16, P16, P16, P16, P16, P16, P16, P16
#define P2K P256, P256, P256, P256, P256, P256, P256, P256
#define P8K P2K, P2K, P2K, P2K
__device__ __align__(8192) uint32_t g_mem32[5 * 2 * 2 * 2048] = {P8K, P8K, P8K, P8K, P8K};
#define g_mem ((uint4*)g_mem32)
constexpr int C_XN = 0;
constexpr int C_O = C_XN + 2 * NBLK;
constexpr int C_HALF = C_O + 6 * 2 * NBLK;
constexpr int C_TOTAL = 512;
constexpr int CSTRIDE = 32;
__device__ __align__(4096) uint32_t g_cnt[C_TOTAL * CSTRIDE];
constexpr uint32_t XN_TARGET = 128;

#define TRACE(c, n, i, v)
#define SLOG(i)
#define PROF(i)
#define PROFA(c)
#define PROFV(i, v)

constexpr uint32_t SMEM0 = 1024;
constexpr uint32_t SM_WK = 0, SM_WO = 81920, SM_H = 163840, SM_QT = 215040, QSTR = 1056  , SM_KT = SM_QT + 5 * QSTR + 1024,
                   SM_SR = SM_KT + 5120  , SM_PROF = SM_SR + 5760, R_SMEM = 232448,
                   SM_RED = SM_QT + 1024, SM_BAR = SM_RED + 768;
constexpr uint32_t SM_P = SM_KT, SM_OB = SM_QT + 3200;
constexpr uint32_t B_HFULL = SM_BAR, B_HEMPTY = SM_BAR + 40, B_MTRY = SM_BAR + 80, B_W = SM_BAR + 112, B_SR = B_W + 32,
                   B_PMEM = B_SR + 24, B_PTOK = B_SR + 32, B_OB = B_SR + 40, B_OPD = B_SR + 48, B_RFREE = B_SR + 56,
                   B_GATE = B_SR + 64, B_PSUM = B_SR + 72, B_END = B_SR + 80, B_TOK = B_SR + 88,
                   B_OPI = B_SR + 96, B_OTOK = B_SR + 112, SM_TOPI = B_SR + 128, B_PACE = SM_TOPI + 8,
                   SM_RS = SM_QT + 2 * QSTR + 1024;
static_assert(B_PACE + 32 <= SM_QT + 2 * QSTR, "barriers must fit the unused q row group");

struct RParams {
  uint64_t dH, dHt, dWK, dWO, dQT, dKT, dP, dOB[6];
  const uint4* mem0;
  const uint32_t* x;
  int pf;
  int nslots, d3, pn, moff, ds, dh, dq;
  int d2[10], d1[8];
  uint32_t slot[2 * NSEG];
};
static void r_fill_desc(RParams& p) {
  p.dH = mkdesc(SMEM0 + SM_H, 128, 2048, 0);
  p.dHt = mkdesc(SMEM0 + SM_H + 2048, 128, 2048, 0);
  p.dWK = mkdesc(SMEM0 + SM_WK, 1024, 1024, 1);
  p.dWO = mkdesc(SMEM0 + SM_WO, 1024, 1024, 1);
  for (int i = 0; i < 6; i++) p.dOB[i] = mkdesc(SMEM0 + SM_OB + (i < 3 ? 0 : (i - 3) * 1024), 128, 128, 0);
  p.dQT = mkdesc(SMEM0 + SM_QT, 128, QSTR, 0);
  p.dKT = mkdesc(SMEM0 + SM_KT, 128, 1024, 0);
  p.dP = mkdesc(SMEM0 + SM_P, 128, 640, 0);
}
DI uint64_t dadd(uint64_t d, int bytes) {
  uint64_t r;
  asm volatile("add.u64 %0, %1, %2;" : "=l"(r) : "l"(d), "l"((long long)(bytes / 16)));
  return r;
}
template <int BYTES> DI void dstep(uint64_t& d) { asm volatile("add.u64 %0, %0, %1;" : "+l"(d) : "n"((long long)(BYTES / 16))); }
__host__ __device__ constexpr int hoff(int ks) { return (ks >> 3) * 10240 + (ks & 7) * 256; }

DI int opaque(int v) { asm volatile("" : "+r"(v)); return v; }
DI uint32_t pin(uint32_t v, int lane) { return __shfl_sync(~0u, v + (lane >> 5), lane); }
DI char* pin(char* p, int lane) { return (char*)__shfl_sync(~0u, (unsigned long long)p, lane); }
DI float blo(uint32_t w) { return __uint_as_float(w << 16); }
DI float bhi(uint32_t w) { return __uint_as_float(w & 0xffff0000u); }
#define RG0 232
#define RG1 216
#define RG2 40
#define RG3 24
DI void ldsm4t(uint32_t* r, uint32_t a) {
  asm volatile("ldmatrix.sync.aligned.m8n8.x4.trans.shared.b16 {%0,%1,%2,%3}, [%4];" : "=r"(r[0]), "=r"(r[1]), "=r"(r[2]), "=r"(r[3]) : "r"(a) : "memory");
}
DI void st_tagged(void* p, float a, float b, uint32_t keep, uint32_t tagbit) {
  asm volatile("{.reg .b32 t; cvt.rn.bf16x2.f32 t, %2, %1; lop3.b32 t, t, %3, %4, 0xea; st.relaxed.gpu.global.b32 [%0], t;}" ::"l"(p), "f"(a), "f"(b),
               "r"(keep), "r"(tagbit) : "memory");
}
DI uint32_t lop_bad(uint32_t a, uint32_t b, uint32_t m) { uint32_t d; asm("lop3.b32 %0, %1, %2, %3, 0x7e;" : "=r"(d) : "r"(a), "r"(b), "r"(m)); return d; }
DI uint32_t lop_or3(uint32_t a, uint32_t b, uint32_t c) { uint32_t d; asm("lop3.b32 %0, %1, %2, %3, 0xfe;" : "=r"(d) : "r"(a), "r"(b), "r"(c)); return d; }
DI uint32_t clk() { uint32_t t; asm volatile("mov.u32 %0, %%clock;" : "=r"(t)); return t; }
DI void spin(uint32_t cyc) { const uint32_t t0 = clk(); while (__any_sync(~0u, clk() - t0 < cyc)) {} }
template <int NL> DI float2 poll_sum(const uint32_t* src, uint32_t tag, uint32_t even, uint32_t& g) {
  uint32_t r[NL];
  while (true) {
#pragma unroll
    for (int i = 0; i < NL; i++) r[i] = ld_rlx(src + i * 32);
    uint32_t bad = lop_or3(lop_bad(r[0], r[1], tag), lop_bad(r[2], r[3], tag), lop_bad(r[4], r[5], tag));
    if (NL == 12) bad = lop_or3(bad, lop_bad(r[6], r[7], tag), lop_bad(r[8], r[9], tag));
    asm volatile("lop3.b32 %0, %0, %1, %2, 0xa8;" : "+r"(bad) : "r"(lop_bad(r[NL - 2], r[NL - 1], tag)), "r"(even));
    if (!__any_sync(~0u, bad)) break;
    g++;
  }
  float x[NL / 2], y[NL / 2];
#pragma unroll
  for (int i = 0; i < NL / 2; i++) { x[i] = blo(r[2 * i]) + blo(r[2 * i + 1]); y[i] = bhi(r[2 * i]) + bhi(r[2 * i + 1]); }
  float2 u = make_float2((x[0] + x[1]) + (x[2] + x[3]), (y[0] + y[1]) + (y[2] + y[3]));
  if (NL == 12) { u.x += x[4] + x[5]; u.y += y[4] + y[5]; }
  return u;
}

constexpr int PLANE = 16 * 40 * 32, MAXPL = 9;
__device__ __align__(4096) uint2 g_acc[(size_t)2 * NBLK * 2 * MAXPL * PLANE];
DI uint2* acc_planes(int lb, int d) { return g_acc + (size_t)((lb * 2 + d) * MAXPL) * PLANE; }
DI void ln_stats(const float4* v, uint32_t red, int warp, int lane, int bar, float& mean, float& rstd) {
  float s = 0.f;
#pragma unroll
  for (int i = 0; i < 5; i++) s += (v[i].x + v[i].y) + (v[i].z + v[i].w);
  s += __shfl_xor_sync(~0u, s, 1);
  s += __shfl_xor_sync(~0u, s, 2);
  s *= 1.f / 80;
  float q = 0.f;
#pragma unroll
  for (int i = 0; i < 5; i++) q += ((v[i].x - s) * (v[i].x - s) + (v[i].y - s) * (v[i].y - s)) + ((v[i].z - s) * (v[i].z - s) + (v[i].w - s) * (v[i].w - s));
  q += __shfl_xor_sync(~0u, q, 1);
  q += __shfl_xor_sync(~0u, q, 2);
  if ((lane & 3) == 0) asm volatile("st.shared.v2.f32 [%0], {%1,%2};" ::"r"(red + lane * 16 + warp * 8), "f"(s), "f"(q) : "memory");
  bar_sync(bar, 256);
  const uint4 t = lds128(red + lane * 16);
  const float m0 = __uint_as_float(t.x), m1 = __uint_as_float(t.z);
  mean = m0 + m1;
  mean += __shfl_xor_sync(~0u, mean, 1);
  mean += __shfl_xor_sync(~0u, mean, 2);
  mean *= 0.125f;
  q = __uint_as_float(t.y) + __uint_as_float(t.w) + 80.f * ((m0 - mean) * (m0 - mean) + (m1 - mean) * (m1 - mean));
  q += __shfl_xor_sync(~0u, q, 1);
  q += __shfl_xor_sync(~0u, q, 2);
  rstd = rsqrtf(q * (1.f / DM) + 1e-5f);
}
template <int SH, int STR> DI void store_img(uint32_t* dst, const float4* v, int warp, float mean, float rstd) {
#pragma unroll
  for (int i = 0; i < 5; i++) {
    const int U = 10 * warp + 2 * i;
    uint32_t* p = dst + (U >> SH) * STR + (U & ((1 << SH) - 1)) * 32;
    p[0] = pack2((v[i].x - mean) * rstd, (v[i].y - mean) * rstd);
    p[32] = pack2((v[i].z - mean) * rstd, (v[i].w - mean) * rstd);
  }
}
DI uint32_t* xn_row_group(int layer, int rg) { return (uint32_t*)(g_xn + (size_t)((layer * NSEG + (rg >> 2)) * 2560 + (rg & 3) * 128)); }

DI void first_ln(const uint32_t* a, int rg, uint32_t red, int warp, int lane, int bar) {
  float4 v[5];
#pragma unroll
  for (int i = 0; i < 5; i++) {
    v[i] = make_float4(blo(a[2 * i]), bhi(a[2 * i]), blo(a[2 * i + 1]), bhi(a[2 * i + 1]));
    acc_planes(rg >> 4, 0)[((rg & 15) * 40 + warp * 5 + i) * 32 + lane] = make_uint2(a[2 * i], a[2 * i + 1]);
  }
  float mean, rstd;
  ln_stats(v, red, warp, lane, bar, mean, rstd);
  store_img<4, 2048>(xn_row_group(0, rg) + lane, v, warp, mean, rstd);
}
#define QK_P0 32
#define QK_KB 0
struct QKOrder { int op[76]; };
__host__ __device__ constexpr QKOrder qk_order() {
  QKOrder o = {};
  int n = 0, k = 0, q = 0;
  for (; k < QK_P0; k++, q++) { o.op[n++] = 64 | k; o.op[n++] = q; }
  for (int i = 0; i < QK_KB; i++) o.op[n++] = 64 | k++;
  for (int i = 0; i < -QK_KB; i++) o.op[n++] = q++;
  const int nk = 40 - k, nq = 36 - q;
  for (int i = 0, dk = 0, dq = 0; i < nk + nq; i++) {
    if (dq * nk <= dk * nq + (QK_KB ? 0 : -nq) && dq < nq) { o.op[n++] = q++; dq++; } else if (dk < nk) { o.op[n++] = 64 | k++; dk++; } else { o.op[n++] = q++; dq++; }
  }
  return o;
}
__global__ void __launch_bounds__(512, 1)
r_kernel(const __grid_constant__ CUtensorMap mapWq, const __grid_constant__ CUtensorMap mapWk, const __grid_constant__ CUtensorMap mapWv,
         const __grid_constant__ CUtensorMap mapWo, const __grid_constant__ RParams prm) {
  const uint32_t sb = smem_base();
  const int wid = __shfl_sync(~0u, threadIdx.x >> 5, 0);
  const int lane0 = __shfl_sync(~0u, threadIdx.x & 31, threadIdx.x & 31);
  const int lane = lane0;
  const int warp = wid & 3, wg = wid >> 2;
  const uint32_t rank = blockIdx.x, head = blockIdx.y, cta = head * 3 + rank;
  const uint32_t peer1 = mapa(sb, rank == 2 ? 0 : rank + 1), peer2 = mapa(sb, rank == 0 ? 2 : rank - 1);
  const int nslots = prm.nslots;

  SLOG(0);
  if (threadIdx.x == 384) {
    if ((sb & 0x3FFFF) != SMEM0) __trap();
    for (int c = 0; c < 5; c++) { mbar_init(sb + B_HFULL + 8 * c, 2); mbar_init(sb + B_HEMPTY + 8 * c, c == 4 ? 8 : 4); }
    for (int c = 0; c < 11; c++) mbar_init(sb + B_MTRY + 8 * c, 1);
    mbar_init(sb + B_PTOK, rank == 0 ? 3 : 2); mbar_init(sb + B_OB, 5); mbar_init(sb + B_OPD, 4);
    mbar_init(sb + B_OPI, 1); mbar_init(sb + B_OPI + 8, 1); mbar_init(sb + B_RFREE, 1); mbar_init(sb + B_GATE, 1); mbar_init(sb + B_PMEM, 2); mbar_init(sb + B_PSUM, 2); mbar_init(sb + B_TOK, 5); mbar_init(sb + B_OTOK, 4); mbar_init(sb + B_OTOK + 8, 4); mbar_init(sb + B_END, 15);
    for (int c = 0; c < 4; c++) mbar_init(sb + B_PACE + 8 * c, 1);
    asm volatile("fence.mbarrier_init.release.cluster;" ::: "memory");
    fence_async_smem();
  }
  asm volatile("griddepcontrol.launch_dependents;");
  asm volatile("barrier.cluster.arrive.release.aligned;" ::: "memory");

  if (wg < 2) {
  {
    uint32_t xa[10];
    const uint32_t* src = prm.x + (size_t)(cta * 8 + (lane >> 2)) * (DM / 2) + wid * 40 + (lane & 3);
#pragma unroll
    for (int i = 0; i < 10; i++) xa[i] = __ldg(src + i * 4);
    asm volatile("barrier.cluster.wait.acquire.aligned;" ::: "memory");
    first_ln(xa, cta, sb + SM_SR, wid, lane, 8);
    bar_arrive(10, 288);
  }
  if (wg == 0) {
    asm volatile("setmaxnreg.inc.sync.aligned.u32 %0;" ::"n"(RG0));
    uint32_t wq[160];
    SLOG(1);
    mbar_wait(sb + B_W, 0);
    SLOG(2);
    {
      const uint32_t ld_off = ((lane >> 4) * 8 + (lane & 7)) * 128 + (((2 * warp + ((lane >> 3) & 1)) ^ (lane & 7)) << 4);
#pragma unroll
      for (int ks = 0; ks < 40; ks++) ldsm4t(wq + 4 * ks, sb + SM_WO + ks * 2048 + ld_off);
    }
    fence_async_smem();
    bar_arrive(5, 160);
    mbar_wait(sb + B_W + 16, 0);
    SLOG(3);
    const uint32_t st_addr = pin(sb + SM_QT + (lane >> 4) * 1024 + (2 * warp + ((lane >> 3) & 1)) * 128 + (lane & 7) * 16, lane);
    const uint32_t sq_addr = pin(sb + SM_QT + (2 + (lane & 3)) * QSTR + warp * 256 + (lane >> 2) * 16, lane);
    const uint32_t to_lo = warp == 0 ? peer1 : mapa(sb, warp == 2 ? 2 : 0), to_hi = warp == 0 ? peer2 : mapa(sb, warp == 1 ? 1 : 0);
    const uint32_t sr_off = SM_SR + warp * 1920 + rank * 640, sr_bar = B_SR + warp * 8;
    const uint32_t sa0 = pin(to_lo + sr_off + lane * 16, lane), sb0 = pin(to_lo + sr_bar, lane), sa1 = pin(to_lo + sr_off + 512 + lane * 4, lane), sb1 = pin(sb0, lane);
    const uint32_t sa2 = pin(to_hi + sr_off + lane * 16, lane), sb2 = pin(to_hi + sr_bar, lane), sa3 = pin(to_hi + sr_off + 512 + lane * 4, lane), sb3 = pin(sb2, lane);
    uint32_t nsolo = 0;
#pragma unroll 1
    for (int n = 0; n < nslots; n++) {
      const uint32_t par = n & 1;
      PROFA(warp == PW);
      const bool alt = prm.slot[n] & 128;
      auto next = [&](uint64_t& d, int ks) { if ((ks & 7) == 7) dstep<10240 - 7 * 256>(d); else dstep<256>(d); };
      auto store_k = [&](const float* ka) {
        stsm2(st_addr + (SM_KT - SM_QT), pack2(ka[0], ka[1]), pack2(ka[2], ka[3]));
        stsm4(st_addr + (SM_KT - SM_QT) + 1024, pack2(ka[4], ka[5]), pack2(ka[6], ka[7]), pack2(ka[8], ka[9]), pack2(ka[10], ka[11]));
        stsm4(st_addr + (SM_KT - SM_QT) + 3072, pack2(ka[12], ka[13]), pack2(ka[14], ka[15]), pack2(ka[16], ka[17]), pack2(ka[18], ka[19]));
      };
      auto store_qt = [&](const float* q) {
        sts128(sq_addr, make_uint4(pack2(q[0], q[1]), pack2(q[4], q[5]), pack2(q[8], q[9]), pack2(q[12], q[13])));
        sts128(sq_addr + 128, make_uint4(pack2(q[2], q[3]), pack2(q[6], q[7]), pack2(q[10], q[11]), pack2(q[14], q[15])));
      };
      if (n > 0 && ((prm.slot[n] >> 8) & 255) == n) {
        {
          float qt[16];
          uint64_t rh = prm.dHt;
          mbar_wait(sb + B_OPI + (par ^ 1) * 8, ((n - 1) >> 1) & 1);
          mbar_wait(sb + B_GATE, 1);
          spin(prm.dq);
          mbar_wait(sb + B_TOK, nsolo++ & 1);
          float kt[16];
          uint64_t rk = prm.dWK;
          wg_fence();
#pragma unroll
          for (int ks = 0; ks < 40; ks++) {
            wg_ss32k(kt, rk, rh, ks != 0);
            wg_rs32(qt, wq[4 * ks], wq[4 * ks + 1], wq[4 * ks + 2], wq[4 * ks + 3], rh, ks != 0);
            if (ks < 39) { dstep<2048>(rk); next(rh, ks); }
          }
          wg_commit();
          mbar_wait(sb + B_OPD, par ^ 1);
          wg_wait<0>();
          reg_fence<16>(qt); reg_fence<16>(kt);
          store_qt(qt);
          stsm4(st_addr + (SM_KT - SM_QT) + 1024, pack2(kt[0], kt[1]), pack2(kt[2], kt[3]), pack2(kt[4], kt[5]), pack2(kt[6], kt[7]));
          stsm4(st_addr + (SM_KT - SM_QT) + 3072, pack2(kt[8], kt[9]), pack2(kt[10], kt[11]), pack2(kt[12], kt[13]), pack2(kt[14], kt[15]));
        }
        float qm[4], km[4];
        uint64_t rk = prm.dWK, rh = prm.dH;
        bool ok = false;
#pragma unroll
        for (int g = 0; g < 20; g++) {
          if ((g & 3) == 0 && !ok) mbar_wait(sb + B_HFULL + 2 * g, par);
          if (g == 0) PROF(0);
          if ((g & 3) == 3 && g < 19) ok = mbar_test(sb + B_HFULL + 2 * (g + 1), par);
          if ((g & 3) == 0) wg_fence();
#pragma unroll
          for (int ks = 2 * g; ks < 2 * g + 2; ks++) {
            wg_ss8k(km, rk, rh, ks != 0);
            wg_rs8(qm, wq[4 * ks], wq[4 * ks + 1], wq[4 * ks + 2], wq[4 * ks + 3], rh, ks != 0);
            if (ks < 39) { dstep<2048>(rk); next(rh, ks); }
          }
          if (g == 18) wg_commit();
        }
        wg_commit();
        wg_wait<1>();
        bar_arrive(2, 256);
        wg_wait<0>();
        reg_fence<4>(qm); reg_fence<4>(km);
        PROF(9);
        stsm2(st_addr + (SM_KT - SM_QT), pack2(km[0], km[1]), pack2(km[2], km[3]));
        stsm2(st_addr, pack2(qm[0], qm[1]), pack2(qm[2], qm[3]));
      } else {
      float qa[20], ka[20];
      uint64_t rk = prm.dWK, rh = prm.dH, rq;
      auto K = [&](int ks) { wg_ss40<1, 0>(ka, rk, rh, ks != 0); };
      auto Q = [&](int ks, uint64_t db) { wg_rs40(qa, wq[4 * ks], wq[4 * ks + 1], wq[4 * ks + 2], wq[4 * ks + 3], db, ks != 0); };
      constexpr QKOrder ord = qk_order();
      auto first = [&](int g, int c) { for (int i = 0; i < 76; i++) if ((ord.op[i] & 63) >> 3 == c) return i >> 2 == g; return false; };
      bool ok = true;
      mbar_wait(sb + B_HFULL, par);
#pragma unroll
      for (int g = 0; g < 19; g++) {
        if (!ok) {
#pragma unroll
          for (int c = 1; c < 5; c++) if (first(g, c)) mbar_wait(sb + B_HFULL + 8 * c, par);
          mbar_wait(sb + B_GATE, 1);
        }
        if (g == 0) PROF(0);
        if (g < 18) ok = mbar_test(sb + B_GATE, 1);
#pragma unroll
        for (int c = 1; c < 5; c++) if (first(g + 1, c)) ok &= mbar_test(sb + B_HFULL + 8 * c, par);
        wg_fence();
#pragma unroll
        for (int i = 4 * g; i < 4 * g + 4; i++) {
          const int ks = ord.op[i] & 63;
          if (i < 2 * QK_P0) {
            if (ord.op[i] & 64) K(ks);
            else { Q(ks, rh); dstep<2048>(rk); next(rh, ks); if (i == 2 * QK_P0 - 1) rq = rh; }
          } else if (ord.op[i] & 64) { K(ks); if (ks < 39) { dstep<2048>(rk); next(rh, ks); } }
          else { Q(ks, rq); next(rq, ks); }
        }
        if (g == 17) wg_commit();
      }
      wg_commit();
#pragma unroll
      for (int ks = 36; ks < 40; ks++) { Q(ks, rq); if (ks < 39) dstep<256>(rq); }
      wg_commit();
      wg_wait<2>();
      if (alt) bar_arrive(2, 256);
      mbar_wait(sb + B_OPD, par ^ 1);
      wg_wait<1>();
      if (!alt) bar_arrive(2, 256);
      reg_fence<20>(ka);
      store_k(ka);
      wg_wait<0>();
      reg_fence<20>(qa);
      PROF(9);
      stsm2(st_addr, pack2(qa[0], qa[1]), pack2(qa[2], qa[3]));
      store_qt(qa + 4);
      }
      mbar_arrive_if(lane == 0, sb + B_HEMPTY + 32);
      fence_async_smem();
      bar_sync(1, 128);
      PROF(1);
      float qa[20];
      wg_fence();
#pragma unroll
      for (int k = 0; k < 4; k++) wg_ss40<1, 1>(qa, dadd(prm.dQT, k * 256), dadd(prm.dKT, k * 256), k != 0);
      wg_commit();
      bar_arrive(7, 256);
      wg_wait<0>();
      reg_fence<20>(qa);
      PROF(3);
      if (warp < 3) {
        uint32_t p[5];
#pragma unroll
        for (int j = 0; j < 5; j++) p[j] = pack2(qa[4 * j], qa[4 * j + 1]);
        if (warp == 0) {
          st_async4(sa0, p[0], p[1], p[2], p[3], sb0);
          st_async4(sa2, p[0], p[1], p[2], p[3], sb2);
          st_async1(sa1, p[4], sb1);
          st_async1(sa3, p[4], sb3);
          sts128(sb + sr_off + lane * 16, make_uint4(p[0], p[1], p[2], p[3]));
          sts32(sb + sr_off + 512 + lane * 4, p[4]);
          __syncwarp();
          mbar_expect_if(lane == 0, sb + B_SR, 1280);
        } else {
          uint32_t h[5];
#pragma unroll
          for (int j = 0; j < 5; j++) h[j] = pack2(qa[4 * j + 2], qa[4 * j + 3]);
          spin(prm.d3);
          st_async4(sa0, p[0], p[1], p[2], p[3], sb0);
          st_async4(sa2, h[0], h[1], h[2], h[3], sb2);
          st_async1(sa1, p[4], sb1);
          st_async1(sa3, h[4], sb3);
        }
      }
    }
  } else {
    asm volatile("setmaxnreg.inc.sync.aligned.u32 %0;" ::"n"(RG1));
    uint32_t wv[160];
    mbar_wait(sb + B_W + 8, 0);
    SLOG(4);
    {
      const uint32_t ld_off = ((lane >> 4) * 8 + (lane & 7)) * 128 + (((2 * warp + ((lane >> 3) & 1)) ^ (lane & 7)) << 4);
#pragma unroll
      for (int ks = 0; ks < 40; ks++) ldsm4t(wv + 4 * ks, sb + SM_WO + ks * 2048 + ld_off);
    }
    fence_async_smem();
    bar_arrive(6, 160);
    const uint64_t dH = prm.dH;
    uint32_t op[8];
    const uint32_t ob_off = SM_OB + (4 * rank + warp) * 256 + lane * 4;
    const uint32_t oa0 = pin(peer1 + ob_off, lane), ob0 = pin(peer1 + B_OB, lane), oa1 = pin(peer2 + ob_off, lane), ob1 = pin(peer2 + B_OB, lane);
    const uint32_t oa2 = pin(oa0 + 128, lane), ob2 = pin(ob0, lane), oa3 = pin(oa1 + 128, lane), ob3 = pin(ob1, lane);
    const uint32_t o_loc = pin(sb + ob_off, lane), rs_addr = pin(sb + SM_RS + (lane & 3) * 8, lane);
    const uint32_t tok_off = pin((cta * 1024 + 64 * warp + (lane ^ (lane >> 3))) * 16, lane), keep = pin((lane & 1) ? ~0u : ~1u, lane);
    const uint32_t pb_off = pin((8 * rank + 2 * warp) * 4096 + head * 128 + lane * 4, lane);
    const uint32_t ph_off = pin(72 * 4096 + 2 * warp * 12288 + cta * 64 + (lane & 2) * 3072 + (lane >> 2) * 8 + (lane & 1) * 4, lane);
    auto store_tok = [&](int m, int lane) {
      const uint32_t ls = prm.slot[m] & 127, sig = prm.slot[m] >> 16;
      uint4* dst = (uint4*)((char*)(g_oT + (size_t)((ls >> 2) * (96 * 1024) + (ls & 3) * 256)) + tok_off);
      dst[0] = make_uint4(op[0], op[1], op[2], op[3]);
      dst[32] = make_uint4(op[4], op[5], op[6], op[7]);
      __syncwarp();
      mbar_arrive_if(sig && lane == 0, sb + B_OTOK + (ls >> 6) * 8);
    };
#pragma unroll 1
    for (int n = 0; n < nslots; n++) {
      const uint32_t par = n & 1;
      const int lane = opaque(lane0);
      PROFA(warp == PW);
      float va[20];
      const bool alt = prm.slot[n] & 128;
      mbar_expect_if(warp == 0 && lane == 0, sb + B_PTOK, rank == 0 ? 1280 : 1920);
      bar_sync(2, 256);
#pragma unroll
      for (int g = 0; g < 10; g++) {
        wg_fence();
#pragma unroll
        for (int ks = 4 * g; ks < 4 * g + 4; ks++) { wg_rs40(va, wv[4 * ks], wv[4 * ks + 1], wv[4 * ks + 2], wv[4 * ks + 3], dadd(dH, hoff(ks)), ks != 0); }
        wg_commit();
        if (g >= 2 && !(g & 1)) {
          wg_wait<1>();
          if (lane == 0) mbar_arrive(sb + B_HEMPTY + 8 * (g / 2 - 1));
        }
        if (g == 1 ? !alt : g == 2 && alt) bar_sync(7, 256);
      }
      wg_wait<0>();
      reg_fence<20>(va);
      if (lane == 0) mbar_arrive(sb + B_HEMPTY + 32);
      PROF(10);
      uint32_t vf[10];
#pragma unroll
      for (int j = 0; j < 10; j++) {
        const int i = (j + 4) % 10;
        asm volatile("cvt.rn.bf16x2.f32 %0, %1, %2;" : "=r"(vf[i]) : "f"(va[2 * i + 1]), "f"(va[2 * i]));
        if (j == 5) mbar_wait(sb + B_W + 8, 0);
      }
      uint32_t z0, z1;
      asm volatile("shr.u32 %0, %2, 5; shr.u32 %1, %2, 6;" : "=r"(z0), "=r"(z1) : "r"(lane));
      const uint32_t info = prm.slot[n];
      const uint32_t tagbit = ~(info >> 1) & ~keep;
      char* const ring = (char*)(g_part + (size_t)((((info >> 5) & 2) + (info & 1)) * PART_RING));
      char* const pb = pin(ring + pb_off, lane);
      char* const ph = ring + ph_off;
      mbar_wait(sb + B_PMEM, par);
      float om[4];
      wg_fence();
      wg_rs8(om, vf[0], vf[1], vf[2], vf[3], prm.dP, 0);
      wg_rs8(om, vf[4], vf[5], vf[6], vf[7], dadd(prm.dP, 256), 1);
      wg_rs8(om, vf[8], vf[9], z0, z1, dadd(prm.dP, 512 - (128 << 16)), 1);
      wg_commit();
      {
        wg_wait<0>();
        reg_fence<4>(om);
        const uint32_t b0 = pack2(om[0], om[1]), b1 = pack2(om[2], om[3]);
        st_async1(oa0, b0, ob0);
        st_async1(oa1, b0, ob1);
        st_async1(oa2, b1, ob2);
        st_async1(oa3, b1, ob3);
        sts32(o_loc, b0);
        sts32(o_loc + 128, b1);
        fence_async_smem();
        __syncwarp();
        mbar_arrive_if(lane == 0, sb + B_OB);
      }
      PROF(11);
      {
        float c[8];
        mbar_wait(sb + B_PSUM, par);
        const uint2 rs = lds64(rs_addr);
        const float r0 = __uint_as_float(rs.x), r1 = __uint_as_float(rs.y);
        if (n == 0) { SLOG(5); mbar_wait(sb + B_W + 24, 0); SLOG(6); }
        mbar_wait(sb + B_OB, par);
        asm volatile("fence.proxy.async::generic.acquire.sync_restrict::shared::cluster.cluster;" ::: "memory");
        PROF(16);
        if ((info & 63) == NSEG - 1) {
          mbar_wait(sb + B_OPI + par * 8, (n >> 1) & 1);
          mbar_arrive_if(warp == 3 && lane == 0, sb + B_GATE);
#pragma unroll
          for (int p = 0; p < 6; p++) st_rlx1(pb + (p >> 1) * 98304 + (p & 1) * 4096, tagbit);
          st_rlx1(ph, tagbit);
          st_rlx1(ph + 12288, tagbit);
        } else {
#pragma unroll
        for (int p = 0; p < 4; p++) {
          float* const cur = c + 4 * (p & 1);
          float* const prv = c + 4 * (~p & 1);
          if (p == 2) mbar_wait(sb + B_OPI + par * 8, (n >> 1) & 1);
          wg_fence();
#pragma unroll
          for (int ks = 0; ks < (p < 3 ? 12 : 4); ks++) {
            wg_ss8(cur, dadd(prm.dWO, p * 24576 + ks * 2048), dadd(prm.dOB[p < 3 ? p : 3 + rank], ks * 256), ks != 0);
            if (p == 3 && ks == 3) mbar_arrive_if(warp == 3 && lane == 0, sb + B_GATE);
            if (p > 0 && ks == 3) {
              wg_commit();
              wg_wait<1>();
              reg_fence<4>(prv);
              st_tagged(pb + (p - 1) * 98304, prv[0] * r0, prv[1] * r1, keep, tagbit);
              st_tagged(pb + (p - 1) * 98304 + 4096, prv[2] * r0, prv[3] * r1, keep, tagbit);
            }
          }
          if (p < 3) wg_commit();
        }
        wg_wait<0>();
        reg_fence<4>(c + 4);
        st_tagged(ph, c[4] * r0, c[5] * r1, keep, tagbit);
        st_tagged(ph + 12288, c[6] * r0, c[7] * r1, keep, tagbit);
        }
        PROF(17);
      }
      mbar_wait(sb + B_PTOK, par);
      PROF(12);
      {
        float ot[16];
        wg_fence();
        wg_rs32(ot, vf[0], vf[1], vf[2], vf[3], dadd(prm.dP, 640), 0);
        wg_rs32(ot, vf[4], vf[5], vf[6], vf[7], dadd(prm.dP, 640 + 256), 1);
        wg_rs32(ot, vf[8], vf[9], z0, z1, dadd(prm.dP, 640 + 512 - (128 << 16)), 1);
        wg_commit();
        wg_wait<0>();
        reg_fence<16>(ot);
#pragma unroll
        for (int i = 0; i < 8; i++) op[(i & 1) * 4 + (i >> 1)] = pack2(ot[2 * i], ot[2 * i + 1]);
      }
      if (lane == 0) mbar_arrive(sb + B_OPD);
      PROF(13);
      if (info & 128) spin(prm.ds);
      store_tok(n, lane);
    }
  }
  } else if (wg == 2) {
    asm volatile("setmaxnreg.dec.sync.aligned.u32 %0;" ::"n"(RG2));
    asm volatile("barrier.cluster.wait.acquire.aligned;" ::: "memory");
    if (warp == 1) {
      const uint32_t depth = prm.pf;
#pragma unroll 1
      for (uint32_t i = 0; i < 20 + depth; i++) {
        if (i >= depth) {
          const uint32_t j = i - depth;
          mbar_wait_wd(sb + B_PACE + 8 * (j & 3), (j >> 2) & 1);
          if (j % 5 == 4) mbar_arrive_if(lane == 0 && (j != 14 || depth == 1), sb + B_W + (j == 4 ? 0 : j == 9 ? 16 : j == 14 ? 8 : 24));
        }
        if (i >= 20) continue;
        const uint32_t m = i / 5, k = i % 5, bar = sb + B_PACE + 8 * (i & 3);
        if (i == 10) bar_sync(5, 160);
        if (i == 15) {
#pragma unroll 1
          for (uint32_t j = 16 - depth; j < 15; j++) mbar_wait_wd(sb + B_PACE + 8 * (j & 3), (j >> 2) & 1);
          mbar_arrive_if(lane == 0 && depth > 1, sb + B_W + 8);
          bar_sync(6, 160);
        }
        if (elect_one()) {
          mbar_expect(bar, 16384);
          if (m < 3) tma_2d(sb + (m == 1 ? SM_WK : SM_WO) + k * 16384, m == 0 ? &mapWq : m == 1 ? &mapWk : &mapWv, cta * 64, k * 128, bar);
          else
            for (uint32_t q = 2 * k; q < 2 * k + 2; q++)
              tma_2d(sb + SM_WO + q * 8192, &mapWo, q < 9 ? (q / 3 * 3 + rank) * 64 : 576, head * DH + (q < 9 ? q % 3 : rank) * 64, bar);
        }
      }
    }
    if (warp == 2 && cta < 80 && lane < 16)
      g_mem[(cta >> 4) * 2048 + (lane >> 3) * 1024 + prm.moff + (cta & 15) * 8 + (lane & 7)] = prm.mem0[(lane & 7) * 80 + cta];
    if (warp == 3) {
      bar_sync(10, 288);
      if (lane == 0) red_rel(&g_cnt[(C_XN + (cta >> 4)) * CSTRIDE], 8);
    }
    const uint32_t grp = warp == 1 ? 1 + rank : 4 - (rank >> 1);
    constexpr float SC = 0.07216878364870322f * 1.4426950408889634f;
    const bool split = cta >= 72;
    const uint32_t wd = split ? 72 * 16 + cta * 16 : cta * 32;
    const uint32_t src_off = pin(split ? 72 * 4096 + (cta - 72) * 6144 + warp * 1536 + (lane & 2) * 32 + (lane >> 2) * 8 + (lane & 1) * 4 : cta * 4096 + warp * 1024 + lane * 4, lane);
    const uint32_t dst_off = pin(((wd >> 9) * 8192 + prm.moff * 4 + (wd & 511) + lane) * 4, lane);
    const uint32_t red = pin(sb + SM_RED + (warp < 2 ? 0 : (warp - 1) * 256) + lane * 8, lane);
    const uint32_t fl = (warp & 2) * 8 + (lane >> 3) * 4 + (lane & 3), hf = lane & 4;
    const uint32_t s0 = pin(sb + SM_SR + fl * 16 + hf * 2, lane), s1 = pin(sb + fl * 4, lane), pd = pin(s1 + hf * 64, lane);
    const uint32_t even = pin(~lane & 1, lane);
    uint32_t nred = 0;
    const uint32_t arm = pin(warp == 0 && (lane == 5 || ((lane == 1 || lane == 2) && lane + rank != 3)) ? sb + B_SR + lane * 8 : 0, lane);
#pragma unroll 1
    for (int n = 0; n < nslots; n++) {
      const uint32_t par = n & 1;
      const int lane = opaque(lane0);
      PROFA(warp == PW2);
      const uint32_t info = prm.slot[n], s = info & 63, l = (info >> 6) & 1;
      {
        mbar_expect_if(arm, arm, lane == 5 ? 2048 : 1920);
        if (warp == 0 || warp == 3) {
          mbar_wait(sb + B_SR, par);
          PROF(4);
          const uint2 a0 = lds64(s0), a1 = lds64(s0 + 640), a2 = lds64(s0 + 1280);
          const uint32_t b0 = lds32(s1 + SM_SR + 512), b1 = lds32(s1 + SM_SR + 1152), b2 = lds32(s1 + SM_SR + 1792);
          float v[6];
          v[0] = blo(a0.x) + blo(a1.x) + blo(a2.x); v[1] = bhi(a0.x) + bhi(a1.x) + bhi(a2.x);
          v[2] = blo(a0.y) + blo(a1.y) + blo(a2.y); v[3] = bhi(a0.y) + bhi(a1.y) + bhi(a2.y);
          v[4] = blo(b0) + blo(b1) + blo(b2); v[5] = bhi(b0) + bhi(b1) + bhi(b2);
          float m = fmaxf(fmaxf(v[0], v[1]), fmaxf(v[2], v[3]));
          m = fmaxf(fmaxf(m, __shfl_xor_sync(~0u, m, 4)), fmaxf(v[4], v[5]));
          {
            const float m1 = __shfl_xor_sync(~0u, m, 1), m2 = __shfl_xor_sync(~0u, m, 2), m3 = __shfl_xor_sync(~0u, m, 3);
            m = fmaxf(fmaxf(m, m1), fmaxf(m2, m3));
          }
          const float ms = -m * SC;
#pragma unroll
          for (int i = 0; i < 6; i++) v[i] = ex2(fmaf(v[i], SC, ms));
          float sum = (v[0] + v[1]) + (v[2] + v[3]);
          const float so = __shfl_xor_sync(~0u, sum, 4);
          sts32(pd + SM_P, pack2(v[0], v[1]));
          sts32(pd + SM_P + 128, pack2(v[2], v[3]));
          sts32(s1 + SM_P + 512, pack2(v[4], v[5]));
          fence_async_smem();
          __syncwarp();
          mbar_arrive_if(lane == 0, sb + B_PMEM);
          PROF(5);
          sum += so + (v[4] + v[5]);
          {
            const float t1 = __shfl_xor_sync(~0u, sum, 1), t2 = __shfl_xor_sync(~0u, sum, 2), t3 = __shfl_xor_sync(~0u, sum, 3);
            sum = (sum + t1) + (t2 + t3);
          }
          float r;
          asm("rcp.approx.ftz.f32 %0, %1;" : "=f"(r) : "f"(sum));
          sts32(sb + SM_RS + (warp & 2) * 8 + (lane >> 3) * 4, __float_as_uint(r));
          __syncwarp();
          mbar_arrive_if(lane == 0, sb + B_PSUM);
        } else {
          if (warp + rank != 3) {
            const uint32_t src = sb + SM_SR + warp * 1920;
            mbar_wait(sb + B_SR + warp * 8, par);
            const uint4 a0 = lds128(src + lane * 16), a1 = lds128(src + 640 + lane * 16), a2 = lds128(src + 1280 + lane * 16);
            const uint32_t b0 = lds32(src + 512 + lane * 4), b1 = lds32(src + 1152 + lane * 4), b2 = lds32(src + 1792 + lane * 4);
            float v[10];
            v[0] = blo(a0.x) + blo(a1.x) + blo(a2.x); v[1] = bhi(a0.x) + bhi(a1.x) + bhi(a2.x);
            v[2] = blo(a0.y) + blo(a1.y) + blo(a2.y); v[3] = bhi(a0.y) + bhi(a1.y) + bhi(a2.y);
            v[4] = blo(a0.z) + blo(a1.z) + blo(a2.z); v[5] = bhi(a0.z) + bhi(a1.z) + bhi(a2.z);
            v[6] = blo(a0.w) + blo(a1.w) + blo(a2.w); v[7] = bhi(a0.w) + bhi(a1.w) + bhi(a2.w);
            v[8] = blo(b0) + blo(b1) + blo(b2); v[9] = bhi(b0) + bhi(b1) + bhi(b2);
            {
              const int lim = 6 + 2 * grp + (lane & 24) + ((lane >> 2) & 1) - 2 * (lane & 3);
#pragma unroll
              for (int i = 2; i < 10; i++) if ((i >> 1) * 8 + (i & 1) > lim) v[i] = -INFINITY;
            }
            float m = fmaxf(fmaxf(fmaxf(v[0], v[1]), fmaxf(v[2], v[3])), fmaxf(fmaxf(v[4], v[5]), fmaxf(v[6], v[7])));
            m = fmaxf(m, fmaxf(v[8], v[9]));
            {
              const float m1 = __shfl_xor_sync(~0u, m, 1), m2 = __shfl_xor_sync(~0u, m, 2), m3 = __shfl_xor_sync(~0u, m, 3);
              m = fmaxf(fmaxf(m, m1), fmaxf(m2, m3));
            }
            const float ms = -m * SC;
#pragma unroll
            for (int i = 0; i < 10; i++) v[i] = ex2(fmaf(v[i], SC, ms));
            float sum = ((v[0] + v[1]) + (v[2] + v[3])) + ((v[4] + v[5]) + (v[6] + v[7])) + (v[8] + v[9]);
            {
              const float s1 = __shfl_xor_sync(~0u, sum, 1), s2 = __shfl_xor_sync(~0u, sum, 2), s3 = __shfl_xor_sync(~0u, sum, 3);
              sum = (sum + s1) + (s2 + s3);
            }
            float r;
            asm("rcp.approx.ftz.f32 %0, %1;" : "=f"(r) : "f"(sum));
            {
              const uint32_t row = SM_P + grp * 640;
#pragma unroll
              for (int j = 0; j < 5; j++) sts32(sb + row + j * 128 + lane * 4, pack2(v[2 * j] * r, v[2 * j + 1] * r));
              fence_async_smem();
              __syncwarp();
              mbar_arrive_if(lane == 0, sb + B_PTOK);
              if (elect_one()) {
                bulk_s2s(peer1 + row, sb + row, 640, peer1 + B_PTOK);
                bulk_s2s(peer2 + row, sb + row, 640, peer2 + B_PTOK);
              }
            }
          }
        }
      }
      const uint32_t* const src = (const uint32_t*)((char*)(g_part + (size_t)((l * 2 + (s & 1)) * PART_RING)) + src_off);
      uint32_t* const dst = (uint32_t*)pin((char*)(g_mem + l * 1024 + (~s & 1) * 512) + dst_off, lane);
      {
        const uint32_t d1 = prm.d1[cta / 24 + ((info >> 5) & 4)];
        if (warp == 3) {
          mbar_wait(sb + B_OB, par);
          mbar_arrive_if(lane == 0, sb + B_GATE);
          sts32(sb + SM_TOPI + par * 4, clk());
          __syncwarp();
          mbar_arrive_if(lane == 0, sb + B_OPI + par * 8);
          TRACE(true, n, 0, gtl());
        }
        const bool reduce = cta < 88 && s != NSEG - 1;
        if (reduce || warp == 0) mbar_wait(sb + B_OPI + par * 8, (n >> 1) & 1);
        if (!reduce) continue;
        mbar_wait(sb + B_RFREE, (nred++ & 1) ^ 1);
        mbar_wait(sb + B_GATE, 1);
        if (d1) spin(d1);
      }
      {
        uint32_t g = 0;
        float2 u;
        PROF(14);
        if (!split) {
          u = poll_sum<8>(src, ~(s >> 1), even, g);
        } else {
          u = poll_sum<12>(src, ~(s >> 1), even, g);
          u.x += __shfl_xor_sync(~0u, u.x, 2);
          u.y += __shfl_xor_sync(~0u, u.y, 2);
        }
        PROF(18);
        if (warp != 1) {
          asm volatile("st.shared.v2.f32 [%0], {%1,%2};" ::"r"(red), "f"(u.x), "f"(u.y) : "memory");
          bar_arrive(3, 128);
        } else {
          bar_sync(3, 128);
          const uint2 o0 = lds64(red), o1 = lds64(red + 256), o2 = lds64(red + 512);
          const uint32_t w = movm(pack2((u.x + __uint_as_float(o0.x)) + (__uint_as_float(o1.x) + __uint_as_float(o2.x)),
                                        (u.y + __uint_as_float(o0.y)) + (__uint_as_float(o1.y) + __uint_as_float(o2.y))));
          if (!split || lane < 16) {
            st_rlx1(dst, w);
            st_rlx1(dst + ((s & 1) ? 2048 : -2048), ~0u);
          }
          mbar_arrive_if(lane == 0, sb + B_RFREE);
        }
        PROF(19);
        PROFV(2, g);
        TRACE(warp == 1, n, 1, gtl());
        TRACE(g, n, 2, g);
      }
    }
  } else {
    asm volatile("setmaxnreg.dec.sync.aligned.u32 %0;" ::"n"(RG3));
    asm volatile("barrier.cluster.wait.acquire.aligned;" ::: "memory");
    const uint32_t chk = lane * 32 + ((lane >> 2) << 2);
    const uint32_t bar = sb + B_MTRY + 8 * warp;
    uint32_t mph = 0, waited = 0, pub = 0, pph = 0, nsolo = 0;
    auto publish = [&](uint32_t upto) {
#pragma unroll 1
      for (; pub < upto; pub++) {
        const uint32_t e = prm.slot[pub], l = (e >> 6) & 1;
        if (warp == 3 && (e >> 16)) {
          mbar_wait_wd(sb + B_OTOK + l * 8, (pph >> l) & 1);
          pph ^= 1 << l;
          if (elect_one()) red_rel(&g_cnt[(e >> 16) * CSTRIDE], 1);
        }
      }
    };
#pragma unroll 1
    for (int m = 0; m < nslots; m++) {
      const uint32_t info = prm.slot[m], prod = (info >> 8) & 255, ls = info & 127;
      uint32_t g = 0;
#pragma unroll 1
      for (; waited < prod && waited + 1 < m; waited++) mbar_wait_wd(sb + B_OPI + (waited & 1) * 8, (waited >> 1) & 1);
      uint32_t t0 = lds32(sb + SM_TOPI + (~waited & 1) * 4);
      publish(waited);
      if ((ls & 3) == 0) {
        while (__any_sync(~0u, ld_acq(&g_cnt[(C_XN + (ls >> 2)) * CSTRIDE]) < XN_TARGET)) guard(g);
        fence_async_global();
      }
#pragma unroll 1
      for (uint32_t c = warp; c < 5; c += 4) {
        const uint32_t dst = sb + SM_H + c * 10240, full = sb + B_HFULL + 8 * c;
        const uint4* src = g_mem + (c * 2048 + (ls >> 6) * 1024 + (ls & 1) * 512 + prm.moff);
        const uint32_t d = prod ? prm.d2[(m - prod) * 5 + c] : 0;
        const uint4* tok = g_xn + (size_t)(ls * 2560 + c * 512);
        const uint32_t pp = (m & 1) ^ 1;
        const bool single = waited < prod;
        mbar_wait_wd(full, pp);
        const bool solo = m > 0 && prod == m;
        const uint32_t tokb = solo ? sb + B_TOK : full;
        if (solo && c < 4) mbar_wait_wd(tokb, (nsolo++ & 1) ^ 1);
        mbar_expect_if(lane < 2 && !(solo && c == 4 && lane == 0), lane ? bar : tokb, lane ? 2048 : 8192);
        if (!single) while (__any_sync(~0u, clk() - t0 < d)) {}
        if (c >= 2) mbar_wait_wd(sb + B_HEMPTY + 8 * c, pp);
        mbar_wait_wd(sb + (c < 2 ? B_HEMPTY + 8 * c : c == 2 && !single ? B_PMEM : B_OB), pp);
        if ((c != 2 || single) && !(solo && c == 4)) { if (elect_one()) bulk_g2s(dst + 2048, tok, 8192, tokb); }
        if (single) {
          mbar_wait_wd(sb + B_OPI + (waited & 1) * 8, (waited >> 1) & 1);
          waited++;
          t0 = lds32(sb + SM_TOPI + (~waited & 1) * 4);
          if (solo && c == 0 && elect_one()) {
            mbar_expect(tokb, 8192);
            bulk_g2s(dst + 4 * 10240 + 2048, tok + 2048, 8192, tokb);
          }
          publish(waited);
          while (__any_sync(~0u, clk() - t0 < d)) {}
        }
        else if (c < 2) spin(prm.dh);
        if (elect_one()) bulk_g2s(dst, src, 2048, bar);
        if (c == 2 && !single) {
          mbar_wait_wd(sb + B_OB, pp);
          if (elect_one()) bulk_g2s(dst + 2048, tok, 8192, full);
        }
        g = 0;
        while (true) {
          mbar_wait_wd(bar, mph);
          mph ^= 1;
          const uint32_t v0 = lds32(dst + chk), v1 = lds32(dst + chk + 1024);
          if (__all_sync(~0u, v0 != ~0u && v1 != ~0u)) break;
          if (elect_one()) {
            mbar_expect(bar, 2048);
            bulk_g2s(dst, src, 2048, bar);
          }
          guard(g);
        }
        mbar_arrive_if(lane == 0, full, solo ? 2 : 1);
        TRACE(c < 2, m, 3 + 2 * c, gtl());
        TRACE(c < 2, m, 4 + 2 * c, g);
      }
    }
    publish(nslots);
    if (warp == 0) mbar_wait_wd(sb + B_END, 0);
  }
  __syncwarp();
  if (wid != 12 && lane0 == 0) mbar_arrive(sb + B_END);
  cluster_sync();
}
__device__ __align__(4096) uint32_t g_xa[NBLK * 10 * 4096];
__device__ __align__(4096) uint32_t g_h[NBLK * 24 * 4096];

enum { T_A = 0, T_F1 = 1, T_U = 2, T_D = 3, T_F2 = 4, T_NONE = 7 };
__host__ __device__ constexpr int c_phase(int type, int lb) { return C_O + type * 32 + lb; }
constexpr int C_TICKET = c_phase(5, 0), C_EXIT = C_TICKET + 1, C_USED = C_HALF + 2 * NBLK;
constexpr int G_NST = 7;
constexpr uint32_t GS_RED = G_NST * 32768, GS_BAR = GS_RED + 1088, G_SMEM = GS_BAR + 224;
constexpr uint32_t GB_FULL = GS_BAR, GB_EMPTY = GS_BAR + 64, GB_ORD = GS_BAR + 128, GB_READY = GS_BAR + 144, GB_ACK = GS_BAR + 152, GB_GATE = GS_BAR + 160, GB_SIG = GS_BAR + 176, GB_SACK = GS_BAR + 192,
                   GS_SIG = GS_BAR + 208, GS_COL = GS_BAR + 216;
#define FPL 6
constexpr int NF = 16;
constexpr int G_EARLY = 36;
constexpr int G_LATE = 96, PL = 6, ML = 8, DL = 30, TL = 10;
constexpr int GRC = 112, GRP = 32;
constexpr uint32_t E_UP = 1u << 8, E_HALF = 1u << 28, E_GRP = 1u << 29, E_HAND = 1u << 30, E_EXCL = 1u << 31;

struct GParams {
  __nv_bfloat16* out;
  const uint32_t* x;
  int moff, gd;
  int pend;
  uint8_t perm[G_EARLY], first[9];
  uint8_t need[5][2 * NBLK];
  uint32_t tab[G_EARLY * (PL + ML + DL) + G_LATE * TL];
};
constexpr int EL = PL + ML + DL, TAB_TAIL = G_EARLY * EL;
struct GIter {
  int p, left, period;
  uint32_t e, type, lb, n0, kb0, nkb;
  bool gemm, valid;
  DI GIter(const GParams& prm, int col) {
    if (col < G_EARLY) { p = col * EL; left = PL; period = 0; }
    else { p = TAB_TAIL + (col - G_EARLY) * TL; left = TL; period = prm.pend; }
  }
  DI bool next(const GParams& prm, int col) {
    do {
      if (left == 0) {
        if (++period > prm.pend) return false;
        left = period < prm.pend ? ML : DL;
        if (period > 1 && period < prm.pend) p -= ML;
      }
      e = prm.tab[p++]; left--;
    } while ((e & 7) == T_NONE);
    const int b = (e >> 4) & 15, blk = period < prm.pend ? period - b : b;
    type = e & 7; valid = blk >= 0; lb = (e & 8) * 2 + (blk & 15); n0 = (e >> 9) & 127; kb0 = (e >> 16) & 127;
    gemm = type != T_F1 && type != T_F2;
    nkb = valid ? (e >> 23) & 31 : 0;
    return true;
  }
  DI int id_(int pend) const { return period < pend ? period * 10 + ML - left : 160 + DL - left; }
};

#define GLOG(nt, i, v)
template <int TA> DI void wg_ss128(float* d, uint64_t da, uint64_t db, int sc) {
  asm volatile("{.reg .pred p; setp.ne.b32 p, %66, 0;\n"
               "wgmma.mma_async.sync.aligned.m64n128k16.f32.bf16.bf16 "
               "{%0,%1,%2,%3,%4,%5,%6,%7,%8,%9,%10,%11,%12,%13,%14,%15,%16,%17,%18,%19,%20,%21,%22,%23,%24,%25,%26,%27,%28,%29,%30,%31,"
               "%32,%33,%34,%35,%36,%37,%38,%39,%40,%41,%42,%43,%44,%45,%46,%47,%48,%49,%50,%51,%52,%53,%54,%55,%56,%57,%58,%59,%60,%61,%62,%63}, "
               "%64, %65, p, 1, 1, %67, 1;}"
               : ACC16(d, 0), ACC16(d, 16), ACC16(d, 32), ACC16(d, 48) : "l"(da), "l"(db), "r"(sc), "n"(TA));
}

template <int TA> DI void g_mainloop(float* acc, uint32_t sb, uint32_t hand, uint32_t gate, int nkb, int cw, int lane, uint32_t st, uint32_t ph) {
  const uint64_t da0 = (TA ? mkdesc(SMEM0, 4096, 512, 2) : mkdesc(SMEM0, 128, 1024, 0)) + (cw >> 2) * 512;
  const uint64_t db0 = mkdesc(SMEM0 + 16384, 8192, 1024, 1);
  uint32_t prev = 0;
#pragma unroll 1
  for (int kb = 0; kb < nkb; kb++) {
    mbar_wait(sb + GB_FULL + 8 * st, ph);
    mbar_wait(gate, 1);
    const uint64_t da = da0 + st * 2048, db = db0 + st * 2048;
    wg_fence();
#pragma unroll
    for (int k = 0; k < 4; k++) wg_ss128<TA>(acc, da + k * (TA ? 64 : 16), db + k * 128, 1);
    wg_commit();
    mbar_arrive_if(hand && kb == nkb - 1 && lane == 0, hand);
    wg_wait<1>();
    mbar_arrive_if(kb > 0 && lane == 0, sb + GB_EMPTY + 8 * prev);
    prev = st;
    if (++st == G_NST) { st = 0; ph ^= 1; }
  }
  wg_wait<0>();
  reg_fence<64>(acc);
  mbar_arrive_if(lane == 0, sb + GB_EMPTY + 8 * prev);
}

__global__ void __launch_bounds__(640, 1)
g_kernel(const __grid_constant__ CUtensorMap mapWo, const __grid_constant__ CUtensorMap mapWg, const __grid_constant__ CUtensorMap mapWu,
         const __grid_constant__ CUtensorMap mapWd, const __grid_constant__ GParams prm) {
  const uint32_t sb = smem_base();
  const int wid = __shfl_sync(~0u, threadIdx.x >> 5, 0), lane = threadIdx.x & 31;
  if (threadIdx.x == 0) {
    if ((sb & 0x3FFFF) != SMEM0) __trap();
    {
      uint32_t sm; asm volatile("mov.u32 %0, %%smid;" : "=r"(sm));
      uint32_t* const tk = &g_cnt[C_TICKET * CSTRIDE];
      uint32_t c = atomicAdd(tk, 1);
      if (c < G_EARLY) {
        const uint32_t k = sm < 64 ? (sm >> 1) & 7 : sm < 120 ? 1 + ((sm - 64) >> 1) % 7 : sm < 124 ? 1 + ((sm >> 1) & 1) : 0;
        const uint32_t t = atomicAdd(tk + 1 + k, 1);
        atomicAdd(tk + 9, 1);
        if (t < prm.first[k + 1] - prm.first[k]) c = prm.perm[prm.first[k] + t];
        else {
          uint32_t o = atomicAdd(tk + 10, 1), g = 0;
          while (ld_acq(tk + 9) < G_EARLY) guard(g);
          for (int j = 0; j < 8; j++)
            for (uint32_t i = prm.first[j] + ld_acq(tk + 1 + j); i < prm.first[j + 1]; i++) if (o-- == 0) c = prm.perm[i];
        }
      }
      sts32(sb + GS_COL, c);
    }
    for (int i = 0; i < G_NST; i++) { mbar_init(sb + GB_FULL + 8 * i, 1); mbar_init(sb + GB_EMPTY + 8 * i, 8); }
    mbar_init(sb + GB_ORD, 8); mbar_init(sb + GB_ORD + 8, 8); mbar_init(sb + GB_READY, 1); mbar_init(sb + GB_ACK, 1);
    mbar_init(sb + GB_GATE, 1); mbar_init(sb + GB_GATE + 8, 1);
    mbar_init(sb + GB_SIG, 8); mbar_init(sb + GB_SIG + 8, 8); mbar_init(sb + GB_SACK, 1); mbar_init(sb + GB_SACK + 8, 1);
    fence_async_smem();
  }
  __syncthreads();
  const int col = __shfl_sync(~0u, lds32(sb + GS_COL), 0);

  if (wid >= 16) {
    GIter t(prm, col);
    asm volatile("setmaxnreg.dec.sync.aligned.u32 %0;" ::"n"(GRP));
    uint32_t st = 0, ph = 1, k = 0;
    if (wid == 16) {
      while (t.next(prm, col)) {
        const CUtensorMap* m0 = t.type == T_A ? &mapWo : t.type == T_U ? &mapWg : &mapWd;
        const CUtensorMap* m1 = t.type == T_U ? &mapWu : m0;
        const int c0 = t.type == T_U ? t.n0 * 64 : (t.n0 & 7) * 128, c1 = t.type == T_U ? c0 : c0 + 64;
        if ((t.e & (E_HALF | E_UP)) == E_UP) poll_ge(&g_cnt[c_phase(t.type, t.lb) * CSTRIDE], prm.need[t.type][t.lb]);
#pragma unroll 1
        for (uint32_t kb = t.kb0; kb < t.kb0 + t.nkb; kb++) {
          mbar_wait(sb + GB_EMPTY + 8 * st, ph);
          if (elect_one()) {
            const uint32_t full = sb + GB_FULL + 8 * st, dst = sb + st * 32768;
            mbar_expect(full, (t.e & E_HALF) ? 24576 : 32768);
            tma_2d(dst + 16384, m0, c0, kb * 64, full);
            tma_2d(dst + 24576, m1, c1, kb * 64, full);
          }
          if (++st == G_NST) { st = 0; ph ^= 1; }
        }
      }
    } else if (wid == 17) {
      while (t.next(prm, col)) {
        if (!t.nkb) continue;
        const char* asrc = t.type == T_A ? (const char*)g_oT + (size_t)t.lb * (96 * 16384)
                         : t.type == T_U ? (const char*)g_xa + (size_t)(t.lb & 15) * (10 * 16384) : (const char*)g_h + (size_t)(t.lb & 15) * (24 * 16384);
        const uint32_t up = (t.e & E_HALF) ? (t.e & E_UP) * 32 : 0;
        GLOG(t.id_(prm.pend), 1, gtime());
        mbar_wait(sb + GB_READY, k & 1);
        mbar_arrive_if(lane == 0, sb + GB_ACK);
        k++;
#pragma unroll 1
        for (uint32_t kb = t.kb0; kb < t.kb0 + t.nkb; kb++) {
          mbar_wait(sb + GB_EMPTY + 8 * st, ph);
          if (elect_one()) bulk_g2s(sb + st * 32768 + up, asrc + (size_t)kb * 16384 + up, (t.e & E_HALF) ? 8192 : 16384, sb + GB_FULL + 8 * st);
          if (++st == G_NST) { st = 0; ph ^= 1; }
        }
      }
    } else if (wid == 18) {
      while (t.next(prm, col)) {
        if (!t.nkb) continue;
        const bool lower = t.type == T_A && (t.e & (E_HALF | E_UP)) == E_HALF;
        poll_ge(&g_cnt[(lower ? C_HALF + t.lb : c_phase(t.type, t.lb)) * CSTRIDE], prm.need[t.type][t.lb]);
        fence_async_global();
        GLOG(t.id_(prm.pend), 2, gtime());
        mbar_wait(sb + GB_ACK, (k & 1) ^ 1);
        mbar_arrive_if(lane == 0, sb + GB_READY);
        k++;
      }
    } else {
      uint32_t live = 3, par = 0, g = 0;
      while (live) {
        const bool ev = lane < 2 && ((live >> lane) & 1) && mbar_test(sb + GB_SIG + 8 * lane, (par >> lane) & 1);
        const uint32_t evs = __ballot_sync(~0u, ev);
        if (!evs) { guard(g); __nanosleep(20); continue; }
        const uint32_t msg = ev ? lds32(sb + GS_SIG + 4 * lane) : 0;
        mbar_arrive_if(ev, sb + GB_SACK + 8 * lane);
        mbar_arrive_if(msg >> 31, sb + GB_GATE + 8 * lane);
        if (msg) red_rel(&g_cnt[(msg & 0xffff) * CSTRIDE], (msg >> 16) & 255);
        par ^= evs;
        live &= ~__ballot_sync(~0u, ev && !msg);
        g = 0;
      }
      asm volatile("griddepcontrol.wait;" ::: "memory");
      if (col < 80 && lane < 16) g_mem[(col >> 4) * 2048 + (lane >> 3) * 1024 + 512 + prm.moff + (col & 15) * 8 + (lane & 7)] = make_uint4(~0u, ~0u, ~0u, ~0u);
      uint32_t last = 0;
      if (lane == 0) last = atomicAdd(&g_cnt[C_EXIT * CSTRIDE], 1) == gridDim.x - 1;
      if (__shfl_sync(~0u, last, 0)) {
        g_cnt[C_TICKET * CSTRIDE + lane] = 0;
        for (int i = lane; i < C_USED; i += 32) g_cnt[i * CSTRIDE] = 0;
      }
    }
  } else {
    asm volatile("setmaxnreg.inc.sync.aligned.u32 %0;" ::"n"(GRC));
    const int cw = wid & 7, wk = wid >> 3;
    GIter t(prm, col);
    uint32_t pos = 0, seen = 0, waited = 0;
    uint32_t nsig = 0;
    auto signal = [&](uint32_t msg) {
      mbar_wait(sb + GB_SACK + 8 * wk, (nsig++ & 1) ^ 1);
      if (cw == 0) sts32(sb + GS_SIG + 4 * wk, msg);
      __syncwarp();
      mbar_arrive_if(lane == 0, sb + GB_SIG + 8 * wk);
    };
    if (col < G_EARLY) {
      spin(prm.gd);
#pragma unroll 1
      for (int rg = 96 + col * 2 + wk; rg < 256; rg += 2 * G_EARLY) {
        uint32_t a[10];
        const uint32_t* src = prm.x + (size_t)(rg * 8 + (lane >> 2)) * (DM / 2) + cw * 40 + (lane & 3);
#pragma unroll
        for (int i = 0; i < 10; i++) a[i] = __ldg(src + i * 4);
        first_ln(a, rg, sb + GS_RED + wk * 512, cw, lane, 1 + wk);
        signal((C_XN + (rg >> 4)) | ((XN_TARGET / NF) << 16));
        bar_sync(1 + wk, 256);
      }
    }
    while (t.next(prm, col)) {
      const uint32_t pos0 = pos;
      pos = (pos + t.nkb) % (2 * G_NST);
      if (((t.e >> 29) & 1) != wk) { seen += (t.e >> 30) & 1; continue; }
      const uint32_t type = t.type, blk = t.lb & 15, layer = t.lb >> 4, n0 = t.n0;
      if (cw == 0 && t.valid) GLOG(t.id_(prm.pend), 0, 0x80000000u | type | (t.lb << 3) | (n0 << 8) | (t.nkb << 16));
      if (!t.gemm) {
        if (!t.valid) continue;
        const int rg = blk * 16 + n0;
        float4 v[5];
        const int off = (n0 * 40 + cw * 5) * 32 + lane, npl = t.kb0;
        const uint2* src = acc_planes(t.lb, type == T_F2) + off;
        if (cw == 0) {
          poll_ge(&g_cnt[c_phase(type, t.lb) * CSTRIDE], prm.need[type][t.lb]);
          mbar_arrive_if((t.e & E_EXCL) && lane == 0, sb + GB_GATE + 8 * wk);
          GLOG(t.id_(prm.pend), 2, gtime()); GLOG(t.id_(prm.pend), 3, gtime());
        }
        bar_sync(1 + wk, 256);
        {
          const uint32_t eye = (lane >> 3) == (lane & 3) ? ((lane & 4) ? 0x3f800000u : 0x00003f80u) : 0u;
#pragma unroll
          for (int i = 0; i < 5; i++) v[i] = make_float4(0.f, 0.f, 0.f, 0.f);
#pragma unroll 1
          for (int p0 = 0; p0 < npl; p0 += FPL) {
            uint32_t r[FPL / 2][5][4];
#pragma unroll
            for (int p = 0; p < FPL; p++)
#pragma unroll
              for (int i = 0; i < 5; i++) {
                const uint2 w = p0 + p < npl ? __ldcg(src + (size_t)(p0 + p) * PLANE + i * 32) : make_uint2(0, 0);
                r[p >> 1][i][(p & 1) * 2] = w.x; r[p >> 1][i][(p & 1) * 2 + 1] = w.y;
              }
#pragma unroll
            for (int p = 0; p < FPL / 2; p++) {
              if (p0 + 2 * p >= npl) break;
              if (t.e & E_EXCL) {
#pragma unroll
                for (int i = 0; i < 5; i++) mma16816(&v[i].x, r[p][i], eye, eye);
              } else {
#pragma unroll
                for (int i = 0; i < 5; i++) {
                  const uint32_t* w = r[p][i];
                  v[i].x += blo(w[0]) + blo(w[2]); v[i].y += bhi(w[0]) + bhi(w[2]); v[i].z += blo(w[1]) + blo(w[3]); v[i].w += bhi(w[1]) + bhi(w[3]);
                }
              }
            }
          }
        }
        if (type == T_F2 && layer == 1) {
          uint2* dst = (uint2*)prm.out + (size_t)(rg * 8 + (lane >> 2)) * (DM / 4) + cw * 20 + (lane & 1) * 2 + ((lane >> 1) & 1);
#pragma unroll
          for (int i = 0; i < 5; i++) {
            const uint32_t a = pack2(v[i].x, v[i].y), b = pack2(v[i].z, v[i].w);
            const uint32_t o = __shfl_xor_sync(~0u, (lane & 1) ? a : b, 1);
            dst[i * 4] = (lane & 1) ? make_uint2(o, b) : make_uint2(a, o);
          }
        } else {
          uint2* nx = (type == T_F1 ? acc_planes(t.lb, 1) : acc_planes(NBLK + blk, 0)) + off;
#pragma unroll
          for (int i = 0; i < 5; i++) {
            const uint2 w = make_uint2(pack2(v[i].x, v[i].y), pack2(v[i].z, v[i].w));
            nx[i * 32] = w;
            v[i] = make_float4(blo(w.x), bhi(w.x), blo(w.y), bhi(w.y));
          }
          float mean, rstd;
          ln_stats(v, sb + GS_RED + wk * 512, cw, lane, 1 + wk, mean, rstd);
          if (type == T_F2) store_img<4, 2048>(xn_row_group(1, rg) + lane, v, cw, mean, rstd);
          else store_img<3, 4096>(g_xa + (size_t)(blk * 10 * 4096 + n0 * 256) + lane, v, cw, mean, rstd);
        }
      } else {
        float acc[64];
#pragma unroll
        for (int j = 0; j < 64; j++) acc[j] = 0.f;
        if (waited != seen) { mbar_wait(sb + GB_ORD + 8 * (wk ^ 1), waited & 1); waited++; }
        const uint32_t hand = (t.e & E_HAND) ? sb + GB_ORD + 8 * wk : 0;
        if (!t.valid) { mbar_arrive_if(hand && lane == 0, hand); continue; }
        if (cw == 0) GLOG(t.id_(prm.pend), 3, gtime());
        const uint32_t ph = pos0 >= G_NST, st = pos0 - ph * G_NST, early = (t.e & E_EXCL) ? 0 : hand;
        const bool idle = (t.e & E_HALF) && ((t.e >> 8) & 1) != (cw >> 2);
        if (idle) {
          uint32_t s2 = st, p2 = ph;
#pragma unroll 1
          for (uint32_t kb = 0; kb < t.nkb; kb++) {
            mbar_wait(sb + GB_FULL + 8 * s2, p2);
            mbar_arrive_if(lane == 0, sb + GB_EMPTY + 8 * s2);
            if (++s2 == G_NST) { s2 = 0; p2 ^= 1; }
          }
          mbar_arrive_if(early && lane == 0, early);
        } else if (type == T_A) g_mainloop<1>(acc, sb, early, sb + GB_GATE + 8 * (wk ^ 1), t.nkb, cw, lane, st, ph);
        else g_mainloop<0>(acc, sb, early, sb + GB_GATE + 8 * (wk ^ 1), t.nkb, cw, lane, st, ph);
        if (cw == 0) GLOG(t.id_(prm.pend), 4, gtime());
        if (idle) {
        } else if (type == T_U) {
          uint32_t* dst = g_h + (size_t)((blk * 24 + n0) * 4096 + cw * 512) + lane;
#pragma unroll
          for (int j = 0; j < 8; j++) {
            float h[4];
#pragma unroll
            for (int e = 0; e < 4; e++) {
              float th;
              asm("tanh.approx.f32 %0, %1;" : "=f"(th) : "f"(0.5f * acc[4 * j + e]));
              h[e] = acc[32 + 4 * j + e] * fmaf(th, 0.5f, 0.5f);
            }
            dst[j * 32] = pack2(h[0], h[1]);
            dst[j * 32 + 256] = pack2(h[2], h[3]);
          }
        } else {
          uint2* dst = acc_planes(t.lb, type == T_D) + (size_t)((1 + (n0 >> 3)) * PLANE + (2 * cw * 40 + (n0 & 7) * 8) * 32) + lane;
#pragma unroll
          for (int j = 0; j < 16; j++) {
            const float* a = acc + (j >> 1) * 8 + (j & 1) * 2;
            dst[(j >> 1) * 32 + (j & 1) * 1280] = make_uint2(pack2(a[0], a[1]), pack2(a[4], a[5]));
          }
        }
        mbar_arrive_if(hand != early && lane == 0, hand);
      }
      if (cw == 0) GLOG(t.id_(prm.pend), 5, gtime());
      if (cw == 0) GLOG(t.id_(prm.pend), 6, gtime());
      if (type == T_F2 && layer == 1) mbar_arrive_if((t.e & E_EXCL) && cw == 0 && lane == 0, sb + GB_GATE + 8 * wk);
      else
        signal((type != T_F2 ? c_phase(type + 1, t.lb) | (1 << 16) : (C_XN + NBLK + blk) | ((XN_TARGET / NF) << 16)) | (t.gemm ? 0 : t.e & E_EXCL));
    }
    signal(0);
  }
}

typedef CUresult (*EncodeFn)(CUtensorMap*, CUtensorMapDataType, cuuint32_t, void*, const cuuint64_t*, const cuuint64_t*, const cuuint32_t*,
                             const cuuint32_t*, CUtensorMapInterleave, CUtensorMapSwizzle, CUtensorMapL2promotion, CUtensorMapFloatOOBfill);
static CUtensorMap make_map(EncodeFn fn, const void* p, uint64_t inner, uint64_t outer, uint32_t bi, uint32_t bo, int promo = 3) {
  CUtensorMap m;
  cuuint64_t dims[2] = {inner, outer}, str[1] = {inner * 2};
  cuuint32_t box[2] = {bi, bo}, es[2] = {1, 1};
  fn(&m, CU_TENSOR_MAP_DATA_TYPE_BFLOAT16, 2, (void*)p, dims, str, box, es, CU_TENSOR_MAP_INTERLEAVE_NONE, CU_TENSOR_MAP_SWIZZLE_128B,
     (CUtensorMapL2promotion)promo, CU_TENSOR_MAP_FLOAT_OOB_FILL_NONE);
  return m;
}
struct Tune {
  int lag = 11, excl = 6, gonly = 0, xl = 1, ronly = 0, pn = 30;
  int da = 120, db = 350, dc = 650, dd = 650, d2 = 2170, p1 = 300, p2 = 800;
  int ea = 60, eb = 310, ec = 550, ed = 550, e2 = 2200, q1 = 200, q2 = 400, d3 = 60, moff = 192, ds = 400, dh = 60, pa = 0, pb = 0, pc = 0, pd = 0, pe = 0, pf = 0, pg = 0, ph = 0, wpf = 4, gd = 22000, dq = 300, sl = 18, pr = 2, pg2 = 3;
};
static void fill_r(RParams& p, const Tune& t, int lag, int n0, int n1) {
  r_fill_desc(p);
  p.nslots = 0; p.d3 = t.d3; p.pn = t.pn; p.moff = t.moff; p.ds = t.ds; p.dh = t.dh; p.dq = t.dq;
  for (int c = 0; c < 5; c++) { p.d2[c] = t.d2 + (c == 0 ? 0 : c < 3 ? t.p1 : t.p2); p.d2[5 + c] = t.e2 + (c == 0 ? 0 : c < 3 ? t.q1 : t.q2); }
  const int d1[8] = {t.da, t.db, t.dc, t.dd, t.ea, t.eb, t.ec, t.ed};
  for (int i = 0; i < 8; i++) p.d1[i] = d1[i];
  int last[2] = {0, 0}, n = 0;
  for (int s0 = 0; s0 < NSEG + lag; s0++)
    for (int l = 0; l < 2; l++) {
      const int s = l ? s0 - lag : s0;
      if (s < 0 || s >= NSEG) continue;
      if (n >= n0 && n < n1) { p.slot[p.nslots] = s | (l << 6) | (last[l] << 8) | (((s & 3) == 3 ? C_O + l * NBLK + s / 4 : s == (l ? 61 : 1) ? C_HALF + l * NBLK + s / 4 : 0) << 16); last[l] = ++p.nslots; }
      n++;
    }
  for (int i = 0; i + 1 < p.nslots; i++) if (((p.slot[i] ^ p.slot[i + 1]) >> 6) & 1) p.slot[i] |= 128;
}
static uint32_t g_entry(int grp, int type, int layer, int blk, int i, int ks) {
  int n0 = i, kb0 = 0, kb1 = type == T_U ? 10 : 0;
  if (type == T_F1 || type == T_F2) kb0 = kb1 = ks + 1;
  if (type == T_A || type == T_D) {
    const int KB = type == T_A ? 96 : 24, sp = i / 5;
    n0 = i % 5 | (sp << 3); kb0 = sp * KB / ks; kb1 = (sp + 1) * KB / ks;
  }
  return type | (layer << 3) | (blk << 4) | (n0 << 9) | (kb0 << 16) | ((kb1 - kb0) << 23) | (grp ? E_GRP : 0);
}
static bool g_is_gemm(uint32_t e) { return (e & 7) == T_A || (e & 7) == T_U || (e & 7) == T_D; }
static void g_handover(uint32_t* e, int len) {
  uint32_t next = 0;
  for (int i = len - 1; i >= 0; i--)
    if (g_is_gemm(e[i])) { if ((e[i] & E_GRP) != next) e[i] |= E_HAND; next = e[i] & E_GRP; }
}
static bool g_overflow = false;
struct GList {
  static void overflow() { g_overflow = true; }
  bool shared = false;
  GParams& g; uint32_t* tab; int ncol, stride, len, n[G_LATE], load[G_LATE], grp[G_LATE];
  GList(GParams& g_, uint32_t* t, int nc, int st, int l) : g(g_), tab(t), ncol(nc), stride(st), len(l) { for (int c = 0; c < nc; c++) { n[c] = load[c] = 0; grp[c] = 1; } }
  void add(int type, int lb, int ks, int c0, int c1, uint32_t flags = 0, int i0 = 0, int i1 = 999, int step = 1) {
    const int half = (flags & E_HALF) != 0, ln = type == T_F1 || type == T_F2;
    const int cnt = (type == T_U ? 24 : ln ? NF : 5 * ks) << half;
    if (type < T_F2) g.need[type + 1][lb] = cnt;
    int used[G_LATE] = {0};
    for (int i = i0; i < cnt && i < i1; i += step) {
      int best = c0;
      for (int c = c0; c < c1; c++) if (used[c] < used[best] || (used[c] == used[best] && load[c] < load[best])) best = c;
      used[best]++;
      if (!ln) grp[best] ^= 1;
      const uint32_t e = g_entry(grp[best], type, lb >> 4, lb & 15, i >> half, ks) | flags | (ln && !shared ? E_EXCL : 0) | ((i & half) ? E_UP : 0);
      if (n[best] >= len) { overflow(); return; }
      tab[best * stride + n[best]++] = e;
      load[best] += (((e >> 23) & 31) >> half) + 2;
    }
  }
  void put(int c, uint32_t e) { if (n[c] >= len) { overflow(); return; } tab[c * stride + n[c]++] = e; if (g_is_gemm(e)) grp[c] = (e & E_GRP) != 0; }
  void finish() { for (int c = 0; c < ncol; c++) g_handover(tab + c * stride, len); }
};
static void fill_g(GParams& g, const Tune& t, void* out) {
  g.out = (__nv_bfloat16*)out;  g.pend = NBLK - 2;
  for (int b = 0; b < 2 * NBLK; b++) {
    g.need[T_A][b] = 96; g.need[T_F1][b] = 20; g.need[T_U][b] = NF; g.need[T_D][b] = 32; g.need[T_F2][b] = 15;
  }
  {
    const uint8_t perm[G_EARLY] = {0, 1, 2, 3, 16, 17, 18, 19, 34, 35, 4, 20, 21, 15, 22, 23, 5, 6, 7, 8, 9, 24, 25, 26, 10, 11, 12, 13, 14, 27, 28, 29, 30, 31, 32, 33};
    const uint8_t first[9] = {0, 10, 13, 16, 20, 24, 28, 32, 36};
    const int* pk = &t.pa;
    for (int i = 0; i < G_EARLY; i++) g.perm[i] = t.pa ? (pk[i / 5] >> (6 * (i % 5))) & 63 : perm[i];
    for (int i = 0; i < 9; i++) g.first[i] = first[i];
  }
  for (uint32_t& e : g.tab) e = T_NONE;
  GList pr(g, g.tab, G_EARLY, EL, PL);
  pr.add(T_A, 0, 7, 1, 36, E_HALF, 0, 999, 2); pr.add(T_A, 0, 7, 1, 36, E_HALF, 1, 999, 2); pr.add(T_F1, 0, 7, 20, 36); pr.add(T_U, 0, 0, 12, 36);
  pr.add(T_D, 0, 3, 20, 36); pr.add(T_F2, 0, 3, 20, 36);
  pr.finish();
  const int d = 3;
  const uint32_t xa = (t.excl & 1) ? E_EXCL : 0, xu = (t.excl & 2) ? E_EXCL : 0, xd = (t.excl & 4) ? E_EXCL : 0;
  for (int c = 0; c < G_EARLY; c++) {
    uint32_t* e = g.tab + c * EL + PL;
    if (c < 20) {
      *e++ = g_entry(0, T_A, 0, 0, c, 4) | xa;
      if (c < NF) *e++ = g_entry(0, T_F1, 0, 0, c, 4) | ((t.xl & 1) ? E_EXCL : 0);
      *e++ = g_entry(1, T_A, 1, d, c, 4);
      if (c >= 20 - NF) *e++ = g_entry(1, T_F1, 1, d, c - (20 - NF), 4);
    } else {
      const int j = c - 20;
      const uint32_t hf = E_HALF | ((j & 1) ? E_UP : 0);
      *e++ = g_entry(0, T_U, 0, 0, j, 0);
      *e++ = g_entry(1, T_U, 0, 0, 16 + j / 2, 0) | hf | xu;
      *e++ = g_entry(0, T_U, 1, d + 1, 16 + j / 2, 0) | hf;
      if (j < 15) *e++ = g_entry(1, T_D, 0, 0, j, 3) | xd;
      *e++ = g_entry(1, T_F2, 0, 0, j, 3) | ((t.xl & 2) ? E_EXCL : 0);
      if (j < 15) *e++ = g_entry(0, T_D, 1, d + 1, j, 3);
      *e++ = g_entry(0, T_U, 1, d, j, 0);
      *e++ = g_entry(1, T_F2, 1, d + 1, j, 3);
    }
    g_handover(g.tab + c * EL + PL, ML);
  }
  GList dr(g, g.tab + PL + ML, G_EARLY, EL, DL);
  GList tl(g, g.tab + TAB_TAIL, G_LATE, TL, TL);
  const int L1 = NBLK;
  auto ufull = [&](int lb, uint32_t fl) { dr.add(T_U, lb, 0, 20, 36, fl, 0, 16); g.need[T_D][lb] = 32; };
  auto uhalf = [&](int lb, int c0, uint32_t fl) { dr.add(T_U, lb, 0, c0, 36, E_HALF | fl, 32); g.need[T_D][lb] = 32; };
  for (int c = 0; c < G_EARLY; c++)
    for (int i = 0; i < ML; i++) {
      uint32_t e = g.tab[c * EL + PL + i] & ~E_HAND;
      const uint32_t ty = e & 7;
      if (ty == T_NONE || ((e & 8) && (ty == T_F2 || (ty == T_U && !(e & E_HALF))))) continue;
      e = (e & ~0xf0u) | (14 - ((e >> 4) & 15)) << 4;
      dr.put(c, e | (ty == T_F2 ? E_EXCL : 0));
    }
  dr.add(T_A, 15, 4, 0, 20, E_EXCL);
  dr.add(T_F1, 15, 4, 4, 20);
  dr.add(T_U, 15, 0, 12, 36, E_EXCL);
  for (int c = 0; c < 20; c++) {
    const int tile = c % 5, sp = c / 5, len = tile < 2 ? (96 - t.sl) / 3 : 48 - t.sl, nl = tile < 2 ? 3 : 2;
    const int k0 = sp <= nl ? sp * len : nl * len + t.sl, nk = sp < nl ? len : sp == 3 ? 96 - k0 : t.sl;
    dr.put(c, (g_entry(dr.grp[c] ^ 1, T_A, 1, 12, c, 4) & ~0x0fff0000u) | k0 << 16 | nk << 23);
  }
  dr.add(T_F1, L1 + 12, 4, 0, 16);
  dr.add(T_A, L1 + 13, 4, 0, 20);
  dr.add(T_D, 15, 3, 20, 36, E_EXCL); dr.add(T_F2, 15, 3, 20, 36);
  ufull(L1 + 11, 0); uhalf(L1 + 11, 20, 0);
  dr.add(T_A, L1 + 14, 4, 0, 20, E_EXCL);
  dr.add(T_F1, L1 + 13, 4, 0, 20);
  dr.add(T_D, L1 + 11, 3, 20, 36);
  ufull(L1 + 12, E_UP); uhalf(L1 + 12, 12, E_EXCL);
  dr.add(T_A, L1 + 15, 7, 0, 35, E_HALF | E_EXCL, 0, 999, 2); dr.add(T_A, L1 + 15, 7, 0, 35, E_HALF | E_EXCL, 1, 999, 2);
  dr.add(T_F1, L1 + 15, 7, 20, 36);
  dr.add(T_F2, L1 + 10, 3, 0, 20);
  dr.shared = true; dr.add(T_F2, L1 + 11, 3, 4, 20); dr.shared = false;
  dr.add(T_D, L1 + 13, 3, 4, 20, E_UP);
  dr.add(T_F2, L1 + 12, 3, 0, 20);
  dr.finish();
  tl.add(T_D, L1 + 12, 3, 72, G_LATE);
  tl.add(T_U, L1 + 13, 0, 24, 48, E_EXCL);
  tl.add(T_F1, L1 + 14, 4, 0, 48);
  tl.add(T_U, L1 + 14, 0, 0, 24);
  tl.add(T_D, L1 + 14, 4, 0, 48, E_HALF | E_EXCL);
  tl.add(T_U, L1 + 15, 0, 48, G_LATE, E_HALF);
  tl.add(T_D, L1 + 15, 4, 48, G_LATE, E_HALF);
  tl.add(T_F2, L1 + 13, 3, 48, 72);
  tl.add(T_F2, L1 + 14, 4, 0, 48);
  tl.add(T_F2, L1 + 15, 4, 48, G_LATE);
  tl.finish();
}
static void launch_all(void* const* d_in, void* d_out, const Tune& t, cudaStream_t st) {
  static EncodeFn fn = nullptr;
  if (!fn) {
    void* f = nullptr;
    cudaDriverEntryPointQueryResult qr;
    cudaGetDriverEntryPoint("cuTensorMapEncodeTiled", &f, cudaEnableDefault, &qr);
    fn = (EncodeFn)f;
    cudaFuncSetAttribute(r_kernel, cudaFuncAttributeMaxDynamicSharedMemorySize, R_SMEM);
    cudaFuncSetAttribute(g_kernel, cudaFuncAttributeMaxDynamicSharedMemorySize, G_SMEM);
  }
  const CUtensorMap mq = make_map(fn, d_in[2], HD, DM, 64, 128, t.pr), mk = make_map(fn, d_in[3], HD, DM, 64, 128, t.pr), mv = make_map(fn, d_in[4], HD, DM, 64, 128, t.pr),
                    mo = make_map(fn, d_in[5], DM, HD, 64, 64, t.pg2), mg = make_map(fn, d_in[8], FF, DM, 64, 64, t.pg2), mu = make_map(fn, d_in[9], FF, DM, 64, 64, t.pg2),
                    md = make_map(fn, d_in[10], DM, FF, 64, 64, t.pg2);
  auto launch_r = [&](int lag, int n0, int n1) {
    RParams p;
    fill_r(p, t, lag, n0, n1);
    p.mem0 = (const uint4*)d_in[1]; p.x = (const uint32_t*)d_in[0]; p.pf = t.wpf;
    cudaLaunchConfig_t cfg = {};
    cfg.gridDim = dim3(3, NH); cfg.blockDim = dim3(512); cfg.dynamicSmemBytes = R_SMEM; cfg.stream = st;
    cudaLaunchAttribute at[1];
    at[0].id = cudaLaunchAttributeClusterDimension; at[0].val.clusterDim.x = 3; at[0].val.clusterDim.y = 1; at[0].val.clusterDim.z = 1;
    cfg.attrs = at; cfg.numAttrs = 1;
    cudaLaunchKernelEx(&cfg, r_kernel, mq, mk, mv, mo, p);
  };
  auto launch_g = [&](const GParams& g, bool pdl) {
    cudaLaunchConfig_t cfg = {};
    cfg.gridDim = dim3(132); cfg.blockDim = dim3(640); cfg.dynamicSmemBytes = G_SMEM; cfg.stream = st;
    cudaLaunchAttribute at[2];
    at[0].id = cudaLaunchAttributeProgrammaticStreamSerialization; at[0].val.programmaticStreamSerializationAllowed = 1;
    cfg.attrs = at; cfg.numAttrs = pdl ? 1 : 0;
    cudaLaunchKernelEx(&cfg, g_kernel, mo, mg, mu, md, g);
  };
  GParams g;
  fill_g(g, t, d_out);
  g.moff = t.moff; g.gd = t.gd; g.x = (const uint32_t*)d_in[0];
  launch_r(t.lag, 0, 2 * NSEG);
  launch_g(g, true);
}

extern "C" void kernel_launch(void* const* d_in, const int* in_sizes, int n_in, void* d_out, int out_size) {
  launch_all(d_in, d_out, Tune(), cudaStreamPerThread);
}
```

```cpp
#include <cuda_runtime.h>
#include <cuda_bf16.h>
#include <cuda.h>
#include <stdint.h>
#include <stdlib.h>

constexpr int SEQ = 2048, DM = 640, NH = 32, DH = 192, HD = NH * DH, FF = 1536;
constexpr int NSEG = 64, SEGL = 32, NMEM = 8;
constexpr int NBLK = 16;

#define DI __device__ __forceinline__

DI uint32_t smem_base() {
  extern __shared__ __align__(1024) unsigned char smem_raw[];
  uint32_t a;
  asm volatile("{.reg .u64 t; cvta.to.shared.u64 t, %1; cvt.u32.u64 %0, t;}" : "=r"(a) : "l"(smem_raw));
  return a;
}
DI uint32_t mapa(uint32_t a, uint32_t r) {
  uint32_t o;
  asm("mapa.shared::cluster.u32 %0, %1, %2;" : "=r"(o) : "r"(a), "r"(r));
  return o;
}
DI void mbar_init(uint32_t bar, uint32_t cnt) { asm volatile("mbarrier.init.shared::cta.b64 [%0], %1;" ::"r"(bar), "r"(cnt) : "memory"); }
DI void mbar_arrive(uint32_t bar) { asm volatile("mbarrier.arrive.shared::cta.b64 _, [%0];" ::"r"(bar) : "memory"); }
DI void mbar_expect(uint32_t bar, uint32_t tx) { asm volatile("mbarrier.arrive.expect_tx.shared::cta.b64 _, [%0], %1;" ::"r"(bar), "r"(tx) : "memory"); }
DI void mbar_arrive_if(bool p, uint32_t bar) { asm volatile("{.reg .pred p; setp.ne.b32 p, %1, 0; @p mbarrier.arrive.shared::cta.b64 _, [%0];}" ::"r"(bar), "r"((int)p) : "memory"); }
DI void mbar_arrive_if(bool p, uint32_t bar, uint32_t cnt) {
  asm volatile("{.reg .pred p; setp.ne.b32 p, %1, 0; @p mbarrier.arrive.shared::cta.b64 _, [%0], %2;}" ::"r"(bar), "r"((int)p), "r"(cnt) : "memory");
}
DI void mbar_expect_if(bool p, uint32_t bar, uint32_t tx) {
  asm volatile("{.reg .pred p; setp.ne.b32 p, %2, 0; @p mbarrier.arrive.expect_tx.shared::cta.b64 _, [%0], %1;}" ::"r"(bar), "r"(tx), "r"((int)p) : "memory");
}
DI bool mbar_test(uint32_t bar, uint32_t par) {
  uint32_t ok;
  asm volatile("{.reg .pred p; mbarrier.test_wait.parity.shared::cta.b64 p, [%1], %2; selp.u32 %0, 1, 0, p;}" : "=r"(ok) : "r"(bar), "r"(par) : "memory");
  return ok;
}
DI void mbar_wait(uint32_t bar, uint32_t par) {
  asm volatile(
      "{.reg .pred p;\n"
      "LOOP:\n"
      "mbarrier.try_wait.parity.shared::cta.b64 p, [%0], %1;\n"
      "@!p bra LOOP;\n}" ::"r"(bar), "r"(par) : "memory");
}
DI void mbar_wait_wd(uint32_t bar, uint32_t par) {
  asm volatile(
      "{.reg .pred p; .reg .u32 c;\n"
      "mov.u32 c, 0;\n"
      "LOOP:\n"
      "mbarrier.try_wait.parity.shared::cta.b64 p, [%0], %1;\n"
      "@p bra DONE;\n"
      "add.u32 c, c, 1;\n"
      "setp.lt.u32 p, c, 4000000;\n"
      "@p bra LOOP;\n"
      "trap;\n"
      "DONE:\n}" ::"r"(bar), "r"(par) : "memory");
}
DI void fence_async_smem() { asm volatile("fence.proxy.async.shared::cta;" ::: "memory"); }
DI void fence_async_global() { asm volatile("fence.proxy.async.global;" ::: "memory"); }
DI void bar_sync(int id, int n) { asm volatile("bar.sync %0, %1;" ::"r"(id), "r"(n) : "memory"); }
DI void bar_arrive(int id, int n) { asm volatile("bar.arrive %0, %1;" ::"r"(id), "r"(n) : "memory"); }
DI void cluster_sync() { asm volatile("barrier.cluster.arrive.release.aligned; barrier.cluster.wait.acquire.aligned;" ::: "memory"); }
DI bool elect_one() {
  uint32_t p;
  asm volatile("{.reg .pred p; elect.sync _|p, 0xffffffff; selp.u32 %0, 1, 0, p;}" : "=r"(p));
  return p;
}
DI void bulk_g2s(uint32_t dst, const void* src, uint32_t bytes, uint32_t bar) {
  asm volatile("cp.async.bulk.shared::cluster.global.mbarrier::complete_tx::bytes [%0], [%1], %2, [%3];" ::"r"(dst), "l"(src), "r"(bytes), "r"(bar) : "memory");
}
DI void bulk_s2s(uint32_t dst, uint32_t src, uint32_t bytes, uint32_t bar) {
  asm volatile("cp.async.bulk.shared::cluster.shared::cta.mbarrier::complete_tx::bytes [%0], [%1], %2, [%3];" ::"r"(dst), "r"(src), "r"(bytes), "r"(bar) : "memory");
}
DI void tma_2d(uint32_t dst, const CUtensorMap* map, int c0, int c1, uint32_t bar) {
  asm volatile("cp.async.bulk.tensor.2d.shared::cluster.global.mbarrier::complete_tx::bytes [%0], [%1, {%3, %4}], [%2];" ::"r"(dst), "l"(map), "r"(bar), "r"(c0), "r"(c1) : "memory");
}
DI void st_async4(uint32_t a, uint32_t x, uint32_t y, uint32_t z, uint32_t w, uint32_t bar) {
  asm volatile("st.async.shared::cluster.mbarrier::complete_tx::bytes.v4.b32 [%0], {%1,%2,%3,%4}, [%5];" ::"r"(a), "r"(x), "r"(y), "r"(z), "r"(w), "r"(bar) : "memory");
}
DI void st_async1(uint32_t a, uint32_t x, uint32_t bar) {
  asm volatile("st.async.shared::cluster.mbarrier::complete_tx::bytes.b32 [%0], %1, [%2];" ::"r"(a), "r"(x), "r"(bar) : "memory");
}
DI void sts32(uint32_t a, uint32_t x) { asm volatile("st.shared.b32 [%0], %1;" ::"r"(a), "r"(x) : "memory"); }
DI void sts128(uint32_t a, uint4 v) { asm volatile("st.shared.v4.b32 [%0], {%1,%2,%3,%4};" ::"r"(a), "r"(v.x), "r"(v.y), "r"(v.z), "r"(v.w) : "memory"); }
DI uint32_t lds32(uint32_t a) { uint32_t v; asm volatile("ld.shared.b32 %0, [%1];" : "=r"(v) : "r"(a) : "memory"); return v; }
DI uint2 lds64(uint32_t a) { uint2 v; asm volatile("ld.shared.v2.b32 {%0,%1}, [%2];" : "=r"(v.x), "=r"(v.y) : "r"(a) : "memory"); return v; }
DI uint4 lds128(uint32_t a) { uint4 v; asm volatile("ld.shared.v4.b32 {%0,%1,%2,%3}, [%4];" : "=r"(v.x), "=r"(v.y), "=r"(v.z), "=r"(v.w) : "r"(a) : "memory"); return v; }
DI void stsm4(uint32_t a, uint32_t r0, uint32_t r1, uint32_t r2, uint32_t r3) {
  asm volatile("stmatrix.sync.aligned.m8n8.x4.shared.b16 [%0], {%1,%2,%3,%4};" ::"r"(a), "r"(r0), "r"(r1), "r"(r2), "r"(r3) : "memory");
}
DI void stsm2(uint32_t a, uint32_t r0, uint32_t r1) {
  asm volatile("stmatrix.sync.aligned.m8n8.x2.shared.b16 [%0], {%1,%2};" ::"r"(a), "r"(r0), "r"(r1) : "memory");
}
DI uint32_t movm(uint32_t a) { uint32_t d; asm volatile("movmatrix.sync.aligned.m8n8.trans.b16 %0, %1;" : "=r"(d) : "r"(a)); return d; }
DI uint32_t pack2(float lo, float hi) { uint32_t d; asm("cvt.rn.bf16x2.f32 %0, %1, %2;" : "=r"(d) : "f"(hi), "f"(lo)); return d; }
DI void st_rlx1(void* p, uint32_t x) { asm volatile("st.relaxed.gpu.global.u32 [%0], %1;" ::"l"(p), "r"(x) : "memory"); }
DI uint32_t ld_acq(const uint32_t* p) { uint32_t v; asm volatile("ld.acquire.gpu.global.u32 %0, [%1];" : "=r"(v) : "l"(p) : "memory"); return v; }
DI uint32_t ld_rlx(const uint32_t* p) { uint32_t v; asm volatile("ld.relaxed.gpu.global.u32 %0, [%1];" : "=r"(v) : "l"(p) : "memory"); return v; }
DI void red_rel(uint32_t* p, uint32_t v) { asm volatile("red.release.gpu.global.add.u32 [%0], %1;" ::"l"(p), "r"(v) : "memory"); }
DI void guard(uint32_t& g) { asm volatile("{.reg .pred p; add.u32 %0, %0, 1; setp.gt.u32 p, %0, 8000000; @p trap;}" : "+r"(g)); }
DI void poll_ge(const uint32_t* p, uint32_t target) {
  asm volatile(
      "{.reg .pred p; .reg .u32 v;\n"
      "LOOP:\n"
      "ld.acquire.gpu.global.u32 v, [%0];\n"
      "setp.lt.u32 p, v, %1;\n"
      "vote.sync.any.pred p, p, 0xffffffff;\n"
      "@p bra.uni LOOP;\n}" ::"l"(p), "r"(target) : "memory");
}
DI float ex2(float x) { float y; asm("ex2.approx.ftz.f32 %0, %1;" : "=f"(y) : "f"(x)); return y; }

DI void wg_fence() { asm volatile("wgmma.fence.sync.aligned;" ::: "memory"); }
DI void wg_commit() { asm volatile("wgmma.commit_group.sync.aligned;" ::: "memory"); }
template <int N> DI void wg_wait() { asm volatile("wgmma.wait_group.sync.aligned %0;" ::"n"(N) : "memory"); }
template <int N> DI void reg_fence(float* d) {
#pragma unroll
  for (int i = 0; i < N; i++) asm volatile("" : "+f"(d[i])::"memory");
}
__host__ __device__ constexpr uint64_t mkdesc(uint32_t addr, uint32_t lbo, uint32_t sbo, uint32_t sw) {
  return (uint64_t)((addr & 0x3FFFF) >> 4) | ((uint64_t)(lbo >> 4) << 16) | ((uint64_t)(sbo >> 4) << 32) | ((uint64_t)sw << 62);
}

#define ACC4(d, o) "+f"(d[o]), "+f"(d[o + 1]), "+f"(d[o + 2]), "+f"(d[o + 3])
#define ACC16(d, o) ACC4(d, o), ACC4(d, o + 4), ACC4(d, o + 8), ACC4(d, o + 12)
#define ACC20(d) ACC16(d, 0), ACC4(d, 16)

template <int TA, int TB> DI void wg_ss40(float* d, uint64_t da, uint64_t db, int sc) {
  asm volatile("{.reg .pred p; setp.ne.b32 p, %22, 0;\n"
               "wgmma.mma_async.sync.aligned.m64n40k16.f32.bf16.bf16 {%0,%1,%2,%3,%4,%5,%6,%7,%8,%9,%10,%11,%12,%13,%14,%15,%16,%17,%18,%19}, %20, %21, p, 1, 1, %23, %24;}"
               : ACC20(d) : "l"(da), "l"(db), "r"(sc), "n"(TA), "n"(TB));
}
DI void wg_rs40(float* d, uint32_t a0, uint32_t a1, uint32_t a2, uint32_t a3, uint64_t db, int sc) {
  asm volatile("{.reg .pred p; setp.ne.b32 p, %25, 0;\n"
               "wgmma.mma_async.sync.aligned.m64n40k16.f32.bf16.bf16 {%0,%1,%2,%3,%4,%5,%6,%7,%8,%9,%10,%11,%12,%13,%14,%15,%16,%17,%18,%19}, {%20,%21,%22,%23}, %24, p, 1, 1, 0;}"
               : ACC20(d) : "r"(a0), "r"(a1), "r"(a2), "r"(a3), "l"(db), "r"(sc));
}
DI void wg_rs32(float* d, uint32_t a0, uint32_t a1, uint32_t a2, uint32_t a3, uint64_t db, int sc) {
  asm volatile("{.reg .pred p; setp.ne.b32 p, %21, 0;\n"
               "wgmma.mma_async.sync.aligned.m64n32k16.f32.bf16.bf16 {%0,%1,%2,%3,%4,%5,%6,%7,%8,%9,%10,%11,%12,%13,%14,%15}, {%16,%17,%18,%19}, %20, p, 1, 1, 0;}"
               : ACC16(d, 0) : "r"(a0), "r"(a1), "r"(a2), "r"(a3), "l"(db), "r"(sc));
}
DI void wg_ss32k(float* d, uint64_t da, uint64_t db, int sc) {
  asm volatile("{.reg .pred p; setp.ne.b32 p, %18, 0;\n"
               "wgmma.mma_async.sync.aligned.m64n32k16.f32.bf16.bf16 {%0,%1,%2,%3,%4,%5,%6,%7,%8,%9,%10,%11,%12,%13,%14,%15}, %16, %17, p, 1, 1, 1, 0;}"
               : ACC16(d, 0) : "l"(da), "l"(db), "r"(sc));
}
DI void wg_ss8k(float* d, uint64_t da, uint64_t db, int sc) {
  asm volatile("{.reg .pred p; setp.ne.b32 p, %6, 0;\n"
               "wgmma.mma_async.sync.aligned.m64n8k16.f32.bf16.bf16 {%0,%1,%2,%3}, %4, %5, p, 1, 1, 1, 0;}"
               : ACC4(d, 0) : "l"(da), "l"(db), "r"(sc));
}
DI void wg_rs8(float* d, uint32_t a0, uint32_t a1, uint32_t a2, uint32_t a3, uint64_t db, int sc) {
  asm volatile("{.reg .pred p; setp.ne.b32 p, %9, 0;\n"
               "wgmma.mma_async.sync.aligned.m64n8k16.f32.bf16.bf16 {%0,%1,%2,%3}, {%4,%5,%6,%7}, %8, p, 1, 1, 0;}"
               : ACC4(d, 0) : "r"(a0), "r"(a1), "r"(a2), "r"(a3), "l"(db), "r"(sc));
}
DI void mma16816(float* c, const uint32_t* a, uint32_t b0, uint32_t b1) {
  asm volatile("mma.sync.aligned.m16n8k16.row.col.f32.bf16.bf16.f32 {%0,%1,%2,%3}, {%4,%5,%6,%7}, {%8,%9}, {%0,%1,%2,%3};"
               : ACC4(c, 0) : "r"(a[0]), "r"(a[1]), "r"(a[2]), "r"(a[3]), "r"(b0), "r"(b1));
}
DI void wg_ss8(float* d, uint64_t da, uint64_t db, int sc) {
  asm volatile("{.reg .pred p; setp.ne.b32 p, %6, 0;\n"
               "wgmma.mma_async.sync.aligned.m64n8k16.f32.bf16.bf16 {%0,%1,%2,%3}, %4, %5, p, 1, 1, 1, 1;}"
               : ACC4(d, 0) : "l"(da), "l"(db), "r"(sc));
}
__device__ __align__(4096) uint4 g_xn[2 * NSEG * 10 * 256];
__device__ __align__(4096) uint4 g_oT[2 * NBLK * 96 * 1024];
constexpr int PART_RING = 96 * 256;
__device__ __align__(4096) uint4 g_part[4 * PART_RING];
#define P4 ~0u, ~0u, ~0u, ~0u
#define P16 P4, P4, P4, P4
#define P256 P16, P16, P16, P16, P16, P16, P16, P16, P16, P16, P16, P16, P16, P16, P16, P16
#define P2K P256, P256, P256, P256, P256, P256, P256, P256
#define P8K P2K, P2K, P2K, P2K
__device__ __align__(8192) uint32_t g_mem32[5 * 2 * 2 * 2048] = {P8K, P8K, P8K, P8K, P8K};
#define g_mem ((uint4*)g_mem32)
constexpr int C_XN = 0;
constexpr int C_O = C_XN + 2 * NBLK;
constexpr int C_HALF = C_O + 6 * 2 * NBLK;
constexpr int C_TOTAL = 512;
constexpr int CSTRIDE = 32;
__device__ __align__(4096) uint32_t g_cnt[C_TOTAL * CSTRIDE];
constexpr uint32_t XN_TARGET = 128;

#define TRACE(c, n, i, v)
#define SLOG(i)
#define PROF(i)
#define PROFA(c)
#define PROFV(i, v)

constexpr uint32_t SMEM0 = 1024;
constexpr uint32_t SM_WK = 0, SM_WO = 81920, SM_H = 163840, SM_QT = 215040, QSTR = 1056  , SM_KT = SM_QT + 5 * QSTR + 1024,
                   SM_SR = SM_KT + 5120  , SM_PROF = SM_SR + 5760, R_SMEM = 232448,
                   SM_RED = SM_QT + 1024, SM_BAR = SM_RED + 768;
constexpr uint32_t SM_P = SM_KT, SM_OB = SM_QT + 3200;
constexpr uint32_t B_HFULL = SM_BAR, B_HEMPTY = SM_BAR + 40, B_MTRY = SM_BAR + 80, B_W = SM_BAR + 112, B_SR = B_W + 32,
                   B_PMEM = B_SR + 24, B_PTOK = B_SR + 32, B_OB = B_SR + 40, B_OPD = B_SR + 48, B_RFREE = B_SR + 56,
                   B_GATE = B_SR + 64, B_PSUM = B_SR + 72, B_END = B_SR + 80, B_TOK = B_SR + 88,
                   B_OPI = B_SR + 96, B_OTOK = B_SR + 112, SM_TOPI = B_SR + 128, B_PACE = SM_TOPI + 8,
                   SM_RS = SM_QT + 2 * QSTR + 1024;
static_assert(B_PACE + 32 <= SM_QT + 2 * QSTR, "barriers must fit the unused q row group");

struct RParams {
  uint64_t dH, dHt, dWK, dWO, dQT, dKT, dP, dOB[6];
  const uint4* mem0;
  const uint32_t* x;
  int pf;
  int nslots, d3, pn, moff, ds, dh, dq;
  int d2[10], d1[8];
  uint32_t slot[2 * NSEG];
};
static void r_fill_desc(RParams& p) {
  p.dH = mkdesc(SMEM0 + SM_H, 128, 2048, 0);
  p.dHt = mkdesc(SMEM0 + SM_H + 2048, 128, 2048, 0);
  p.dWK = mkdesc(SMEM0 + SM_WK, 1024, 1024, 1);
  p.dWO = mkdesc(SMEM0 + SM_WO, 1024, 1024, 1);
  for (int i = 0; i < 6; i++) p.dOB[i] = mkdesc(SMEM0 + SM_OB + (i < 3 ? 0 : (i - 3) * 1024), 128, 128, 0);
  p.dQT = mkdesc(SMEM0 + SM_QT, 128, QSTR, 0);
  p.dKT = mkdesc(SMEM0 + SM_KT, 128, 1024, 0);
  p.dP = mkdesc(SMEM0 + SM_P, 128, 640, 0);
}
DI uint64_t dadd(uint64_t d, int bytes) {
  uint64_t r;
  asm volatile("add.u64 %0, %1, %2;" : "=l"(r) : "l"(d), "l"((long long)(bytes / 16)));
  return r;
}
template <int BYTES> DI void dstep(uint64_t& d) { asm volatile("add.u64 %0, %0, %1;" : "+l"(d) : "n"((long long)(BYTES / 16))); }
__host__ __device__ constexpr int hoff(int ks) { return (ks >> 3) * 10240 + (ks & 7) * 256; }

DI int opaque(int v) { asm volatile("" : "+r"(v)); return v; }
DI uint32_t pin(uint32_t v, int lane) { return __shfl_sync(~0u, v + (lane >> 5), lane); }
DI char* pin(char* p, int lane) { return (char*)__shfl_sync(~0u, (unsigned long long)p, lane); }
DI float blo(uint32_t w) { return __uint_as_float(w << 16); }
DI float bhi(uint32_t w) { return __uint_as_float(w & 0xffff0000u); }
#define RG0 232
#define RG1 216
#define RG2 40
#define RG3 24
DI void ldsm4t(uint32_t* r, uint32_t a) {
  asm volatile("ldmatrix.sync.aligned.m8n8.x4.trans.shared.b16 {%0,%1,%2,%3}, [%4];" : "=r"(r[0]), "=r"(r[1]), "=r"(r[2]), "=r"(r[3]) : "r"(a) : "memory");
}
DI void st_tagged(void* p, float a, float b, uint32_t keep, uint32_t tagbit) {
  asm volatile("{.reg .b32 t; cvt.rn.bf16x2.f32 t, %2, %1; lop3.b32 t, t, %3, %4, 0xea; st.relaxed.gpu.global.b32 [%0], t;}" ::"l"(p), "f"(a), "f"(b),
               "r"(keep), "r"(tagbit) : "memory");
}
DI uint32_t lop_bad(uint32_t a, uint32_t b, uint32_t m) { uint32_t d; asm("lop3.b32 %0, %1, %2, %3, 0x7e;" : "=r"(d) : "r"(a), "r"(b), "r"(m)); return d; }
DI uint32_t lop_or3(uint32_t a, uint32_t b, uint32_t c) { uint32_t d; asm("lop3.b32 %0, %1, %2, %3, 0xfe;" : "=r"(d) : "r"(a), "r"(b), "r"(c)); return d; }
DI uint32_t clk() { uint32_t t; asm volatile("mov.u32 %0, %%clock;" : "=r"(t)); return t; }
DI void spin(uint32_t cyc) { const uint32_t t0 = clk(); while (__any_sync(~0u, clk() - t0 < cyc)) {} }
template <int NL> DI float2 poll_sum(const uint32_t* src, uint32_t tag, uint32_t even, uint32_t& g) {
  uint32_t r[NL];
  while (true) {
#pragma unroll
    for (int i = 0; i < NL; i++) r[i] = ld_rlx(src + i * 32);
    uint32_t bad = lop_or3(lop_bad(r[0], r[1], tag), lop_bad(r[2], r[3], tag), lop_bad(r[4], r[5], tag));
    if (NL == 12) bad = lop_or3(bad, lop_bad(r[6], r[7], tag), lop_bad(r[8], r[9], tag));
    asm volatile("lop3.b32 %0, %0, %1, %2, 0xa8;" : "+r"(bad) : "r"(lop_bad(r[NL - 2], r[NL - 1], tag)), "r"(even));
    if (!__any_sync(~0u, bad)) break;
    g++;
  }
  float x[NL / 2], y[NL / 2];
#pragma unroll
  for (int i = 0; i < NL / 2; i++) { x[i] = blo(r[2 * i]) + blo(r[2 * i + 1]); y[i] = bhi(r[2 * i]) + bhi(r[2 * i + 1]); }
  float2 u = make_float2((x[0] + x[1]) + (x[2] + x[3]), (y[0] + y[1]) + (y[2] + y[3]));
  if (NL == 12) { u.x += x[4] + x[5]; u.y += y[4] + y[5]; }
  return u;
}

constexpr int PLANE = 16 * 40 * 32, MAXPL = 9;
__device__ __align__(4096) uint2 g_acc[(size_t)2 * NBLK * 2 * MAXPL * PLANE];
DI uint2* acc_planes(int lb, int d) { return g_acc + (size_t)((lb * 2 + d) * MAXPL) * PLANE; }
DI void ln_stats(const float4* v, uint32_t red, int warp, int lane, int bar, float& mean, float& rstd) {
  float s = 0.f;
#pragma unroll
  for (int i = 0; i < 5; i++) s += (v[i].x + v[i].y) + (v[i].z + v[i].w);
  s += __shfl_xor_sync(~0u, s, 1);
  s += __shfl_xor_sync(~0u, s, 2);
  s *= 1.f / 80;
  float q = 0.f;
#pragma unroll
  for (int i = 0; i < 5; i++) q += ((v[i].x - s) * (v[i].x - s) + (v[i].y - s) * (v[i].y - s)) + ((v[i].z - s) * (v[i].z - s) + (v[i].w - s) * (v[i].w - s));
  q += __shfl_xor_sync(~0u, q, 1);
  q += __shfl_xor_sync(~0u, q, 2);
  if ((lane & 3) == 0) asm volatile("st.shared.v2.f32 [%0], {%1,%2};" ::"r"(red + lane * 16 + warp * 8), "f"(s), "f"(q) : "memory");
  bar_sync(bar, 256);
  const uint4 t = lds128(red + lane * 16);
  const float m0 = __uint_as_float(t.x), m1 = __uint_as_float(t.z);
  mean = m0 + m1;
  mean += __shfl_xor_sync(~0u, mean, 1);
  mean += __shfl_xor_sync(~0u, mean, 2);
  mean *= 0.125f;
  q = __uint_as_float(t.y) + __uint_as_float(t.w) + 80.f * ((m0 - mean) * (m0 - mean) + (m1 - mean) * (m1 - mean));
  q += __shfl_xor_sync(~0u, q, 1);
  q += __shfl_xor_sync(~0u, q, 2);
  rstd = rsqrtf(q * (1.f / DM) + 1e-5f);
}
template <int SH, int STR> DI void store_img(uint32_t* dst, const float4* v, int warp, float mean, float rstd) {
#pragma unroll
  for (int i = 0; i < 5; i++) {
    const int U = 10 * warp + 2 * i;
    uint32_t* p = dst + (U >> SH) * STR + (U & ((1 << SH) - 1)) * 32;
    p[0] = pack2((v[i].x - mean) * rstd, (v[i].y - mean) * rstd);
    p[32] = pack2((v[i].z - mean) * rstd, (v[i].w - mean) * rstd);
  }
}
DI uint32_t* xn_row_group(int layer, int rg) { return (uint32_t*)(g_xn + (size_t)((layer * NSEG + (rg >> 2)) * 2560 + (rg & 3) * 128)); }

DI void first_ln(const uint32_t* a, int rg, uint32_t red, int warp, int lane, int bar) {
  float4 v[5];
#pragma unroll
  for (int i = 0; i < 5; i++) {
    v[i] = make_float4(blo(a[2 * i]), bhi(a[2 * i]), blo(a[2 * i + 1]), bhi(a[2 * i + 1]));
    acc_planes(rg >> 4, 0)[((rg & 15) * 40 + warp * 5 + i) * 32 + lane] = make_uint2(a[2 * i], a[2 * i + 1]);
  }
  float mean, rstd;
  ln_stats(v, red, warp, lane, bar, mean, rstd);
  store_img<4, 2048>(xn_row_group(0, rg) + lane, v, warp, mean, rstd);
}
#define QK_P0 32
#define QK_KB 0
struct QKOrder { int op[76]; };
__host__ __device__ constexpr QKOrder qk_order() {
  QKOrder o = {};
  int n = 0, k = 0, q = 0;
  for (; k < QK_P0; k++, q++) { o.op[n++] = 64 | k; o.op[n++] = q; }
  for (int i = 0; i < QK_KB; i++) o.op[n++] = 64 | k++;
  for (int i = 0; i < -QK_KB; i++) o.op[n++] = q++;
  const int nk = 40 - k, nq = 36 - q;
  for (int i = 0, dk = 0, dq = 0; i < nk + nq; i++) {
    if (dq * nk <= dk * nq + (QK_KB ? 0 : -nq) && dq < nq) { o.op[n++] = q++; dq++; } else if (dk < nk) { o.op[n++] = 64 | k++; dk++; } else { o.op[n++] = q++; dq++; }
  }
  return o;
}
__global__ void __launch_bounds__(512, 1)
r_kernel(const __grid_constant__ CUtensorMap mapWq, const __grid_constant__ CUtensorMap mapWk, const __grid_constant__ CUtensorMap mapWv,
         const __grid_constant__ CUtensorMap mapWo, const __grid_constant__ RParams prm) {
  const uint32_t sb = smem_base();
  const int wid = __shfl_sync(~0u, threadIdx.x >> 5, 0);
  const int lane0 = __shfl_sync(~0u, threadIdx.x & 31, threadIdx.x & 31);
  const int lane = lane0;
  const int warp = wid & 3, wg = wid >> 2;
  const uint32_t rank = blockIdx.x, head = blockIdx.y, cta = head * 3 + rank;
  const uint32_t peer1 = mapa(sb, rank == 2 ? 0 : rank + 1), peer2 = mapa(sb, rank == 0 ? 2 : rank - 1);
  const int nslots = prm.nslots;

  SLOG(0);
  if (threadIdx.x == 384) {
    if ((sb & 0x3FFFF) != SMEM0) __trap();
    for (int c = 0; c < 5; c++) { mbar_init(sb + B_HFULL + 8 * c, 2); mbar_init(sb + B_HEMPTY + 8 * c, c == 4 ? 8 : 4); }
    for (int c = 0; c < 11; c++) mbar_init(sb + B_MTRY + 8 * c, 1);
    mbar_init(sb + B_PTOK, rank == 0 ? 3 : 2); mbar_init(sb + B_OB, 5); mbar_init(sb + B_OPD, 4);
    mbar_init(sb + B_OPI, 1); mbar_init(sb + B_OPI + 8, 1); mbar_init(sb + B_RFREE, 1); mbar_init(sb + B_GATE, 1); mbar_init(sb + B_PMEM, 2); mbar_init(sb + B_PSUM, 2); mbar_init(sb + B_TOK, 5); mbar_init(sb + B_OTOK, 4); mbar_init(sb + B_OTOK + 8, 4); mbar_init(sb + B_END, 15);
    for (int c = 0; c < 4; c++) mbar_init(sb + B_PACE + 8 * c, 1);
    asm volatile("fence.mbarrier_init.release.cluster;" ::: "memory");
    fence_async_smem();
  }
  asm volatile("griddepcontrol.launch_dependents;");
  asm volatile("barrier.cluster.arrive.release.aligned;" ::: "memory");

  if (wg < 2) {
  {
    uint32_t xa[10];
    const uint32_t* src = prm.x + (size_t)(cta * 8 + (lane >> 2)) * (DM / 2) + wid * 40 + (lane & 3);
#pragma unroll
    for (int i = 0; i < 10; i++) xa[i] = __ldg(src + i * 4);
    asm volatile("barrier.cluster.wait.acquire.aligned;" ::: "memory");
    first_ln(xa, cta, sb + SM_SR, wid, lane, 8);
    bar_arrive(10, 288);
  }
  if (wg == 0) {
    asm volatile("setmaxnreg.inc.sync.aligned.u32 %0;" ::"n"(RG0));
    uint32_t wq[160];
    SLOG(1);
    mbar_wait(sb + B_W, 0);
    SLOG(2);
    {
      const uint32_t ld_off = ((lane >> 4) * 8 + (lane & 7)) * 128 + (((2 * warp + ((lane >> 3) & 1)) ^ (lane & 7)) << 4);
#pragma unroll
      for (int ks = 0; ks < 40; ks++) ldsm4t(wq + 4 * ks, sb + SM_WO + ks * 2048 + ld_off);
    }
    fence_async_smem();
    bar_arrive(5, 160);
    mbar_wait(sb + B_W + 16, 0);
    SLOG(3);
    const uint32_t st_addr = pin(sb + SM_QT + (lane >> 4) * 1024 + (2 * warp + ((lane >> 3) & 1)) * 128 + (lane & 7) * 16, lane);
    const uint32_t sq_addr = pin(sb + SM_QT + (2 + (lane & 3)) * QSTR + warp * 256 + (lane >> 2) * 16, lane);
    const uint32_t to_lo = warp == 0 ? peer1 : mapa(sb, warp == 2 ? 2 : 0), to_hi = warp == 0 ? peer2 : mapa(sb, warp == 1 ? 1 : 0);
    const uint32_t sr_off = SM_SR + warp * 1920 + rank * 640, sr_bar = B_SR + warp * 8;
    const uint32_t sa0 = pin(to_lo + sr_off + lane * 16, lane), sb0 = pin(to_lo + sr_bar, lane), sa1 = pin(to_lo + sr_off + 512 + lane * 4, lane), sb1 = pin(sb0, lane);
    const uint32_t sa2 = pin(to_hi + sr_off + lane * 16, lane), sb2 = pin(to_hi + sr_bar, lane), sa3 = pin(to_hi + sr_off + 512 + lane * 4, lane), sb3 = pin(sb2, lane);
    uint32_t nsolo = 0;
#pragma unroll 1
    for (int n = 0; n < nslots; n++) {
      const uint32_t par = n & 1;
      PROFA(warp == PW);
      const bool alt = prm.slot[n] & 128;
      auto next = [&](uint64_t& d, int ks) { if ((ks & 7) == 7) dstep<10240 - 7 * 256>(d); else dstep<256>(d); };
      auto store_k = [&](const float* ka) {
        stsm2(st_addr + (SM_KT - SM_QT), pack2(ka[0], ka[1]), pack2(ka[2], ka[3]));
        stsm4(st_addr + (SM_KT - SM_QT) + 1024, pack2(ka[4], ka[5]), pack2(ka[6], ka[7]), pack2(ka[8], ka[9]), pack2(ka[10], ka[11]));
        stsm4(st_addr + (SM_KT - SM_QT) + 3072, pack2(ka[12], ka[13]), pack2(ka[14], ka[15]), pack2(ka[16], ka[17]), pack2(ka[18], ka[19]));
      };
      auto store_qt = [&](const float* q) {
        sts128(sq_addr, make_uint4(pack2(q[0], q[1]), pack2(q[4], q[5]), pack2(q[8], q[9]), pack2(q[12], q[13])));
        sts128(sq_addr + 128, make_uint4(pack2(q[2], q[3]), pack2(q[6], q[7]), pack2(q[10], q[11]), pack2(q[14], q[15])));
      };
      if (n > 0 && ((prm.slot[n] >> 8) & 255) == n) {
        {
          float qt[16];
          uint64_t rh = prm.dHt;
          mbar_wait(sb + B_OPI + (par ^ 1) * 8, ((n - 1) >> 1) & 1);
          mbar_wait(sb + B_GATE, 1);
          spin(prm.dq);
          mbar_wait(sb + B_TOK, nsolo++ & 1);
          float kt[16];
          uint64_t rk = prm.dWK;
          wg_fence();
#pragma unroll
          for (int ks = 0; ks < 40; ks++) {
            wg_ss32k(kt, rk, rh, ks != 0);
            wg_rs32(qt, wq[4 * ks], wq[4 * ks + 1], wq[4 * ks + 2], wq[4 * ks + 3], rh, ks != 0);
            if (ks < 39) { dstep<2048>(rk); next(rh, ks); }
          }
          wg_commit();
          mbar_wait(sb + B_OPD, par ^ 1);
          wg_wait<0>();
          reg_fence<16>(qt); reg_fence<16>(kt);
          store_qt(qt);
          stsm4(st_addr + (SM_KT - SM_QT) + 1024, pack2(kt[0], kt[1]), pack2(kt[2], kt[3]), pack2(kt[4], kt[5]), pack2(kt[6], kt[7]));
          stsm4(st_addr + (SM_KT - SM_QT) + 3072, pack2(kt[8], kt[9]), pack2(kt[10], kt[11]), pack2(kt[12], kt[13]), pack2(kt[14], kt[15]));
        }
        float qm[4], km[4];
        uint64_t rk = prm.dWK, rh = prm.dH;
        bool ok = false;
#pragma unroll
        for (int g = 0; g < 20; g++) {
          if ((g & 3) == 0 && !ok) mbar_wait(sb + B_HFULL + 2 * g, par);
          if (g == 0) PROF(0);
          if ((g & 3) == 3 && g < 19) ok = mbar_test(sb + B_HFULL + 2 * (g + 1), par);
          if ((g & 3) == 0) wg_fence();
#pragma unroll
          for (int ks = 2 * g; ks < 2 * g + 2; ks++) {
            wg_ss8k(km, rk, rh, ks != 0);
            wg_rs8(qm, wq[4 * ks], wq[4 * ks + 1], wq[4 * ks + 2], wq[4 * ks + 3], rh, ks != 0);
            if (ks < 39) { dstep<2048>(rk); next(rh, ks); }
          }
          if (g == 18) wg_commit();
        }
        wg_commit();
        wg_wait<1>();
        bar_arrive(2, 256);
        wg_wait<0>();
        reg_fence<4>(qm); reg_fence<4>(km);
        PROF(9);
        stsm2(st_addr + (SM_KT - SM_QT), pack2(km[0], km[1]), pack2(km[2], km[3]));
        stsm2(st_addr, pack2(qm[0], qm[1]), pack2(qm[2], qm[3]));
      } else {
      float qa[20], ka[20];
      uint64_t rk = prm.dWK, rh = prm.dH, rq;
      auto K = [&](int ks) { wg_ss40<1, 0>(ka, rk, rh, ks != 0); };
      auto Q = [&](int ks, uint64_t db) { wg_rs40(qa, wq[4 * ks], wq[4 * ks + 1], wq[4 * ks + 2], wq[4 * ks + 3], db, ks != 0); };
      constexpr QKOrder ord = qk_order();
      auto first = [&](int g, int c) { for (int i = 0; i < 76; i++) if ((ord.op[i] & 63) >> 3 == c) return i >> 2 == g; return false; };
      bool ok = true;
      mbar_wait(sb + B_HFULL, par);
#pragma unroll
      for (int g = 0; g < 19; g++) {
        if (!ok) {
#pragma unroll
          for (int c = 1; c < 5; c++) if (first(g, c)) mbar_wait(sb + B_HFULL + 8 * c, par);
          mbar_wait(sb + B_GATE, 1);
        }
        if (g == 0) PROF(0);
        if (g < 18) ok = mbar_test(sb + B_GATE, 1);
#pragma unroll
        for (int c = 1; c < 5; c++) if (first(g + 1, c)) ok &= mbar_test(sb + B_HFULL + 8 * c, par);
        wg_fence();
#pragma unroll
        for (int i = 4 * g; i < 4 * g + 4; i++) {
          const int ks = ord.op[i] & 63;
          if (i < 2 * QK_P0) {
            if (ord.op[i] & 64) K(ks);
            else { Q(ks, rh); dstep<2048>(rk); next(rh, ks); if (i == 2 * QK_P0 - 1) rq = rh; }
          } else if (ord.op[i] & 64) { K(ks); if (ks < 39) { dstep<2048>(rk); next(rh, ks); } }
          else { Q(ks, rq); next(rq, ks); }
        }
        if (g == 17) wg_commit();
      }
      wg_commit();
#pragma unroll
      for (int ks = 36; ks < 40; ks++) { Q(ks, rq); if (ks < 39) dstep<256>(rq); }
      wg_commit();
      wg_wait<2>();
      if (alt) bar_arrive(2, 256);
      mbar_wait(sb + B_OPD, par ^ 1);
      wg_wait<1>();
      if (!alt) bar_arrive(2, 256);
      reg_fence<20>(ka);
      store_k(ka);
      wg_wait<0>();
      reg_fence<20>(qa);
      PROF(9);
      stsm2(st_addr, pack2(qa[0], qa[1]), pack2(qa[2], qa[3]));
      store_qt(qa + 4);
      }
      mbar_arrive_if(lane == 0, sb + B_HEMPTY + 32);
      fence_async_smem();
      bar_sync(1, 128);
      PROF(1);
      float qa[20];
      wg_fence();
#pragma unroll
      for (int k = 0; k < 4; k++) wg_ss40<1, 1>(qa, dadd(prm.dQT, k * 256), dadd(prm.dKT, k * 256), k != 0);
      wg_commit();
      bar_arrive(7, 256);
      wg_wait<0>();
      reg_fence<20>(qa);
      PROF(3);
      if (warp < 3) {
        uint32_t p[5];
#pragma unroll
        for (int j = 0; j < 5; j++) p[j] = pack2(qa[4 * j], qa[4 * j + 1]);
        if (warp == 0) {
          st_async4(sa0, p[0], p[1], p[2], p[3], sb0);
          st_async4(sa2, p[0], p[1], p[2], p[3], sb2);
          st_async1(sa1, p[4], sb1);
          st_async1(sa3, p[4], sb3);
          sts128(sb + sr_off + lane * 16, make_uint4(p[0], p[1], p[2], p[3]));
          sts32(sb + sr_off + 512 + lane * 4, p[4]);
          __syncwarp();
          mbar_expect_if(lane == 0, sb + B_SR, 1280);
        } else {
          uint32_t h[5];
#pragma unroll
          for (int j = 0; j < 5; j++) h[j] = pack2(qa[4 * j + 2], qa[4 * j + 3]);
          spin(prm.d3);
          st_async4(sa0, p[0], p[1], p[2], p[3], sb0);
          st_async4(sa2, h[0], h[1], h[2], h[3], sb2);
          st_async1(sa1, p[4], sb1);
          st_async1(sa3, h[4], sb3);
        }
      }
    }
  } else {
    asm volatile("setmaxnreg.inc.sync.aligned.u32 %0;" ::"n"(RG1));
    uint32_t wv[160];
    mbar_wait(sb + B_W + 8, 0);
    SLOG(4);
    {
      const uint32_t ld_off = ((lane >> 4) * 8 + (lane & 7)) * 128 + (((2 * warp + ((lane >> 3) & 1)) ^ (lane & 7)) << 4);
#pragma unroll
      for (int ks = 0; ks < 40; ks++) ldsm4t(wv + 4 * ks, sb + SM_WO + ks * 2048 + ld_off);
    }
    fence_async_smem();
    bar_arrive(6, 160);
    const uint64_t dH = prm.dH;
    uint32_t op[8];
    const uint32_t ob_off = SM_OB + (4 * rank + warp) * 256 + lane * 4;
    const uint32_t oa0 = pin(peer1 + ob_off, lane), ob0 = pin(peer1 + B_OB, lane), oa1 = pin(peer2 + ob_off, lane), ob1 = pin(peer2 + B_OB, lane);
    const uint32_t oa2 = pin(oa0 + 128, lane), ob2 = pin(ob0, lane), oa3 = pin(oa1 + 128, lane), ob3 = pin(ob1, lane);
    const uint32_t o_loc = pin(sb + ob_off, lane), rs_addr = pin(sb + SM_RS + (lane & 3) * 8, lane);
    const uint32_t tok_off = pin((cta * 1024 + 64 * warp + (lane ^ (lane >> 3))) * 16, lane), keep = pin((lane & 1) ? ~0u : ~1u, lane);
    const uint32_t pb_off = pin((8 * rank + 2 * warp) * 4096 + head * 128 + lane * 4, lane);
    const uint32_t ph_off = pin(72 * 4096 + 2 * warp * 12288 + cta * 64 + (lane & 2) * 3072 + (lane >> 2) * 8 + (lane & 1) * 4, lane);
    auto store_tok = [&](int m, int lane) {
      const uint32_t ls = prm.slot[m] & 127, sig = prm.slot[m] >> 16;
      uint4* dst = (uint4*)((char*)(g_oT + (size_t)((ls >> 2) * (96 * 1024) + (ls & 3) * 256)) + tok_off);
      dst[0] = make_uint4(op[0], op[1], op[2], op[3]);
      dst[32] = make_uint4(op[4], op[5], op[6], op[7]);
      __syncwarp();
      mbar_arrive_if(sig && lane == 0, sb + B_OTOK + (ls >> 6) * 8);
    };
#pragma unroll 1
    for (int n = 0; n < nslots; n++) {
      const uint32_t par = n & 1;
      const int lane = opaque(lane0);
      PROFA(warp == PW);
      float va[20];
      const bool alt = prm.slot[n] & 128;
      mbar_expect_if(warp == 0 && lane == 0, sb + B_PTOK, rank == 0 ? 1280 : 1920);
      bar_sync(2, 256);
#pragma unroll
      for (int g = 0; g < 10; g++) {
        wg_fence();
#pragma unroll
        for (int ks = 4 * g; ks < 4 * g + 4; ks++) { wg_rs40(va, wv[4 * ks], wv[4 * ks + 1], wv[4 * ks + 2], wv[4 * ks + 3], dadd(dH, hoff(ks)), ks != 0); }
        wg_commit();
        if (g >= 2 && !(g & 1)) {
          wg_wait<1>();
          if (lane == 0) mbar_arrive(sb + B_HEMPTY + 8 * (g / 2 - 1));
        }
        if (g == 1 ? !alt : g == 2 && alt) bar_sync(7, 256);
      }
      wg_wait<0>();
      reg_fence<20>(va);
      if (lane == 0) mbar_arrive(sb + B_HEMPTY + 32);
      PROF(10);
      uint32_t vf[10];
#pragma unroll
      for (int j = 0; j < 10; j++) {
        const int i = (j + 4) % 10;
        asm volatile("cvt.rn.bf16x2.f32 %0, %1, %2;" : "=r"(vf[i]) : "f"(va[2 * i + 1]), "f"(va[2 * i]));
        if (j == 5) mbar_wait(sb + B_W + 8, 0);
      }
      uint32_t z0, z1;
      asm volatile("shr.u32 %0, %2, 5; shr.u32 %1, %2, 6;" : "=r"(z0), "=r"(z1) : "r"(lane));
      const uint32_t info = prm.slot[n];
      const uint32_t tagbit = ~(info >> 1) & ~keep;
      char* const ring = (char*)(g_part + (size_t)((((info >> 5) & 2) + (info & 1)) * PART_RING));
      char* const pb = pin(ring + pb_off, lane);
      char* const ph = ring + ph_off;
      mbar_wait(sb + B_PMEM, par);
      float om[4];
      wg_fence();
      wg_rs8(om, vf[0], vf[1], vf[2], vf[3], prm.dP, 0);
      wg_rs8(om, vf[4], vf[5], vf[6], vf[7], dadd(prm.dP, 256), 1);
      wg_rs8(om, vf[8], vf[9], z0, z1, dadd(prm.dP, 512 - (128 << 16)), 1);
      wg_commit();
      {
        wg_wait<0>();
        reg_fence<4>(om);
        const uint32_t b0 = pack2(om[0], om[1]), b1 = pack2(om[2], om[3]);
        st_async1(oa0, b0, ob0);
        st_async1(oa1, b0, ob1);
        st_async1(oa2, b1, ob2);
        st_async1(oa3, b1, ob3);
        sts32(o_loc, b0);
        sts32(o_loc + 128, b1);
        fence_async_smem();
        __syncwarp();
        mbar_arrive_if(lane == 0, sb + B_OB);
      }
      PROF(11);
      {
        float c[8];
        mbar_wait(sb + B_PSUM, par);
        const uint2 rs = lds64(rs_addr);
        const float r0 = __uint_as_float(rs.x), r1 = __uint_as_float(rs.y);
        if (n == 0) { SLOG(5); mbar_wait(sb + B_W + 24, 0); SLOG(6); }
        mbar_wait(sb + B_OB, par);
        asm volatile("fence.proxy.async::generic.acquire.sync_restrict::shared::cluster.cluster;" ::: "memory");
        PROF(16);
        if ((info & 63) == NSEG - 1) {
          mbar_wait(sb + B_OPI + par * 8, (n >> 1) & 1);
          mbar_arrive_if(warp == 3 && lane == 0, sb + B_GATE);
#pragma unroll
          for (int p = 0; p < 6; p++) st_rlx1(pb + (p >> 1) * 98304 + (p & 1) * 4096, tagbit);
          st_rlx1(ph, tagbit);
          st_rlx1(ph + 12288, tagbit);
        } else {
#pragma unroll
        for (int p = 0; p < 4; p++) {
          float* const cur = c + 4 * (p & 1);
          float* const prv = c + 4 * (~p & 1);
          if (p == 2) mbar_wait(sb + B_OPI + par * 8, (n >> 1) & 1);
          wg_fence();
#pragma unroll
          for (int ks = 0; ks < (p < 3 ? 12 : 4); ks++) {
            wg_ss8(cur, dadd(prm.dWO, p * 24576 + ks * 2048), dadd(prm.dOB[p < 3 ? p : 3 + rank], ks * 256), ks != 0);
            if (p == 3 && ks == 3) mbar_arrive_if(warp == 3 && lane == 0, sb + B_GATE);
            if (p > 0 && ks == 3) {
              wg_commit();
              wg_wait<1>();
              reg_fence<4>(prv);
              st_tagged(pb + (p - 1) * 98304, prv[0] * r0, prv[1] * r1, keep, tagbit);
              st_tagged(pb + (p - 1) * 98304 + 4096, prv[2] * r0, prv[3] * r1, keep, tagbit);
            }
          }
          if (p < 3) wg_commit();
        }
        wg_wait<0>();
        reg_fence<4>(c + 4);
        st_tagged(ph, c[4] * r0, c[5] * r1, keep, tagbit);
        st_tagged(ph + 12288, c[6] * r0, c[7] * r1, keep, tagbit);
        }
        PROF(17);
      }
      mbar_wait(sb + B_PTOK, par);
      PROF(12);
      {
        float ot[16];
        wg_fence();
        wg_rs32(ot, vf[0], vf[1], vf[2], vf[3], dadd(prm.dP, 640), 0);
        wg_rs32(ot, vf[4], vf[5], vf[6], vf[7], dadd(prm.dP, 640 + 256), 1);
        wg_rs32(ot, vf[8], vf[9], z0, z1, dadd(prm.dP, 640 + 512 - (128 << 16)), 1);
        wg_commit();
        wg_wait<0>();
        reg_fence<16>(ot);
#pragma unroll
        for (int i = 0; i < 8; i++) op[(i & 1) * 4 + (i >> 1)] = pack2(ot[2 * i], ot[2 * i + 1]);
      }
      if (lane == 0) mbar_arrive(sb + B_OPD);
      PROF(13);
      if (info & 128) spin(prm.ds);
      store_tok(n, lane);
    }
  }
  } else if (wg == 2) {
    asm volatile("setmaxnreg.dec.sync.aligned.u32 %0;" ::"n"(RG2));
    asm volatile("barrier.cluster.wait.acquire.aligned;" ::: "memory");
    if (warp == 1) {
      const uint32_t depth = prm.pf;
#pragma unroll 1
      for (uint32_t i = 0; i < 20 + depth; i++) {
        if (i >= depth) {
          const uint32_t j = i - depth;
          mbar_wait_wd(sb + B_PACE + 8 * (j & 3), (j >> 2) & 1);
          if (j % 5 == 4) mbar_arrive_if(lane == 0 && (j != 14 || depth == 1), sb + B_W + (j == 4 ? 0 : j == 9 ? 16 : j == 14 ? 8 : 24));
        }
        if (i >= 20) continue;
        const uint32_t m = i / 5, k = i % 5, bar = sb + B_PACE + 8 * (i & 3);
        if (i == 10) bar_sync(5, 160);
        if (i == 15) {
#pragma unroll 1
          for (uint32_t j = 16 - depth; j < 15; j++) mbar_wait_wd(sb + B_PACE + 8 * (j & 3), (j >> 2) & 1);
          mbar_arrive_if(lane == 0 && depth > 1, sb + B_W + 8);
          bar_sync(6, 160);
        }
        if (elect_one()) {
          mbar_expect(bar, 16384);
          if (m < 3) tma_2d(sb + (m == 1 ? SM_WK : SM_WO) + k * 16384, m == 0 ? &mapWq : m == 1 ? &mapWk : &mapWv, cta * 64, k * 128, bar);
          else
            for (uint32_t q = 2 * k; q < 2 * k + 2; q++)
              tma_2d(sb + SM_WO + q * 8192, &mapWo, q < 9 ? (q / 3 * 3 + rank) * 64 : 576, head * DH + (q < 9 ? q % 3 : rank) * 64, bar);
        }
      }
    }
    if (warp == 2 && cta < 80 && lane < 16)
      g_mem[(cta >> 4) * 2048 + (lane >> 3) * 1024 + prm.moff + (cta & 15) * 8 + (lane & 7)] = prm.mem0[(lane & 7) * 80 + cta];
    if (warp == 3) {
      bar_sync(10, 288);
      if (lane == 0) red_rel(&g_cnt[(C_XN + (cta >> 4)) * CSTRIDE], 8);
    }
    const uint32_t grp = warp == 1 ? 1 + rank : 4 - (rank >> 1);
    constexpr float SC = 0.07216878364870322f * 1.4426950408889634f;
    const bool split = cta >= 72;
    const uint32_t wd = split ? 72 * 16 + cta * 16 : cta * 32;
    const uint32_t src_off = pin(split ? 72 * 4096 + (cta - 72) * 6144 + warp * 1536 + (lane & 2) * 32 + (lane >> 2) * 8 + (lane & 1) * 4 : cta * 4096 + warp * 1024 + lane * 4, lane);
    const uint32_t dst_off = pin(((wd >> 9) * 8192 + prm.moff * 4 + (wd & 511) + lane) * 4, lane);
    const uint32_t red = pin(sb + SM_RED + (warp < 2 ? 0 : (warp - 1) * 256) + lane * 8, lane);
    const uint32_t fl = (warp & 2) * 8 + (lane >> 3) * 4 + (lane & 3), hf = lane & 4;
    const uint32_t s0 = pin(sb + SM_SR + fl * 16 + hf * 2, lane), s1 = pin(sb + fl * 4, lane), pd = pin(s1 + hf * 64, lane);
    const uint32_t even = pin(~lane & 1, lane);
    uint32_t nred = 0;
    const uint32_t arm = pin(lane == 0 && warp != 3 && warp + rank != 3 ? sb + (warp ? B_SR + warp * 8 : B_OB) : 0, lane);
#pragma unroll 1
    for (int n = 0; n < nslots; n++) {
      const uint32_t par = n & 1;
      const int lane = opaque(lane0);
      PROFA(warp == PW2);
      const uint32_t info = prm.slot[n], s = info & 63, l = (info >> 6) & 1;
      {
        mbar_expect_if(arm, arm, warp ? 1920 : 2048);
        if (warp == 0 || warp == 3) {
          mbar_wait(sb + B_SR, par);
          PROF(4);
          const uint2 a0 = lds64(s0), a1 = lds64(s0 + 640), a2 = lds64(s0 + 1280);
          const uint32_t b0 = lds32(s1 + SM_SR + 512), b1 = lds32(s1 + SM_SR + 1152), b2 = lds32(s1 + SM_SR + 1792);
          float v[6];
          v[0] = blo(a0.x) + blo(a1.x) + blo(a2.x); v[1] = bhi(a0.x) + bhi(a1.x) + bhi(a2.x);
          v[2] = blo(a0.y) + blo(a1.y) + blo(a2.y); v[3] = bhi(a0.y) + bhi(a1.y) + bhi(a2.y);
          v[4] = blo(b0) + blo(b1) + blo(b2); v[5] = bhi(b0) + bhi(b1) + bhi(b2);
          float m = fmaxf(fmaxf(v[0], v[1]), fmaxf(v[2], v[3]));
          m = fmaxf(fmaxf(m, __shfl_xor_sync(~0u, m, 4)), fmaxf(v[4], v[5]));
          {
            const float m1 = __shfl_xor_sync(~0u, m, 1), m2 = __shfl_xor_sync(~0u, m, 2), m3 = __shfl_xor_sync(~0u, m, 3);
            m = fmaxf(fmaxf(m, m1), fmaxf(m2, m3));
          }
#pragma unroll
          for (int i = 0; i < 6; i++) v[i] = ex2((v[i] - m) * SC);
          float sum = (v[0] + v[1]) + (v[2] + v[3]);
          const float so = __shfl_xor_sync(~0u, sum, 4);
          sts32(pd + SM_P, pack2(v[0], v[1]));
          sts32(pd + SM_P + 128, pack2(v[2], v[3]));
          sts32(s1 + SM_P + 512, pack2(v[4], v[5]));
          fence_async_smem();
          __syncwarp();
          mbar_arrive_if(lane == 0, sb + B_PMEM);
          PROF(5);
          sum += so + (v[4] + v[5]);
          {
            const float t1 = __shfl_xor_sync(~0u, sum, 1), t2 = __shfl_xor_sync(~0u, sum, 2), t3 = __shfl_xor_sync(~0u, sum, 3);
            sum = (sum + t1) + (t2 + t3);
          }
          float r;
          asm("rcp.approx.ftz.f32 %0, %1;" : "=f"(r) : "f"(sum));
          sts32(sb + SM_RS + (warp & 2) * 8 + (lane >> 3) * 4, __float_as_uint(r));
          __syncwarp();
          mbar_arrive_if(lane == 0, sb + B_PSUM);
        } else {
          if (warp + rank != 3) {
            const uint32_t src = sb + SM_SR + warp * 1920;
            mbar_wait(sb + B_SR + warp * 8, par);
            const uint4 a0 = lds128(src + lane * 16), a1 = lds128(src + 640 + lane * 16), a2 = lds128(src + 1280 + lane * 16);
            const uint32_t b0 = lds32(src + 512 + lane * 4), b1 = lds32(src + 1152 + lane * 4), b2 = lds32(src + 1792 + lane * 4);
            float v[10];
            v[0] = blo(a0.x) + blo(a1.x) + blo(a2.x); v[1] = bhi(a0.x) + bhi(a1.x) + bhi(a2.x);
            v[2] = blo(a0.y) + blo(a1.y) + blo(a2.y); v[3] = bhi(a0.y) + bhi(a1.y) + bhi(a2.y);
            v[4] = blo(a0.z) + blo(a1.z) + blo(a2.z); v[5] = bhi(a0.z) + bhi(a1.z) + bhi(a2.z);
            v[6] = blo(a0.w) + blo(a1.w) + blo(a2.w); v[7] = bhi(a0.w) + bhi(a1.w) + bhi(a2.w);
            v[8] = blo(b0) + blo(b1) + blo(b2); v[9] = bhi(b0) + bhi(b1) + bhi(b2);
            {
              const int lim = 6 + 2 * grp + (lane & 24) + ((lane >> 2) & 1) - 2 * (lane & 3);
#pragma unroll
              for (int i = 2; i < 10; i++) if ((i >> 1) * 8 + (i & 1) > lim) v[i] = -INFINITY;
            }
            float m = fmaxf(fmaxf(fmaxf(v[0], v[1]), fmaxf(v[2], v[3])), fmaxf(fmaxf(v[4], v[5]), fmaxf(v[6], v[7])));
            m = fmaxf(m, fmaxf(v[8], v[9]));
            {
              const float m1 = __shfl_xor_sync(~0u, m, 1), m2 = __shfl_xor_sync(~0u, m, 2), m3 = __shfl_xor_sync(~0u, m, 3);
              m = fmaxf(fmaxf(m, m1), fmaxf(m2, m3));
            }
  #pragma unroll
            for (int i = 0; i < 10; i++) v[i] = ex2((v[i] - m) * SC);
            float sum = ((v[0] + v[1]) + (v[2] + v[3])) + ((v[4] + v[5]) + (v[6] + v[7])) + (v[8] + v[9]);
            {
              const float s1 = __shfl_xor_sync(~0u, sum, 1), s2 = __shfl_xor_sync(~0u, sum, 2), s3 = __shfl_xor_sync(~0u, sum, 3);
              sum = (sum + s1) + (s2 + s3);
            }
            float r;
            asm("rcp.approx.ftz.f32 %0, %1;" : "=f"(r) : "f"(sum));
            {
              const uint32_t row = SM_P + grp * 640;
#pragma unroll
              for (int j = 0; j < 5; j++) sts32(sb + row + j * 128 + lane * 4, pack2(v[2 * j] * r, v[2 * j + 1] * r));
              fence_async_smem();
              __syncwarp();
              mbar_arrive_if(lane == 0, sb + B_PTOK);
              if (elect_one()) {
                bulk_s2s(peer1 + row, sb + row, 640, peer1 + B_PTOK);
                bulk_s2s(peer2 + row, sb + row, 640, peer2 + B_PTOK);
              }
            }
          }
        }
      }
      const uint32_t* const src = (const uint32_t*)((char*)(g_part + (size_t)((l * 2 + (s & 1)) * PART_RING)) + src_off);
      uint32_t* const dst = (uint32_t*)pin((char*)(g_mem + l * 1024 + (~s & 1) * 512) + dst_off, lane);
      {
        const uint32_t d1 = prm.d1[cta / 24 + ((info >> 5) & 4)];
        if (warp == 3) {
          mbar_wait(sb + B_OB, par);
          mbar_arrive_if(lane == 0, sb + B_GATE);
          sts32(sb + SM_TOPI + par * 4, clk());
          __syncwarp();
          mbar_arrive_if(lane == 0, sb + B_OPI + par * 8);
          TRACE(true, n, 0, gtl());
        }
        const bool reduce = cta < 88 && s != NSEG - 1;
        if (reduce || warp == 0) mbar_wait(sb + B_OPI + par * 8, (n >> 1) & 1);
        if (!reduce) continue;
        mbar_wait(sb + B_RFREE, (nred++ & 1) ^ 1);
        mbar_wait(sb + B_GATE, 1);
        if (d1) spin(d1);
      }
      {
        uint32_t g = 0;
        float2 u;
        PROF(14);
        if (!split) {
          u = poll_sum<8>(src, ~(s >> 1), even, g);
        } else {
          u = poll_sum<12>(src, ~(s >> 1), even, g);
          u.x += __shfl_xor_sync(~0u, u.x, 2);
          u.y += __shfl_xor_sync(~0u, u.y, 2);
        }
        PROF(18);
        if (warp != 1) {
          asm volatile("st.shared.v2.f32 [%0], {%1,%2};" ::"r"(red), "f"(u.x), "f"(u.y) : "memory");
          bar_arrive(3, 128);
        } else {
          bar_sync(3, 128);
          const uint2 o0 = lds64(red), o1 = lds64(red + 256), o2 = lds64(red + 512);
          const uint32_t w = movm(pack2((u.x + __uint_as_float(o0.x)) + (__uint_as_float(o1.x) + __uint_as_float(o2.x)),
                                        (u.y + __uint_as_float(o0.y)) + (__uint_as_float(o1.y) + __uint_as_float(o2.y))));
          if (!split || lane < 16) {
            st_rlx1(dst, w);
            st_rlx1(dst + ((s & 1) ? 2048 : -2048), ~0u);
          }
          mbar_arrive_if(lane == 0, sb + B_RFREE);
        }
        PROF(19);
        PROFV(2, g);
        TRACE(warp == 1, n, 1, gtl());
        TRACE(g, n, 2, g);
      }
    }
  } else {
    asm volatile("setmaxnreg.dec.sync.aligned.u32 %0;" ::"n"(RG3));
    asm volatile("barrier.cluster.wait.acquire.aligned;" ::: "memory");
    const uint32_t chk = lane * 32 + ((lane >> 2) << 2);
    const uint32_t bar = sb + B_MTRY + 8 * warp;
    uint32_t mph = 0, waited = 0, pub = 0, pph = 0, nsolo = 0;
    auto publish = [&](uint32_t upto) {
#pragma unroll 1
      for (; pub < upto; pub++) {
        const uint32_t e = prm.slot[pub], l = (e >> 6) & 1;
        if (warp == 3 && (e >> 16)) {
          mbar_wait_wd(sb + B_OTOK + l * 8, (pph >> l) & 1);
          pph ^= 1 << l;
          if (elect_one()) red_rel(&g_cnt[(e >> 16) * CSTRIDE], 1);
        }
      }
    };
#pragma unroll 1
    for (int m = 0; m < nslots; m++) {
      const uint32_t info = prm.slot[m], prod = (info >> 8) & 255, ls = info & 127;
      uint32_t g = 0;
#pragma unroll 1
      for (; waited < prod && waited + 1 < m; waited++) mbar_wait_wd(sb + B_OPI + (waited & 1) * 8, (waited >> 1) & 1);
      uint32_t t0 = lds32(sb + SM_TOPI + (~waited & 1) * 4);
      publish(waited);
      if ((ls & 3) == 0) {
        while (__any_sync(~0u, ld_acq(&g_cnt[(C_XN + (ls >> 2)) * CSTRIDE]) < XN_TARGET)) guard(g);
        fence_async_global();
      }
#pragma unroll 1
      for (uint32_t c = warp; c < 5; c += 4) {
        const uint32_t dst = sb + SM_H + c * 10240, full = sb + B_HFULL + 8 * c;
        const uint4* src = g_mem + (c * 2048 + (ls >> 6) * 1024 + (ls & 1) * 512 + prm.moff);
        const uint32_t d = prod ? prm.d2[(m - prod) * 5 + c] : 0;
        const uint4* tok = g_xn + (size_t)(ls * 2560 + c * 512);
        const uint32_t pp = (m & 1) ^ 1;
        const bool single = waited < prod;
        mbar_wait_wd(full, pp);
        const bool solo = m > 0 && prod == m;
        const uint32_t tokb = solo ? sb + B_TOK : full;
        if (solo && c < 4) mbar_wait_wd(tokb, (nsolo++ & 1) ^ 1);
        mbar_expect_if(lane < 2 && !(solo && c == 4 && lane == 0), lane ? bar : tokb, lane ? 2048 : 8192);
        if (!single) while (__any_sync(~0u, clk() - t0 < d)) {}
        if (c >= 2) mbar_wait_wd(sb + B_HEMPTY + 8 * c, pp);
        mbar_wait_wd(sb + (c < 2 ? B_HEMPTY + 8 * c : c == 2 && !single ? B_PMEM : B_OB), pp);
        if ((c != 2 || single) && !(solo && c == 4)) { if (elect_one()) bulk_g2s(dst + 2048, tok, 8192, tokb); }
        if (single) {
          mbar_wait_wd(sb + B_OPI + (waited & 1) * 8, (waited >> 1) & 1);
          waited++;
          t0 = lds32(sb + SM_TOPI + (~waited & 1) * 4);
          if (solo && c == 0 && elect_one()) {
            mbar_expect(tokb, 8192);
            bulk_g2s(dst + 4 * 10240 + 2048, tok + 2048, 8192, tokb);
          }
          publish(waited);
          while (__any_sync(~0u, clk() - t0 < d)) {}
        }
        else if (c < 2) spin(prm.dh);
        if (elect_one()) bulk_g2s(dst, src, 2048, bar);
        if (c == 2 && !single) {
          mbar_wait_wd(sb + B_OB, pp);
          if (elect_one()) bulk_g2s(dst + 2048, tok, 8192, full);
        }
        g = 0;
        while (true) {
          mbar_wait_wd(bar, mph);
          mph ^= 1;
          const uint32_t v0 = lds32(dst + chk), v1 = lds32(dst + chk + 1024);
          if (__all_sync(~0u, v0 != ~0u && v1 != ~0u)) break;
          if (elect_one()) {
            mbar_expect(bar, 2048);
            bulk_g2s(dst, src, 2048, bar);
          }
          guard(g);
        }
        mbar_arrive_if(lane == 0, full, solo ? 2 : 1);
        TRACE(c < 2, m, 3 + 2 * c, gtl());
        TRACE(c < 2, m, 4 + 2 * c, g);
      }
    }
    publish(nslots);
    if (warp == 0) mbar_wait_wd(sb + B_END, 0);
  }
  __syncwarp();
  if (wid != 12 && lane0 == 0) mbar_arrive(sb + B_END);
  cluster_sync();
}
__device__ __align__(4096) uint32_t g_xa[NBLK * 10 * 4096];
__device__ __align__(4096) uint32_t g_h[NBLK * 24 * 4096];

enum { T_A = 0, T_F1 = 1, T_U = 2, T_D = 3, T_F2 = 4, T_NONE = 7 };
__host__ __device__ constexpr int c_phase(int type, int lb) { return C_O + type * 32 + lb; }
constexpr int C_TICKET = c_phase(5, 0), C_EXIT = C_TICKET + 1, C_USED = C_HALF + 2 * NBLK;
constexpr int G_NST = 7;
constexpr uint32_t GS_RED = G_NST * 32768, GS_BAR = GS_RED + 1088, G_SMEM = GS_BAR + 224;
constexpr uint32_t GB_FULL = GS_BAR, GB_EMPTY = GS_BAR + 64, GB_ORD = GS_BAR + 128, GB_READY = GS_BAR + 144, GB_ACK = GS_BAR + 152, GB_GATE = GS_BAR + 160, GB_SIG = GS_BAR + 176, GB_SACK = GS_BAR + 192,
                   GS_SIG = GS_BAR + 208, GS_COL = GS_BAR + 216;
#define FPL 6
constexpr int NF = 16;
constexpr int G_EARLY = 36;
constexpr int G_LATE = 96, PL = 6, ML = 9, DL = 30, TL = 10;
constexpr int GRC = 112, GRP = 32;
constexpr uint32_t E_UP = 1u << 8, E_HALF = 1u << 28, E_GRP = 1u << 29, E_HAND = 1u << 30, E_EXCL = 1u << 31;

struct GParams {
  __nv_bfloat16* out;
  const uint32_t* x;
  int moff, gd;
  int pend;
  uint8_t perm[G_EARLY], first[9];
  uint8_t need[5][2 * NBLK];
  uint32_t tab[G_EARLY * (PL + ML + DL) + G_LATE * TL];
};
constexpr int EL = PL + ML + DL, TAB_TAIL = G_EARLY * EL;
struct GIter {
  int p, left, period;
  uint32_t e, type, lb, n0, kb0, nkb;
  bool gemm, valid;
  DI GIter(const GParams& prm, int col) {
    if (col < G_EARLY) { p = col * EL; left = PL; period = 0; }
    else { p = TAB_TAIL + (col - G_EARLY) * TL; left = TL; period = prm.pend; }
  }
  DI bool next(const GParams& prm, int col) {
    do {
      if (left == 0) {
        if (++period > prm.pend) return false;
        left = period < prm.pend ? ML : DL;
        if (period > 1 && period < prm.pend) p -= ML;
      }
      e = prm.tab[p++]; left--;
    } while ((e & 7) == T_NONE);
    const int b = (e >> 4) & 15, blk = period < prm.pend ? period - b : b;
    type = e & 7; valid = blk >= 0; lb = (e & 8) * 2 + (blk & 15); n0 = (e >> 9) & 127; kb0 = (e >> 16) & 127;
    gemm = type != T_F1 && type != T_F2;
    nkb = valid ? (e >> 23) & 31 : 0;
    return true;
  }
  DI int id_(int pend) const { return period < pend ? period * 10 + ML - left : 160 + DL - left; }
};

#define GLOG(nt, i, v)
template <int TA> DI void wg_ss128(float* d, uint64_t da, uint64_t db, int sc) {
  asm volatile("{.reg .pred p; setp.ne.b32 p, %66, 0;\n"
               "wgmma.mma_async.sync.aligned.m64n128k16.f32.bf16.bf16 "
               "{%0,%1,%2,%3,%4,%5,%6,%7,%8,%9,%10,%11,%12,%13,%14,%15,%16,%17,%18,%19,%20,%21,%22,%23,%24,%25,%26,%27,%28,%29,%30,%31,"
               "%32,%33,%34,%35,%36,%37,%38,%39,%40,%41,%42,%43,%44,%45,%46,%47,%48,%49,%50,%51,%52,%53,%54,%55,%56,%57,%58,%59,%60,%61,%62,%63}, "
               "%64, %65, p, 1, 1, %67, 1;}"
               : ACC16(d, 0), ACC16(d, 16), ACC16(d, 32), ACC16(d, 48) : "l"(da), "l"(db), "r"(sc), "n"(TA));
}

template <int TA> DI void g_mainloop(float* acc, uint32_t sb, uint32_t hand, uint32_t gate, int nkb, int cw, int lane, uint32_t st, uint32_t ph) {
  const uint64_t da0 = (TA ? mkdesc(SMEM0, 4096, 512, 2) : mkdesc(SMEM0, 128, 1024, 0)) + (cw >> 2) * 512;
  const uint64_t db0 = mkdesc(SMEM0 + 16384, 8192, 1024, 1);
  uint32_t prev = 0;
#pragma unroll 1
  for (int kb = 0; kb < nkb; kb++) {
    mbar_wait(sb + GB_FULL + 8 * st, ph);
    mbar_wait(gate, 1);
    const uint64_t da = da0 + st * 2048, db = db0 + st * 2048;
    wg_fence();
#pragma unroll
    for (int k = 0; k < 4; k++) wg_ss128<TA>(acc, da + k * (TA ? 64 : 16), db + k * 128, 1);
    wg_commit();
    mbar_arrive_if(hand && kb == nkb - 1 && lane == 0, hand);
    wg_wait<1>();
    mbar_arrive_if(kb > 0 && lane == 0, sb + GB_EMPTY + 8 * prev);
    prev = st;
    if (++st == G_NST) { st = 0; ph ^= 1; }
  }
  wg_wait<0>();
  reg_fence<64>(acc);
  mbar_arrive_if(lane == 0, sb + GB_EMPTY + 8 * prev);
}

__global__ void __launch_bounds__(640, 1)
g_kernel(const __grid_constant__ CUtensorMap mapWo, const __grid_constant__ CUtensorMap mapWg, const __grid_constant__ CUtensorMap mapWu,
         const __grid_constant__ CUtensorMap mapWd, const __grid_constant__ GParams prm) {
  const uint32_t sb = smem_base();
  const int wid = __shfl_sync(~0u, threadIdx.x >> 5, 0), lane = threadIdx.x & 31;
  if (threadIdx.x == 0) {
    if ((sb & 0x3FFFF) != SMEM0) __trap();
    {
      uint32_t sm; asm volatile("mov.u32 %0, %%smid;" : "=r"(sm));
      uint32_t* const tk = &g_cnt[C_TICKET * CSTRIDE];
      uint32_t c = atomicAdd(tk, 1);
      if (c < G_EARLY) {
        const uint32_t k = sm < 64 ? (sm >> 1) & 7 : sm < 120 ? 1 + ((sm - 64) >> 1) % 7 : sm < 124 ? 1 + ((sm >> 1) & 1) : 0;
        const uint32_t t = atomicAdd(tk + 1 + k, 1);
        atomicAdd(tk + 9, 1);
        if (t < prm.first[k + 1] - prm.first[k]) c = prm.perm[prm.first[k] + t];
        else {
          uint32_t o = atomicAdd(tk + 10, 1), g = 0;
          while (ld_acq(tk + 9) < G_EARLY) guard(g);
          for (int j = 0; j < 8; j++)
            for (uint32_t i = prm.first[j] + ld_acq(tk + 1 + j); i < prm.first[j + 1]; i++) if (o-- == 0) c = prm.perm[i];
        }
      }
      sts32(sb + GS_COL, c);
    }
    for (int i = 0; i < G_NST; i++) { mbar_init(sb + GB_FULL + 8 * i, 1); mbar_init(sb + GB_EMPTY + 8 * i, 8); }
    mbar_init(sb + GB_ORD, 8); mbar_init(sb + GB_ORD + 8, 8); mbar_init(sb + GB_READY, 1); mbar_init(sb + GB_ACK, 1);
    mbar_init(sb + GB_GATE, 1); mbar_init(sb + GB_GATE + 8, 1);
    mbar_init(sb + GB_SIG, 8); mbar_init(sb + GB_SIG + 8, 8); mbar_init(sb + GB_SACK, 1); mbar_init(sb + GB_SACK + 8, 1);
    fence_async_smem();
  }
  __syncthreads();
  const int col = __shfl_sync(~0u, lds32(sb + GS_COL), 0);

  if (wid >= 16) {
    GIter t(prm, col);
    asm volatile("setmaxnreg.dec.sync.aligned.u32 %0;" ::"n"(GRP));
    uint32_t st = 0, ph = 1, k = 0;
    if (wid == 16) {
      while (t.next(prm, col)) {
        const CUtensorMap* m0 = t.type == T_A ? &mapWo : t.type == T_U ? &mapWg : &mapWd;
        const CUtensorMap* m1 = t.type == T_U ? &mapWu : m0;
        const int c0 = t.type == T_U ? t.n0 * 64 : (t.n0 & 7) * 128, c1 = t.type == T_U ? c0 : c0 + 64;
        if ((t.e & (E_HALF | E_UP)) == E_UP) poll_ge(&g_cnt[c_phase(t.type, t.lb) * CSTRIDE], prm.need[t.type][t.lb]);
#pragma unroll 1
        for (uint32_t kb = t.kb0; kb < t.kb0 + t.nkb; kb++) {
          mbar_wait(sb + GB_EMPTY + 8 * st, ph);
          if (elect_one()) {
            const uint32_t full = sb + GB_FULL + 8 * st, dst = sb + st * 32768;
            mbar_expect(full, (t.e & E_HALF) ? 24576 : 32768);
            tma_2d(dst + 16384, m0, c0, kb * 64, full);
            tma_2d(dst + 24576, m1, c1, kb * 64, full);
          }
          if (++st == G_NST) { st = 0; ph ^= 1; }
        }
      }
    } else if (wid == 17) {
      while (t.next(prm, col)) {
        if (!t.nkb) continue;
        const char* asrc = t.type == T_A ? (const char*)g_oT + (size_t)t.lb * (96 * 16384)
                         : t.type == T_U ? (const char*)g_xa + (size_t)(t.lb & 15) * (10 * 16384) : (const char*)g_h + (size_t)(t.lb & 15) * (24 * 16384);
        const uint32_t up = (t.e & E_HALF) ? (t.e & E_UP) * 32 : 0;
        GLOG(t.id_(prm.pend), 1, gtime());
        mbar_wait(sb + GB_READY, k & 1);
        mbar_arrive_if(lane == 0, sb + GB_ACK);
        k++;
#pragma unroll 1
        for (uint32_t kb = t.kb0; kb < t.kb0 + t.nkb; kb++) {
          mbar_wait(sb + GB_EMPTY + 8 * st, ph);
          if (elect_one()) bulk_g2s(sb + st * 32768 + up, asrc + (size_t)kb * 16384 + up, (t.e & E_HALF) ? 8192 : 16384, sb + GB_FULL + 8 * st);
          if (++st == G_NST) { st = 0; ph ^= 1; }
        }
      }
    } else if (wid == 18) {
      while (t.next(prm, col)) {
        if (!t.nkb) continue;
        const bool lower = t.type == T_A && (t.e & (E_HALF | E_UP)) == E_HALF;
        poll_ge(&g_cnt[(lower ? C_HALF + t.lb : c_phase(t.type, t.lb)) * CSTRIDE], prm.need[t.type][t.lb]);
        fence_async_global();
        GLOG(t.id_(prm.pend), 2, gtime());
        mbar_wait(sb + GB_ACK, (k & 1) ^ 1);
        mbar_arrive_if(lane == 0, sb + GB_READY);
        k++;
      }
    } else {
      uint32_t live = 3, par = 0, g = 0;
      while (live) {
        const bool ev = lane < 2 && ((live >> lane) & 1) && mbar_test(sb + GB_SIG + 8 * lane, (par >> lane) & 1);
        const uint32_t evs = __ballot_sync(~0u, ev);
        if (!evs) { guard(g); __nanosleep(20); continue; }
        const uint32_t msg = ev ? lds32(sb + GS_SIG + 4 * lane) : 0;
        mbar_arrive_if(ev, sb + GB_SACK + 8 * lane);
        mbar_arrive_if(msg >> 31, sb + GB_GATE + 8 * lane);
        if (msg) red_rel(&g_cnt[(msg & 0xffff) * CSTRIDE], (msg >> 16) & 255);
        par ^= evs;
        live &= ~__ballot_sync(~0u, ev && !msg);
        g = 0;
      }
      asm volatile("griddepcontrol.wait;" ::: "memory");
      if (col < 80 && lane < 16) g_mem[(col >> 4) * 2048 + (lane >> 3) * 1024 + 512 + prm.moff + (col & 15) * 8 + (lane & 7)] = make_uint4(~0u, ~0u, ~0u, ~0u);
      uint32_t last = 0;
      if (lane == 0) last = atomicAdd(&g_cnt[C_EXIT * CSTRIDE], 1) == gridDim.x - 1;
      if (__shfl_sync(~0u, last, 0)) {
        g_cnt[C_TICKET * CSTRIDE + lane] = 0;
        for (int i = lane; i < C_USED; i += 32) g_cnt[i * CSTRIDE] = 0;
      }
    }
  } else {
    asm volatile("setmaxnreg.inc.sync.aligned.u32 %0;" ::"n"(GRC));
    const int cw = wid & 7, wk = wid >> 3;
    GIter t(prm, col);
    uint32_t pos = 0, seen = 0, waited = 0;
    uint32_t nsig = 0;
    auto signal = [&](uint32_t msg) {
      mbar_wait(sb + GB_SACK + 8 * wk, (nsig++ & 1) ^ 1);
      if (cw == 0) sts32(sb + GS_SIG + 4 * wk, msg);
      __syncwarp();
      mbar_arrive_if(lane == 0, sb + GB_SIG + 8 * wk);
    };
    if (col < G_EARLY) {
      spin(prm.gd);
#pragma unroll 1
      for (int rg = 96 + col * 2 + wk; rg < 256; rg += 2 * G_EARLY) {
        uint32_t a[10];
        const uint32_t* src = prm.x + (size_t)(rg * 8 + (lane >> 2)) * (DM / 2) + cw * 40 + (lane & 3);
#pragma unroll
        for (int i = 0; i < 10; i++) a[i] = __ldg(src + i * 4);
        first_ln(a, rg, sb + GS_RED + wk * 512, cw, lane, 1 + wk);
        signal((C_XN + (rg >> 4)) | ((XN_TARGET / NF) << 16));
        bar_sync(1 + wk, 256);
      }
    }
    while (t.next(prm, col)) {
      const uint32_t pos0 = pos;
      pos = (pos + t.nkb) % (2 * G_NST);
      if (((t.e >> 29) & 1) != wk) { seen += (t.e >> 30) & 1; continue; }
      const uint32_t type = t.type, blk = t.lb & 15, layer = t.lb >> 4, n0 = t.n0;
      if (cw == 0 && t.valid) GLOG(t.id_(prm.pend), 0, 0x80000000u | type | (t.lb << 3) | (n0 << 8) | (t.nkb << 16));
      if (!t.gemm) {
        if (!t.valid) continue;
        const int rg = blk * 16 + n0;
        float4 v[5];
        const int off = (n0 * 40 + cw * 5) * 32 + lane, npl = t.kb0;
        const uint2* src = acc_planes(t.lb, type == T_F2) + off;
        if (cw == 0) {
          poll_ge(&g_cnt[c_phase(type, t.lb) * CSTRIDE], prm.need[type][t.lb]);
          mbar_arrive_if((t.e & E_EXCL) && lane == 0, sb + GB_GATE + 8 * wk);
          GLOG(t.id_(prm.pend), 2, gtime()); GLOG(t.id_(prm.pend), 3, gtime());
        }
        bar_sync(1 + wk, 256);
        {
          const uint32_t eye = (lane >> 3) == (lane & 3) ? ((lane & 4) ? 0x3f800000u : 0x00003f80u) : 0u;
#pragma unroll
          for (int i = 0; i < 5; i++) v[i] = make_float4(0.f, 0.f, 0.f, 0.f);
#pragma unroll 1
          for (int p0 = 0; p0 < npl; p0 += FPL) {
            uint32_t r[FPL / 2][5][4];
#pragma unroll
            for (int p = 0; p < FPL; p++)
#pragma unroll
              for (int i = 0; i < 5; i++) {
                const uint2 w = p0 + p < npl ? __ldcg(src + (size_t)(p0 + p) * PLANE + i * 32) : make_uint2(0, 0);
                r[p >> 1][i][(p & 1) * 2] = w.x; r[p >> 1][i][(p & 1) * 2 + 1] = w.y;
              }
#pragma unroll
            for (int p = 0; p < FPL / 2; p++) {
              if (p0 + 2 * p >= npl) break;
              if (t.e & E_EXCL) {
#pragma unroll
                for (int i = 0; i < 5; i++) mma16816(&v[i].x, r[p][i], eye, eye);
              } else {
#pragma unroll
                for (int i = 0; i < 5; i++) {
                  const uint32_t* w = r[p][i];
                  v[i].x += blo(w[0]) + blo(w[2]); v[i].y += bhi(w[0]) + bhi(w[2]); v[i].z += blo(w[1]) + blo(w[3]); v[i].w += bhi(w[1]) + bhi(w[3]);
                }
              }
            }
          }
        }
        if (type == T_F2 && layer == 1) {
          uint2* dst = (uint2*)prm.out + (size_t)(rg * 8 + (lane >> 2)) * (DM / 4) + cw * 20 + (lane & 1) * 2 + ((lane >> 1) & 1);
#pragma unroll
          for (int i = 0; i < 5; i++) {
            const uint32_t a = pack2(v[i].x, v[i].y), b = pack2(v[i].z, v[i].w);
            const uint32_t o = __shfl_xor_sync(~0u, (lane & 1) ? a : b, 1);
            dst[i * 4] = (lane & 1) ? make_uint2(o, b) : make_uint2(a, o);
          }
        } else {
          uint2* nx = (type == T_F1 ? acc_planes(t.lb, 1) : acc_planes(NBLK + blk, 0)) + off;
#pragma unroll
          for (int i = 0; i < 5; i++) {
            const uint2 w = make_uint2(pack2(v[i].x, v[i].y), pack2(v[i].z, v[i].w));
            nx[i * 32] = w;
            v[i] = make_float4(blo(w.x), bhi(w.x), blo(w.y), bhi(w.y));
          }
          float mean, rstd;
          ln_stats(v, sb + GS_RED + wk * 512, cw, lane, 1 + wk, mean, rstd);
          if (type == T_F2) store_img<4, 2048>(xn_row_group(1, rg) + lane, v, cw, mean, rstd);
          else store_img<3, 4096>(g_xa + (size_t)(blk * 10 * 4096 + n0 * 256) + lane, v, cw, mean, rstd);
        }
      } else {
        float acc[64];
#pragma unroll
        for (int j = 0; j < 64; j++) acc[j] = 0.f;
        if (waited != seen) { mbar_wait(sb + GB_ORD + 8 * (wk ^ 1), waited & 1); waited++; }
        const uint32_t hand = (t.e & E_HAND) ? sb + GB_ORD + 8 * wk : 0;
        if (!t.valid) { mbar_arrive_if(hand && lane == 0, hand); continue; }
        if (cw == 0) GLOG(t.id_(prm.pend), 3, gtime());
        const uint32_t ph = pos0 >= G_NST, st = pos0 - ph * G_NST, early = (t.e & E_EXCL) ? 0 : hand;
        const bool idle = (t.e & E_HALF) && ((t.e >> 8) & 1) != (cw >> 2);
        if (idle) {
          uint32_t s2 = st, p2 = ph;
#pragma unroll 1
          for (uint32_t kb = 0; kb < t.nkb; kb++) {
            mbar_wait(sb + GB_FULL + 8 * s2, p2);
            mbar_arrive_if(lane == 0, sb + GB_EMPTY + 8 * s2);
            if (++s2 == G_NST) { s2 = 0; p2 ^= 1; }
          }
          mbar_arrive_if(early && lane == 0, early);
        } else if (type == T_A) g_mainloop<1>(acc, sb, early, sb + GB_GATE + 8 * (wk ^ 1), t.nkb, cw, lane, st, ph);
        else g_mainloop<0>(acc, sb, early, sb + GB_GATE + 8 * (wk ^ 1), t.nkb, cw, lane, st, ph);
        if (cw == 0) GLOG(t.id_(prm.pend), 4, gtime());
        if (idle) {
        } else if (type == T_U) {
          uint32_t* dst = g_h + (size_t)((blk * 24 + n0) * 4096 + cw * 512) + lane;
#pragma unroll
          for (int j = 0; j < 8; j++) {
            float h[4];
#pragma unroll
            for (int e = 0; e < 4; e++) {
              float th;
              asm("tanh.approx.f32 %0, %1;" : "=f"(th) : "f"(0.5f * acc[4 * j + e]));
              h[e] = acc[32 + 4 * j + e] * fmaf(th, 0.5f, 0.5f);
            }
            dst[j * 32] = pack2(h[0], h[1]);
            dst[j * 32 + 256] = pack2(h[2], h[3]);
          }
        } else {
          uint2* dst = acc_planes(t.lb, type == T_D) + (size_t)((1 + (n0 >> 3)) * PLANE + (2 * cw * 40 + (n0 & 7) * 8) * 32) + lane;
#pragma unroll
          for (int j = 0; j < 16; j++) {
            const float* a = acc + (j >> 1) * 8 + (j & 1) * 2;
            dst[(j >> 1) * 32 + (j & 1) * 1280] = make_uint2(pack2(a[0], a[1]), pack2(a[4], a[5]));
          }
        }
        mbar_arrive_if(hand != early && lane == 0, hand);
      }
      if (cw == 0) GLOG(t.id_(prm.pend), 5, gtime());
      if (cw == 0) GLOG(t.id_(prm.pend), 6, gtime());
      if (type == T_F2 && layer == 1) mbar_arrive_if((t.e & E_EXCL) && cw == 0 && lane == 0, sb + GB_GATE + 8 * wk);
      else
        signal((type != T_F2 ? c_phase(type + 1, t.lb) | (1 << 16) : (C_XN + NBLK + blk) | ((XN_TARGET / NF) << 16)) | (t.gemm ? 0 : t.e & E_EXCL));
    }
    signal(0);
  }
}

typedef CUresult (*EncodeFn)(CUtensorMap*, CUtensorMapDataType, cuuint32_t, void*, const cuuint64_t*, const cuuint64_t*, const cuuint32_t*,
                             const cuuint32_t*, CUtensorMapInterleave, CUtensorMapSwizzle, CUtensorMapL2promotion, CUtensorMapFloatOOBfill);
static CUtensorMap make_map(EncodeFn fn, const void* p, uint64_t inner, uint64_t outer, uint32_t bi, uint32_t bo, int promo = 3) {
  CUtensorMap m;
  cuuint64_t dims[2] = {inner, outer}, str[1] = {inner * 2};
  cuuint32_t box[2] = {bi, bo}, es[2] = {1, 1};
  fn(&m, CU_TENSOR_MAP_DATA_TYPE_BFLOAT16, 2, (void*)p, dims, str, box, es, CU_TENSOR_MAP_INTERLEAVE_NONE, CU_TENSOR_MAP_SWIZZLE_128B,
     (CUtensorMapL2promotion)promo, CU_TENSOR_MAP_FLOAT_OOB_FILL_NONE);
  return m;
}
struct Tune {
  int lag = 11, excl = 6, gonly = 0, xl = 1, ronly = 0, pn = 30;
  int da = 120, db = 350, dc = 650, dd = 650, d2 = 2170, p1 = 300, p2 = 800;
  int ea = 60, eb = 310, ec = 550, ed = 550, e2 = 2200, q1 = 200, q2 = 400, d3 = 60, moff = 192, ds = 400, dh = 60, pa = 0, pb = 0, pc = 0, pd = 0, pe = 0, pf = 0, pg = 0, ph = 0, wpf = 4, gd = 22000, dq = 300, sl = 18, pr = 2, pg2 = 3;
};
static void fill_r(RParams& p, const Tune& t, int lag, int n0, int n1) {
  r_fill_desc(p);
  p.nslots = 0; p.d3 = t.d3; p.pn = t.pn; p.moff = t.moff; p.ds = t.ds; p.dh = t.dh; p.dq = t.dq;
  for (int c = 0; c < 5; c++) { p.d2[c] = t.d2 + (c == 0 ? 0 : c < 3 ? t.p1 : t.p2); p.d2[5 + c] = t.e2 + (c == 0 ? 0 : c < 3 ? t.q1 : t.q2); }
  const int d1[8] = {t.da, t.db, t.dc, t.dd, t.ea, t.eb, t.ec, t.ed};
  for (int i = 0; i < 8; i++) p.d1[i] = d1[i];
  int last[2] = {0, 0}, n = 0;
  for (int s0 = 0; s0 < NSEG + lag; s0++)
    for (int l = 0; l < 2; l++) {
      const int s = l ? s0 - lag : s0;
      if (s < 0 || s >= NSEG) continue;
      if (n >= n0 && n < n1) { p.slot[p.nslots] = s | (l << 6) | (last[l] << 8) | (((s & 3) == 3 ? C_O + l * NBLK + s / 4 : s == (l ? 61 : 1) ? C_HALF + l * NBLK + s / 4 : 0) << 16); last[l] = ++p.nslots; }
      n++;
    }
  for (int i = 0; i + 1 < p.nslots; i++) if (((p.slot[i] ^ p.slot[i + 1]) >> 6) & 1) p.slot[i] |= 128;
}
static uint32_t g_entry(int grp, int type, int layer, int blk, int i, int ks) {
  int n0 = i, kb0 = 0, kb1 = type == T_U ? 10 : 0;
  if (type == T_F1 || type == T_F2) kb0 = kb1 = ks + 1;
  if (type == T_A || type == T_D) {
    const int KB = type == T_A ? 96 : 24, sp = i / 5;
    n0 = i % 5 | (sp << 3); kb0 = sp * KB / ks; kb1 = (sp + 1) * KB / ks;
  }
  return type | (layer << 3) | (blk << 4) | (n0 << 9) | (kb0 << 16) | ((kb1 - kb0) << 23) | (grp ? E_GRP : 0);
}
static bool g_is_gemm(uint32_t e) { return (e & 7) == T_A || (e & 7) == T_U || (e & 7) == T_D; }
static void g_handover(uint32_t* e, int len) {
  uint32_t next = 0;
  for (int i = len - 1; i >= 0; i--)
    if (g_is_gemm(e[i])) { if ((e[i] & E_GRP) != next) e[i] |= E_HAND; next = e[i] & E_GRP; }
}
static bool g_overflow = false;
struct GList {
  static void overflow() { g_overflow = true; }
  bool shared = false;
  GParams& g; uint32_t* tab; int ncol, stride, len, n[G_LATE], load[G_LATE], grp[G_LATE];
  GList(GParams& g_, uint32_t* t, int nc, int st, int l) : g(g_), tab(t), ncol(nc), stride(st), len(l) { for (int c = 0; c < nc; c++) { n[c] = load[c] = 0; grp[c] = 1; } }
  void add(int type, int lb, int ks, int c0, int c1, uint32_t flags = 0, int i0 = 0, int i1 = 999, int step = 1) {
    const int half = (flags & E_HALF) != 0, ln = type == T_F1 || type == T_F2;
    const int cnt = (type == T_U ? 24 : ln ? NF : 5 * ks) << half;
    if (type < T_F2) g.need[type + 1][lb] = cnt;
    int used[G_LATE] = {0};
    for (int i = i0; i < cnt && i < i1; i += step) {
      int best = c0;
      for (int c = c0; c < c1; c++) if (used[c] < used[best] || (used[c] == used[best] && load[c] < load[best])) best = c;
      used[best]++;
      if (!ln) grp[best] ^= 1;
      const uint32_t e = g_entry(grp[best], type, lb >> 4, lb & 15, i >> half, ks) | flags | (ln && !shared ? E_EXCL : 0) | ((i & half) ? E_UP : 0);
      if (n[best] >= len) { overflow(); return; }
      tab[best * stride + n[best]++] = e;
      load[best] += (((e >> 23) & 31) >> half) + 2;
    }
  }
  void put(int c, uint32_t e) { if (n[c] >= len) { overflow(); return; } tab[c * stride + n[c]++] = e; if (g_is_gemm(e)) grp[c] = (e & E_GRP) != 0; }
  void finish() { for (int c = 0; c < ncol; c++) g_handover(tab + c * stride, len); }
};
static void fill_g(GParams& g, const Tune& t, void* out) {
  g.out = (__nv_bfloat16*)out;  g.pend = NBLK - 2;
  for (int b = 0; b < 2 * NBLK; b++) {
    g.need[T_A][b] = 96; g.need[T_F1][b] = 20; g.need[T_U][b] = NF; g.need[T_D][b] = 32; g.need[T_F2][b] = 15;
  }
  {
    const uint8_t perm[G_EARLY] = {0, 1, 2, 3, 16, 17, 18, 19, 34, 35, 4, 20, 21, 15, 22, 23, 5, 6, 7, 8, 9, 24, 25, 26, 10, 11, 12, 13, 14, 27, 28, 29, 30, 31, 32, 33};
    const uint8_t first[9] = {0, 10, 13, 16, 20, 24, 28, 32, 36};
    const int* pk = &t.pa;
    for (int i = 0; i < G_EARLY; i++) g.perm[i] = t.pa ? (pk[i / 5] >> (6 * (i % 5))) & 63 : perm[i];
    for (int i = 0; i < 9; i++) g.first[i] = first[i];
  }
  for (uint32_t& e : g.tab) e = T_NONE;
  GList pr(g, g.tab, G_EARLY, EL, PL);
  pr.add(T_A, 0, 7, 1, 36, E_HALF, 0, 999, 2); pr.add(T_A, 0, 7, 1, 36, E_HALF, 1, 999, 2); pr.add(T_F1, 0, 7, 20, 36); pr.add(T_U, 0, 0, 12, 36);
  pr.add(T_D, 0, 3, 20, 36); pr.add(T_F2, 0, 3, 20, 36);
  pr.finish();
  const int d = 3;
  const uint32_t xa = (t.excl & 1) ? E_EXCL : 0, xu = (t.excl & 2) ? E_EXCL : 0, xd = (t.excl & 4) ? E_EXCL : 0;
  for (int c = 0; c < G_EARLY; c++) {
    uint32_t* e = g.tab + c * EL + PL;
    if (c < 20) {
      *e++ = (g_entry(0, T_A, 0, 0, c, 4) | xa) - (c < 5 ? 1 << 23 : 1 << 16) + (c >= 15 ? 1 << 23 : 0);
      if (c < NF) *e++ = g_entry(0, T_F1, 0, 0, c, 4) | ((t.xl & 1) ? E_EXCL : 0);
      *e++ = g_entry(1, T_A, 1, d, c, 4);
      if (c >= 20 - NF) *e++ = g_entry(1, T_F1, 1, d, c - (20 - NF), 4);
    } else {
      const int j = c - 20;
      const uint32_t hf = E_HALF | ((j & 1) ? E_UP : 0);
      *e++ = g_entry(0, T_U, 0, 0, j, 0);
      *e++ = g_entry(1, T_U, 0, 0, 16 + j / 2, 0) | hf | xu;
      *e++ = g_entry(1, T_U, 1, d + 1, 16 + j / 2, 0) | hf;
      if (j < 15) *e++ = g_entry(1, T_D, 0, 0, j, 3) | xd;
      *e++ = g_entry(1, T_F2, 0, 0, j, 3) | ((t.xl & 2) ? E_EXCL : 0);
      if (j < 15) *e++ = g_entry(0, T_D, 1, d + 1, j, 3);
      *e++ = g_entry(0, T_U, 1, d, j, 0);
      *e++ = g_entry(1, T_F2, 1, d + 1, j, 3);
    }
    g_handover(g.tab + c * EL + PL, ML);
  }
  GList dr(g, g.tab + PL + ML, G_EARLY, EL, DL);
  GList tl(g, g.tab + TAB_TAIL, G_LATE, TL, TL);
  const int L1 = NBLK;
  auto ufull = [&](int lb, uint32_t fl) { dr.add(T_U, lb, 0, 20, 36, fl, 0, 16); g.need[T_D][lb] = 32; };
  auto uhalf = [&](int lb, int c0, uint32_t fl) { dr.add(T_U, lb, 0, c0, 36, E_HALF | fl, 32); g.need[T_D][lb] = 32; };
  for (int c = 0; c < G_EARLY; c++)
    for (int i = 0; i < ML; i++) {
      uint32_t e = g.tab[c * EL + PL + i] & ~E_HAND;
      const uint32_t ty = e & 7;
      if (ty == T_NONE || ((e & 8) && (ty == T_F2 || (ty == T_U && !(e & E_HALF))))) continue;
      e = (e & ~0xf0u) | (14 - ((e >> 4) & 15)) << 4;
      dr.put(c, e | (ty == T_F2 ? E_EXCL : 0));
    }
  dr.add(T_A, 15, 4, 0, 20, E_EXCL);
  dr.add(T_F1, 15, 4, 4, 20);
  dr.add(T_U, 15, 0, 12, 36, E_EXCL);
  for (int c = 0; c < 20; c++) {
    const int tile = c % 5, sp = c / 5, len = tile < 2 ? (96 - t.sl) / 3 : 48 - t.sl, nl = tile < 2 ? 3 : 2;
    const int k0 = sp <= nl ? sp * len : nl * len + t.sl, nk = sp < nl ? len : sp == 3 ? 96 - k0 : t.sl;
    dr.put(c, (g_entry(dr.grp[c] ^ 1, T_A, 1, 12, c, 4) & ~0x0fff0000u) | k0 << 16 | nk << 23);
  }
  dr.add(T_F1, L1 + 12, 4, 0, 16);
  dr.add(T_A, L1 + 13, 4, 0, 20);
  dr.add(T_D, 15, 3, 20, 36, E_EXCL); dr.add(T_F2, 15, 3, 20, 36);
  ufull(L1 + 11, 0); uhalf(L1 + 11, 20, 0);
  dr.add(T_A, L1 + 14, 4, 0, 20, E_EXCL);
  dr.add(T_F1, L1 + 13, 4, 0, 20);
  dr.add(T_D, L1 + 11, 3, 20, 36);
  ufull(L1 + 12, E_UP); uhalf(L1 + 12, 12, E_EXCL);
  dr.add(T_A, L1 + 15, 7, 0, 35, E_HALF | E_EXCL, 0, 999, 2); dr.add(T_A, L1 + 15, 7, 0, 35, E_HALF | E_EXCL, 1, 999, 2);
  dr.add(T_F1, L1 + 15, 7, 20, 36);
  dr.add(T_F2, L1 + 10, 3, 0, 20);
  dr.shared = true; dr.add(T_F2, L1 + 11, 3, 4, 20); dr.shared = false;
  dr.add(T_D, L1 + 13, 3, 4, 20, E_UP);
  dr.add(T_F2, L1 + 12, 3, 0, 20);
  dr.finish();
  tl.add(T_D, L1 + 12, 3, 72, G_LATE);
  tl.add(T_U, L1 + 13, 0, 24, 48, E_EXCL);
  tl.add(T_F1, L1 + 14, 4, 0, 48);
  tl.add(T_U, L1 + 14, 0, 0, 24);
  tl.add(T_D, L1 + 14, 4, 0, 48, E_HALF | E_EXCL);
  tl.add(T_U, L1 + 15, 0, 48, G_LATE, E_HALF);
  tl.add(T_D, L1 + 15, 4, 48, G_LATE, E_HALF);
  tl.add(T_F2, L1 + 13, 3, 48, 72);
  tl.add(T_F2, L1 + 14, 4, 0, 48);
  tl.add(T_F2, L1 + 15, 4, 48, G_LATE);
  tl.finish();
}
static void launch_all(void* const* d_in, void* d_out, const Tune& t, cudaStream_t st) {
  static EncodeFn fn = nullptr;
  if (!fn) {
    void* f = nullptr;
    cudaDriverEntryPointQueryResult qr;
    cudaGetDriverEntryPoint("cuTensorMapEncodeTiled", &f, cudaEnableDefault, &qr);
    fn = (EncodeFn)f;
    cudaFuncSetAttribute(r_kernel, cudaFuncAttributeMaxDynamicSharedMemorySize, R_SMEM);
    cudaFuncSetAttribute(g_kernel, cudaFuncAttributeMaxDynamicSharedMemorySize, G_SMEM);
  }
  const CUtensorMap mq = make_map(fn, d_in[2], HD, DM, 64, 128, t.pr), mk = make_map(fn, d_in[3], HD, DM, 64, 128, t.pr), mv = make_map(fn, d_in[4], HD, DM, 64, 128, t.pr),
                    mo = make_map(fn, d_in[5], DM, HD, 64, 64, t.pg2), mg = make_map(fn, d_in[8], FF, DM, 64, 64, t.pg2), mu = make_map(fn, d_in[9], FF, DM, 64, 64, t.pg2),
                    md = make_map(fn, d_in[10], DM, FF, 64, 64, t.pg2);
  auto launch_r = [&](int lag, int n0, int n1) {
    RParams p;
    fill_r(p, t, lag, n0, n1);
    p.mem0 = (const uint4*)d_in[1]; p.x = (const uint32_t*)d_in[0]; p.pf = t.wpf;
    cudaLaunchConfig_t cfg = {};
    cfg.gridDim = dim3(3, NH); cfg.blockDim = dim3(512); cfg.dynamicSmemBytes = R_SMEM; cfg.stream = st;
    cudaLaunchAttribute at[1];
    at[0].id = cudaLaunchAttributeClusterDimension; at[0].val.clusterDim.x = 3; at[0].val.clusterDim.y = 1; at[0].val.clusterDim.z = 1;
    cfg.attrs = at; cfg.numAttrs = 1;
    cudaLaunchKernelEx(&cfg, r_kernel, mq, mk, mv, mo, p);
  };
  auto launch_g = [&](const GParams& g, bool pdl) {
    cudaLaunchConfig_t cfg = {};
    cfg.gridDim = dim3(132); cfg.blockDim = dim3(640); cfg.dynamicSmemBytes = G_SMEM; cfg.stream = st;
    cudaLaunchAttribute at[2];
    at[0].id = cudaLaunchAttributeProgrammaticStreamSerialization; at[0].val.programmaticStreamSerializationAllowed = 1;
    cfg.attrs = at; cfg.numAttrs = pdl ? 1 : 0;
    cudaLaunchKernelEx(&cfg, g_kernel, mo, mg, mu, md, g);
  };
  GParams g;
  fill_g(g, t, d_out);
  g.moff = t.moff; g.gd = t.gd; g.x = (const uint32_t*)d_in[0];
  launch_r(t.lag, 0, 2 * NSEG);
  launch_g(g, true);
}

extern "C" void kernel_launch(void* const* d_in, const int* in_sizes, int n_in, void* d_out, int out_size) {
  launch_all(d_in, d_out, Tune(), cudaStreamPerThread);
}
```
